```python
import torch

def _softmax(x, axis=-1):
    return torch.softmax(x, dim=axis)

def _gelu(x):
    return torch.nn.functional.gelu(x, approximate='tanh')

def _silu(x):
    return torch.nn.functional.silu(x)

def _sigmoid(x):
    return torch.sigmoid(x)

def _layernorm(x, axis=-1, eps=1e-05):
    m = x.mean(dim=axis, keepdim=True)
    v = x.var(dim=axis, keepdim=True, unbiased=False)
    return (x - m) / torch.sqrt(v + eps)

def _scatter_add(tgt, idx, src, axis=0):
    return tgt.clone().index_add_(axis, idx, src)

def _segment_sum(src, seg, n):
    out = torch.zeros((n,) + src.shape[1:], dtype=src.dtype)
    return out.index_add_(0, seg, src)

def _pad(x, pw):
    flat = tuple((v for pair in reversed(pw) for v in pair))
    return torch.nn.functional.pad(x, flat)
kernel_name = 'gated_mix__memory_aug_recurrent_mem_tr__sliding_block__prompt'

def setup_inputs():

    _w = lambda a: (lambda t: t.to(torch.bfloat16) if t.is_floating_point() else t)(torch.as_tensor(a))

    def _A_setup():
        B, S, Dm = (1, 2048, 576)
        H, Dh = (32, 128)
        M, seg = (8, 32)
        seg = min(seg, S)
        S = S // seg * seg
        return {'x': _w((lambda *s: torch.randn(*s, dtype=torch.bfloat16) * 0.05)(B, S, Dm)), 'mem0': _w((lambda *s: torch.randn(*s, dtype=torch.bfloat16) * 1.6)(B, M, Dm)), 'Wq': _w((lambda *s: torch.randn(*s, dtype=torch.bfloat16) * 0.8)(Dm, H, Dh) * Dm ** (-0.5)), 'Wk': _w((lambda *s: torch.randn(*s, dtype=torch.bfloat16) * 0.8)(Dm, H, Dh) * Dm ** (-0.5)), 'Wv': _w((lambda *s: torch.randn(*s, dtype=torch.bfloat16) * 1.6)(Dm, H, Dh) * Dm ** (-0.5)), 'Wo': _w((lambda *s: torch.randn(*s, dtype=torch.bfloat16) * 1.6)(H, Dh, Dm) * (H * Dh) ** (-0.5)), 'seg_len': seg}
    _A_in = _A_setup()

    def _B_setup():
        B, S, D = (1, 2048, 576)
        return {'x': _w((lambda *s: torch.randn(*s, dtype=torch.bfloat16) * 0.05)(B, S, D)), 'wqkv': _w((lambda *s: torch.randn(*s, dtype=torch.bfloat16) * 1.6)(D, 3 * D)), 'wo': _w((lambda *s: torch.randn(*s, dtype=torch.bfloat16) * 0.05)(D, D))}
    _B_in = _B_setup()
    return {'A_x': _A_in['x'], 'A_mem0': _A_in['mem0'], 'A_Wq': _A_in['Wq'], 'A_Wk': _A_in['Wk'], 'A_Wv': _A_in['Wv'], 'A_Wo': _A_in['Wo'], 'A_seg_len': _A_in['seg_len'], 'B_x': _B_in['x'], 'B_wqkv': _B_in['wqkv'], 'B_wo': _B_in['wo'], 'gate_w': _w((lambda *s: torch.randn(*s, dtype=torch.bfloat16) * 0.05)(576) * 16.0)}

def reference(A_x, A_mem0, A_Wq, A_Wk, A_Wv, A_Wo, A_seg_len, B_x, B_wqkv, B_wo, gate_w):

    def _A_ref(x, mem0, Wq, Wk, Wv, Wo, seg_len):
        B, S, Dm = x.shape
        H, Dh = (Wq.shape[1], Wq.shape[2])
        M = mem0.shape[1]
        scale = Dh ** (-0.5)
        n_seg = S // seg_len
        L = M + seg_len
        idx = torch.arange(L)
        mask = (idx[:, None] < M) | (idx[:, None] >= idx[None, :])
        mem = mem0
        outs = []
        for s in range(n_seg):
            xs = x[:, s * seg_len:(s + 1) * seg_len, :].clone()
            h = torch.concatenate([mem, xs], axis=1)
            q = torch.einsum('btd,dhe->bhte', h, Wq)
            k = torch.einsum('btd,dhe->bhte', h, Wk)
            v = torch.einsum('btd,dhe->bhte', h, Wv)
            scores = torch.einsum('bhqe,bhke->bhqk', q, k) * scale
            scores = torch.where(mask[None, None], scores, -1000000000.0)
            p = _softmax(scores, axis=-1)
            o = torch.einsum('bhqk,bhke->bhqe', p, v)
            o = torch.einsum('bhte,hed->btd', o, Wo)
            mem = o[:, :M, :].clone()
            outs.append(o[:, M:, :])
        return torch.concatenate(outs, axis=1)

    def _B_ref(x, wqkv, wo):
        B, S, D = x.shape
        H = 32
        Dh = D // H
        W = 256
        qkv = (lambda x, *d: x.permute(*d))((x @ wqkv).reshape(B, S, 3, H, Dh), 2, 0, 3, 1, 4)
        q, k, v = (qkv[0], qkv[1], qkv[2])
        scores = torch.einsum('bhqd,bhkd->bhqk', q, k) * Dh ** (-0.5)
        idx = torch.arange(S)
        mask = (idx[:, None] - idx[None, :] >= 0) & (idx[:, None] - idx[None, :] < W)
        scores = torch.where(mask[None, None], scores, -1000000000.0)
        p = _softmax(scores, axis=-1)
        o = torch.einsum('bhqk,bhkd->bhqd', p, v)
        return (lambda x, *d: x.permute(*d))(o, 0, 2, 1, 3).reshape(B, S, D) @ wo
    x = A_x
    g = _sigmoid((x * gate_w).sum(-1, keepdims=True))
    a = _A_ref(x, A_mem0, A_Wq, A_Wk, A_Wv, A_Wo, A_seg_len)
    b = _B_ref(x, B_wqkv, B_wo)
    return g * a + (1 - g) * b
```

```cpp
#include <cuda_runtime.h>
#include <cuda_bf16.h>
#include <cuda_fp16.h>
#include <cuda.h>
#include <stdint.h>

typedef __nv_bfloat16 bf16;

constexpr int SEQ = 2048, DM = 576, NH = 32, DH = 128, NMEM = 8, SEG = 32, NSEG = 64;
constexpr int HD = NH * DH;
constexpr int OK = HD + DM;
constexpr int BH = 32, BD = 18, BDP = 24, WIN = 256;

__device__ bf16 g_O[SEQ * OK];
__device__ bf16 g_qkvB[SEQ * 3 * DM];
__device__ float g_acc[SEQ * DM];
__device__ float g_gate[SEQ];
__device__ float g_red[8 * 192 * 256];
__device__ uint4 g_redh[8 * 96 * 72];
__device__ unsigned g_sync[32];
__device__ unsigned g_ctr[512];
#define PROF(i)
#define PROFT(i, th)
#define PROFW(i)
#define PROFDUMP()

__device__ __forceinline__ uint32_t s2u(const void* p) { return (uint32_t)__cvta_generic_to_shared(p); }
__device__ __forceinline__ uint32_t mapa(uint32_t a, uint32_t r) {
    uint32_t o; asm volatile("mapa.shared::cluster.u32 %0,%1,%2;" : "=r"(o) : "r"(a), "r"(r)); return o;
}
__device__ __forceinline__ void mbar_init(uint32_t a, int c) {
    asm volatile("mbarrier.init.shared::cta.b64 [%0],%1;" ::"r"(a), "r"(c) : "memory");
}
__device__ __forceinline__ void mbar_expect(uint32_t a, int bytes) {
    asm volatile("mbarrier.arrive.expect_tx.shared::cta.b64 _,[%0],%1;" ::"r"(a), "r"(bytes) : "memory");
}
__device__ __forceinline__ void mbar_arrive(uint32_t a) {
    asm volatile("mbarrier.arrive.shared::cta.b64 _,[%0];" ::"r"(a) : "memory");
}
__device__ __forceinline__ bool mbar_try(uint32_t a, int ph) {
    uint32_t ok;
    asm volatile("{.reg .pred p; mbarrier.try_wait.parity.shared::cta.b64 p,[%1],%2; selp.u32 %0,1,0,p;}"
                 : "=r"(ok) : "r"(a), "r"(ph) : "memory");
    return ok;
}
__device__ __forceinline__ bool mbar_try_cl(uint32_t a, int ph) {
    uint32_t ok;
    asm volatile("{.reg .pred p; mbarrier.try_wait.parity.acquire.cluster.shared::cta.b64 p,[%1],%2; selp.u32 %0,1,0,p;}"
                 : "=r"(ok) : "r"(a), "r"(ph) : "memory");
    return ok;
}
__device__ __forceinline__ void mbar_wait(uint32_t a, int ph) {
    asm volatile("{.reg .pred p; .reg .u32 n; mov.u32 n,0;\n"
                 "WL%=: mbarrier.try_wait.parity.shared::cta.b64 p,[%0],%1; @p bra.uni WD%=;\n"
                 "add.u32 n,n,1; setp.lt.u32 p,n,4194304; @p bra.uni WL%=; trap;\n"
                 "WD%=: }" ::"r"(a), "r"(ph) : "memory");
}
__device__ __forceinline__ void mbar_wait_cl(uint32_t a, int ph) {
    int it = 0;
    while (!mbar_try_cl(a, ph)) { if (++it > (1 << 22)) __trap(); }
}
__device__ __forceinline__ void bar_sync(int id, int n) { asm volatile("bar.sync %0,%1;" ::"r"(id), "r"(n) : "memory"); }
__device__ __forceinline__ void bar_arrive(int id, int n) { asm volatile("bar.arrive %0,%1;" ::"r"(id), "r"(n) : "memory"); }
__device__ __forceinline__ void cluster_sync() {
    asm volatile("barrier.cluster.arrive.release.aligned; barrier.cluster.wait.acquire.aligned;" ::: "memory");
}
__device__ __forceinline__ void fence_async() { asm volatile("fence.proxy.async.shared::cta;" ::: "memory"); }
__device__ __forceinline__ void ldsm4(uint32_t* r, uint32_t a) {
    asm volatile("ldmatrix.sync.aligned.m8n8.x4.shared.b16 {%0,%1,%2,%3},[%4];"
                 : "=r"(r[0]), "=r"(r[1]), "=r"(r[2]), "=r"(r[3]) : "r"(a) : "memory");
}
__device__ __forceinline__ void ldsm4t(uint32_t* r, uint32_t a) {
    asm volatile("ldmatrix.sync.aligned.m8n8.x4.trans.shared.b16 {%0,%1,%2,%3},[%4];"
                 : "=r"(r[0]), "=r"(r[1]), "=r"(r[2]), "=r"(r[3]) : "r"(a) : "memory");
}
__device__ __forceinline__ void ldsm2(uint32_t* r, uint32_t a) {
    asm volatile("ldmatrix.sync.aligned.m8n8.x2.shared.b16 {%0,%1},[%2];" : "=r"(r[0]), "=r"(r[1]) : "r"(a) : "memory");
}
__device__ __forceinline__ void ldsm2t(uint32_t* r, uint32_t a) {
    asm volatile("ldmatrix.sync.aligned.m8n8.x2.trans.shared.b16 {%0,%1},[%2];" : "=r"(r[0]), "=r"(r[1]) : "r"(a) : "memory");
}
__device__ __forceinline__ void mma16(float* c, const uint32_t* a, uint32_t b0, uint32_t b1) {
    asm("mma.sync.aligned.m16n8k16.row.col.f32.bf16.bf16.f32 {%0,%1,%2,%3},{%4,%5,%6,%7},{%8,%9},{%0,%1,%2,%3};"
                 : "+f"(c[0]), "+f"(c[1]), "+f"(c[2]), "+f"(c[3])
                 : "r"(a[0]), "r"(a[1]), "r"(a[2]), "r"(a[3]), "r"(b0), "r"(b1));
}
__device__ __forceinline__ void mma16v(float* c, const uint32_t* a, uint32_t b0, uint32_t b1) {
    asm volatile("mma.sync.aligned.m16n8k16.row.col.f32.bf16.bf16.f32 {%0,%1,%2,%3},{%4,%5,%6,%7},{%8,%9},{%0,%1,%2,%3};"
                 : "+f"(c[0]), "+f"(c[1]), "+f"(c[2]), "+f"(c[3])
                 : "r"(a[0]), "r"(a[1]), "r"(a[2]), "r"(a[3]), "r"(b0), "r"(b1));
}
__device__ __forceinline__ void mma8(float* c, uint32_t a0, uint32_t a1, uint32_t b0) {
    asm("mma.sync.aligned.m16n8k8.row.col.f32.bf16.bf16.f32 {%0,%1,%2,%3},{%4,%5},{%6},{%0,%1,%2,%3};"
                 : "+f"(c[0]), "+f"(c[1]), "+f"(c[2]), "+f"(c[3]) : "r"(a0), "r"(a1), "r"(b0));
}
__device__ __forceinline__ uint32_t pack2(float lo, float hi) {
    uint32_t r; asm("cvt.rn.bf16x2.f32 %0,%1,%2;" : "=r"(r) : "f"(hi), "f"(lo)); return r;
}
__device__ __forceinline__ float ex2(float x) { float y; asm("ex2.approx.ftz.f32 %0,%1;" : "=f"(y) : "f"(x)); return y; }
__device__ __forceinline__ void sts32(uint32_t a, uint32_t v) { asm volatile("st.shared.u32 [%0],%1;" ::"r"(a), "r"(v) : "memory"); }
__device__ __forceinline__ void sts32f(uint32_t a, float v) { asm volatile("st.shared.f32 [%0],%1;" ::"r"(a), "f"(v) : "memory"); }
__device__ __forceinline__ void sts128(uint32_t a, const uint32_t* v) {
    asm volatile("st.shared.v4.u32 [%0],{%1,%2,%3,%4};" ::"r"(a), "r"(v[0]), "r"(v[1]), "r"(v[2]), "r"(v[3]) : "memory");
}
__device__ __forceinline__ void lds128(uint32_t* v, uint32_t a) {
    asm volatile("ld.shared.v4.u32 {%0,%1,%2,%3},[%4];" : "=r"(v[0]), "=r"(v[1]), "=r"(v[2]), "=r"(v[3]) : "r"(a) : "memory");
}
__device__ __forceinline__ float2 lds64f(uint32_t a) {
    float2 v; asm volatile("ld.shared.v2.f32 {%0,%1},[%2];" : "=f"(v.x), "=f"(v.y) : "r"(a) : "memory"); return v;
}
__device__ __forceinline__ void tma2d(uint32_t dst, const CUtensorMap* m, int c0, int c1, uint32_t bar) {
    asm volatile("cp.async.bulk.tensor.2d.shared::cluster.global.mbarrier::complete_tx::bytes [%0],[%1,{%3,%4}],[%2];"
                 ::"r"(dst), "l"(m), "r"(bar), "r"(c0), "r"(c1) : "memory");
}
__device__ __forceinline__ void tma2d_mc(uint32_t dst, const CUtensorMap* m, int c0, int c1, uint32_t bar, uint16_t mask) {
    asm volatile("cp.async.bulk.tensor.2d.shared::cluster.global.mbarrier::complete_tx::bytes.multicast::cluster [%0],[%1,{%3,%4}],[%2],%5;"
                 ::"r"(dst), "l"(m), "r"(bar), "r"(c0), "r"(c1), "h"(mask) : "memory");
}
__device__ __forceinline__ uint64_t desc_sw128(uint32_t addr, uint32_t lbo, uint32_t sbo) {
    return (uint64_t)((addr & 0x3FFFF) >> 4) | ((uint64_t)(lbo >> 4) << 16) | ((uint64_t)(sbo >> 4) << 32) | (1ull << 62);
}
__device__ __forceinline__ void wg_fence() { asm volatile("wgmma.fence.sync.aligned;" ::: "memory"); }
__device__ __forceinline__ void wg_commit() { asm volatile("wgmma.commit_group.sync.aligned;" ::: "memory"); }
template <int N> __device__ __forceinline__ void wg_wait() { asm volatile("wgmma.wait_group.sync.aligned %0;" ::"n"(N) : "memory"); }

__device__ __forceinline__ void wgmma_rs_n32(float* d, const uint32_t* a, uint32_t dlo, int acc) {
    asm volatile("{.reg .pred p; .reg .b64 dd; setp.ne.b32 p,%21,0; mov.b64 dd,{%20,0x40000040};\n"
                 "wgmma.mma_async.sync.aligned.m64n32k16.f32.bf16.bf16 "
                 "{%0,%1,%2,%3,%4,%5,%6,%7,%8,%9,%10,%11,%12,%13,%14,%15},{%16,%17,%18,%19},dd,p,1,1,0;}"
                 : "+f"(d[0]), "+f"(d[1]), "+f"(d[2]), "+f"(d[3]), "+f"(d[4]), "+f"(d[5]), "+f"(d[6]), "+f"(d[7]),
                   "+f"(d[8]), "+f"(d[9]), "+f"(d[10]), "+f"(d[11]), "+f"(d[12]), "+f"(d[13]), "+f"(d[14]), "+f"(d[15])
                 : "r"(a[0]), "r"(a[1]), "r"(a[2]), "r"(a[3]), "r"(dlo), "r"(acc));
}

#define R8(b) "+f"(d[b]), "+f"(d[b + 1]), "+f"(d[b + 2]), "+f"(d[b + 3]), "+f"(d[b + 4]), "+f"(d[b + 5]), "+f"(d[b + 6]), "+f"(d[b + 7])
__device__ __forceinline__ void wgmma_ss_n192(float* d, uint64_t da, uint64_t db, int acc) {
    asm volatile("{.reg .pred p; setp.ne.b32 p,%98,0;\n"
                 "wgmma.mma_async.sync.aligned.m64n192k16.f32.bf16.bf16 "
                 "{%0,%1,%2,%3,%4,%5,%6,%7,%8,%9,%10,%11,%12,%13,%14,%15,%16,%17,%18,%19,%20,%21,%22,%23,"
                 "%24,%25,%26,%27,%28,%29,%30,%31,%32,%33,%34,%35,%36,%37,%38,%39,%40,%41,%42,%43,%44,%45,%46,%47,"
                 "%48,%49,%50,%51,%52,%53,%54,%55,%56,%57,%58,%59,%60,%61,%62,%63,%64,%65,%66,%67,%68,%69,%70,%71,"
                 "%72,%73,%74,%75,%76,%77,%78,%79,%80,%81,%82,%83,%84,%85,%86,%87,%88,%89,%90,%91,%92,%93,%94,%95},"
                 "%96,%97,p,1,1,0,1;}"
                 : R8(0), R8(8), R8(16), R8(24), R8(32), R8(40), R8(48), R8(56), R8(64), R8(72), R8(80), R8(88)
                 : "l"(da), "l"(db), "r"(acc));
}

#define WCH 6
#define FA 0
#define QCH 2
#define WO_PRE3 3
#define WO_PRE 8
#define WO_PRE2 2
constexpr int MP = 1168;
constexpr int XT = 36864;
constexpr int XR_STAGE = 14 * 1024;
constexpr int MR_STAGE = 14 * 256;
constexpr int SM_X = 0;
constexpr int SM_XR = 2 * XT;
constexpr int SM_MR = SM_XR + 3 * XR_STAGE;
constexpr int SM_MEM = SM_MR + 3 * MR_STAGE;
constexpr int SM_SC = SM_MEM + 8 * MP;
constexpr int SM_OB = SM_SC + 3 * 1536;
constexpr int SM_WO = SM_OB + 2048;
constexpr int SM_BAR = SM_WO + 49152;
constexpr int REC_SMEM = SM_BAR + 512 + 1024;

__device__ uint4 g_xr[NSEG * NH * 24 * 64];
__device__ uint4 g_mr[NSEG * NH * 24 * 16];
__device__ unsigned g_flagA[NSEG];

constexpr int F_FIRST_SPLIT = 9;
struct RecParams {
    const bf16* mem0; const bf16* Wq; const bf16* Wk; const bf16* Wv; const bf16* Wo;
    int d0, dd, dsend;
};

__device__ __forceinline__ float* red_line(int s, int line) { return g_red + ((s >> 3) * 192 + line) * 256 + (s & 7) * 32; }

#define PIN(x) asm volatile("" : "+r"(x))
#define PINL(x) asm volatile("" : "+l"(x))
__device__ __forceinline__ float4 ld_relaxed4(const float* q) {
    float4 v;
    asm volatile("ld.relaxed.gpu.global.v4.f32 {%0,%1,%2,%3},[%4];" : "=f"(v.x), "=f"(v.y), "=f"(v.z), "=f"(v.w) : "l"(q) : "memory");
    return v;
}
__device__ __forceinline__ void reld_relaxed4(float4& v, const float* q) {
    asm volatile("{.reg .pred p; setp.neu.f32 p,%3,0f42000000;\n"
                 "@p ld.relaxed.gpu.global.v4.f32 {%0,%1,%2,%3},[%4];}"
                 : "+f"(v.x), "+f"(v.y), "+f"(v.z), "+f"(v.w) : "l"(q) : "memory");
}
__device__ __forceinline__ unsigned ld_relaxed1(const unsigned* q) {
    unsigned v; asm volatile("ld.relaxed.gpu.global.u32 %0,[%1];" : "=r"(v) : "l"(q) : "memory"); return v;
}
__device__ __forceinline__ uint4 ld_relaxed4u(const uint4* q) {
    uint4 v;
    asm volatile("ld.relaxed.gpu.global.v4.u32 {%0,%1,%2,%3},[%4];" : "=r"(v.x), "=r"(v.y), "=r"(v.z), "=r"(v.w) : "l"(q) : "memory");
    return v;
}
__device__ __forceinline__ void reld_relaxed4u(uint4& v, const uint4* q) {
    asm volatile("{.reg .pred p; .reg .b32 q; and.b32 q,%3,0xffff; setp.ne.u32 p,q,0x5000;\n"
                 "@p ld.relaxed.gpu.global.v4.u32 {%0,%1,%2,%3},[%4];}"
                 : "+r"(v.x), "+r"(v.y), "+r"(v.z), "+r"(v.w) : "l"(q) : "memory");
}
__device__ __forceinline__ uint32_t packh2(float lo, float hi) {
    uint32_t r; asm("cvt.rn.f16x2.f32 %0,%1,%2;" : "=r"(r) : "f"(hi), "f"(lo)); return r;
}
__device__ __forceinline__ float maxn(float a, float b) {
    float r; asm("max.NaN.f32 %0,%1,%2;" : "=f"(r) : "f"(fabsf(a)), "f"(fabsf(b))); return r;
}
__device__ __forceinline__ void redh4(uint4* q, const float* v, uint32_t tag) {
    asm volatile("red.relaxed.gpu.global.add.noftz.v4.f16x2 [%0],{%1,%2,%3,%4};"
                 ::"l"(q), "r"(packh2(v[0], v[1])), "r"(packh2(v[2], v[3])), "r"(packh2(v[4], v[5])), "r"(tag) : "memory");
}
__device__ __forceinline__ void red4(float* q, float a, float b, float c2, float d) {
    asm volatile("red.relaxed.gpu.global.add.v4.f32 [%0],{%1,%2,%3,%4};" ::"l"(q), "f"(a), "f"(b), "f"(c2), "f"(d) : "memory");
}
__device__ __forceinline__ unsigned clk32() { return (unsigned)clock64(); }
__device__ __forceinline__ unsigned gtime() { unsigned v; asm volatile("mov.u32 %0,%%globaltimer_lo;" : "=r"(v)); return v; }
__device__ __forceinline__ float rcp_fast(float x) { float y; asm("rcp.approx.ftz.f32 %0,%1;" : "=f"(y) : "f"(x)); return y; }
__device__ __forceinline__ void bulk_store(void* gdst, uint32_t src, int bytes) {
    asm volatile("cp.async.bulk.global.shared::cta.bulk_group [%0],[%1],%2;" ::"l"(gdst), "r"(src), "r"(bytes) : "memory");
}
__device__ __forceinline__ void bulk_load(uint32_t dst, const void* gsrc, int bytes, uint32_t bar) {
    asm volatile("cp.async.bulk.shared::cluster.global.mbarrier::complete_tx::bytes [%0],[%1],%2,[%3];"
                 ::"r"(dst), "l"(gsrc), "r"(bytes), "r"(bar) : "memory");
}
__device__ __forceinline__ void bulk_load_mc(uint32_t dst, const void* gsrc, int bytes, uint32_t bar, uint16_t mask) {
    asm volatile("cp.async.bulk.shared::cluster.global.mbarrier::complete_tx::bytes.multicast::cluster [%0],[%1],%2,[%3],%4;"
                 ::"r"(dst), "l"(gsrc), "r"(bytes), "r"(bar), "h"(mask) : "memory");
}

__device__ __forceinline__ void bulk_s2s(uint32_t rdst, uint32_t src, int bytes, uint32_t rbar) {
    asm volatile("cp.async.bulk.shared::cluster.shared::cta.mbarrier::complete_tx::bytes [%0],[%1],%2,[%3];"
                 ::"r"(rdst), "r"(src), "r"(bytes), "r"(rbar) : "memory");
}
__device__ __forceinline__ void stas4(uint32_t rdst, uint32_t a, uint32_t b, uint32_t c2, uint32_t d, uint32_t rbar) {
    asm volatile("st.async.weak.shared::cluster.mbarrier::complete_tx::bytes.v4.b32 [%0],{%1,%2,%3,%4},[%5];"
                 ::"r"(rdst), "r"(a), "r"(b), "r"(c2), "r"(d), "r"(rbar) : "memory");
}
__device__ __forceinline__ void stas2(uint32_t rdst, uint32_t a, uint32_t b, uint32_t rbar) {
    asm volatile("st.async.weak.shared::cluster.mbarrier::complete_tx::bytes.v2.b32 [%0],{%1,%2},[%3];"
                 ::"r"(rdst), "r"(a), "r"(b), "r"(rbar) : "memory");
}
__device__ __forceinline__ float4 lds128f(uint32_t a) {
    float4 v; asm volatile("ld.shared.v4.f32 {%0,%1,%2,%3},[%4];" : "=f"(v.x), "=f"(v.y), "=f"(v.z), "=f"(v.w) : "r"(a) : "memory"); return v;
}

__global__ void __launch_bounds__(384, 1) k_rec(const __grid_constant__ CUtensorMap tmx, const RecParams p) {
    extern __shared__ uint8_t smem_raw[];
    const uint32_t sb = (s2u(smem_raw) + 1023) & ~1023u;
    const int tid = threadIdx.x, warp = __shfl_sync(0xffffffffu, tid >> 5, 0), lane = tid & 31, g = lane >> 2, t = lane & 3;
    const int l7 = lane & 7, l3 = lane >> 3;
    const int c = blockIdx.x % 3, h = blockIdx.x / 3;
    const int nq = c < 2 ? 3 : 2, nv = 8 - 2 * nq, v0 = 2 * c;
    const uint32_t bXF = sb + SM_BAR, bVX = bXF + 16, bS = bVX + 16, bV = bS + 8, bC = bV + 8;
    const uint32_t peer1 = (c + 1) % 3, peer2 = (c + 2) % 3;
    auto vslot = [](int r, int d) { return (r < 2 ? 6 : 4) + ((d - 2 * r) & 7); };

    if (tid == 0) {
        for (int i = 0; i < 2; i++) { mbar_init(bXF + 8 * i, 1); mbar_init(bVX + 8 * i, 1); }
        mbar_init(bS, 4); mbar_init(bV, nv + 1);
        for (int i = 0; i < 3; i++) mbar_init(bC + 8 * i, 4);
        asm volatile("fence.mbarrier_init.release.cluster;" ::: "memory");
        for (int i = 0; i < 2; i++) { mbar_expect(bXF + 8 * i, XT); mbar_expect(bVX + 8 * i, (8 - nv) * 1024); }
        mbar_expect(bS, 2560); mbar_expect(bV, (8 - nv) * 256);
    }
    {
        float4* z = reinterpret_cast<float4*>(g_red) + blockIdx.x * 1024;
        for (int i = tid; i < 1024; i += 384) z[i] = make_float4(0.f, 0.f, 0.f, 0.f);
        for (int i = tid; i < 576; i += 384) g_redh[blockIdx.x * 576 + i] = make_uint4(0u, 0u, 0u, 0u);
        float4* za = reinterpret_cast<float4*>(g_acc + F_FIRST_SPLIT * 128 * DM) + blockIdx.x * ((16 - F_FIRST_SPLIT) * 192);
        for (int i = tid; i < (16 - F_FIRST_SPLIT) * 192; i += 384) za[i] = make_float4(0.f, 0.f, 0.f, 0.f);
        if (blockIdx.x == 0) {
            for (int i = tid; i < 512; i += 384) g_ctr[i] = 0;
            if (tid < NSEG) g_flagA[tid] = 0;
        }
        __threadfence();
    }
    __syncthreads();
    asm volatile("griddepcontrol.launch_dependents;" ::: "memory");
    if (tid == 0) asm volatile("red.relaxed.gpu.global.add.u32 [%0],1;" ::"l"(g_sync) : "memory");
    cluster_sync();

    if (warp < 8) {
        asm volatile("setmaxnreg.inc.sync.aligned.u32 192;");
        if (tid == 0) {
            for (int sl = 0; sl < 2; sl++)
                for (int j = 0; j < 3; j++)
                    tma2d_mc(sb + SM_X + sl * XT + (c * 3 + j) * 4096, &tmx, (c * 3 + j) * 64, sl * 32, bXF + 8 * sl, 7);
        }
        const bool isv = warp >= 2 * nq;
        const int slot = warp;
        uint32_t w[36][4];
        {
            const int dt = isv ? v0 + warp - 2 * nq : 3 * c + (warp >= nq ? warp - nq : warp);
            const bf16* W = (isv ? p.Wv : (warp >= nq ? p.Wk : p.Wq)) + h * DH + dt * 16 + 2 * g + (size_t)(2 * t) * HD;
#pragma unroll
            for (int k = 0; k < 36; k++) {
                const uint32_t* q = reinterpret_cast<const uint32_t*>(W + (size_t)k * 16 * HD);
                w[k][0] = __ldg(q); w[k][1] = __ldg(q + HD / 2); w[k][2] = __ldg(q + 4 * HD); w[k][3] = __ldg(q + 4 * HD + HD / 2);
            }
#pragma unroll
            for (int k = 0; k < 36; k++) {
                uint32_t a = w[k][0], b = w[k][1], d = w[k][2], e = w[k][3];
                w[k][0] = __byte_perm(a, b, 0x5410); w[k][1] = __byte_perm(a, b, 0x7632);
                w[k][2] = __byte_perm(d, e, 0x5410); w[k][3] = __byte_perm(d, e, 0x7632);
            }
        }
        const uint32_t woff = 2 * t * 32 + (((g >> 2) ^ (t >> 1)) << 4) + (g & 3) * 4;

        float d[16];
        auto xdesc = [&](int sl) { return __shfl_sync(0xffffffffu, (((sb + SM_X + sl * XT) & 0x3FFFF) >> 4) | 0x10000u, 0); };
        auto fill_a = [&](uint32_t xd) {
            wg_fence();
#pragma unroll
            for (int k = 0; k < FA; k++) wgmma_rs_n32(d, w[k], xd + ((k >> 2) * 256 + (k & 3) * 2), k > 0);
            wg_commit();
        };
        auto fill_b = [&](uint32_t xd, int stg) {
            wg_fence();
#pragma unroll
            for (int k = FA; k < 36; k++) wgmma_rs_n32(d, w[k], xd + ((k >> 2) * 256 + (k & 3) * 2), k > 0);
            wg_commit();
            wg_wait<0>();
            const uint32_t dst = sb + SM_XR + stg * XR_STAGE + slot * 1024 + woff;
#pragma unroll
            for (int j = 0; j < 4; j++) {
                sts32(dst + j * 256, pack2(d[4 * j], d[4 * j + 2]));
                sts32(dst + j * 256 + 32, pack2(d[4 * j + 1], d[4 * j + 3]));
            }
        };
        auto fwd_v = [&](int sl, int stg) {
            const uint32_t base = sb + SM_XR + stg * XR_STAGE;
            bulk_s2s(mapa(base + vslot(peer1, v0) * 1024, peer1), base + 2 * nq * 1024, nv * 1024, mapa(bVX + 8 * sl, peer1));
            bulk_s2s(mapa(base + vslot(peer2, v0) * 1024, peer2), base + 2 * nq * 1024, nv * 1024, mapa(bVX + 8 * sl, peer2));
        };

        mbar_wait(bXF, 0);
        if (FA) fill_a(xdesc(0));
        fill_b(xdesc(0), 0);
        fence_async();
        bar_sync(9, 256);
        if (tid == 32) fwd_v(0, 0);
        __syncwarp();
        mbar_wait(bXF + 8, 0);
        if (FA) fill_a(xdesc(1));
        fill_b(xdesc(1), 1);
        bar_sync(9, 256);
        if (tid == 0) { mbar_expect(bXF, XT); mbar_expect(bXF + 8, XT); }
        cluster_sync();
        if (tid == 0) {
            for (int sl = 0; sl < 2; sl++)
                for (int j = 0; j < 3; j++)
                    tma2d_mc(sb + SM_X + sl * XT + (c * 3 + j) * 4096, &tmx, (c * 3 + j) * 64, (2 + sl) * 32, bXF + 8 * sl, 7);
        }
        __syncwarp();
        uint32_t mema = sb + SM_MEM + l7 * MP + l3 * 16;
        const uint32_t xpeer = (g & 2) ? peer2 : peer1;
        const uint32_t rdst0 = mapa(sb + SM_MR + vslot(xpeer, v0 + warp - 2 * nq) * 256 + (2 * t + (g & 1)) * 32 + (((g >> 2) ^ (t >> 1)) << 4), xpeer);
        uint32_t rbar = mapa(bV, xpeer);
        int s3 = 0;
        for (int s = 0; s < NSEG; s++) {
            const int st = s & 1, s3n = s3 == 2 ? 0 : s3 + 1, s3p = s3 == 0 ? 2 : s3 - 1;
            uint32_t rdst = rdst0 + s3 * MR_STAGE;
            uint32_t ldst = sb + SM_MR + s3 * MR_STAGE + slot * 256 + woff;
            PIN(rdst); PIN(rbar); PIN(ldst); PIN(mema);
            float a[QCH][4];
#pragma unroll
            for (int i = 0; i < QCH; i++) { a[i][0] = 0.f; a[i][1] = 0.f; a[i][2] = 0.f; a[i][3] = 0.f; }
            mbar_wait(bC, st);
            PROFT(24, 0);
#pragma unroll
            for (int i = 0; i < 18; i++) {
                uint32_t bf[4];
                ldsm4(bf, mema + i * 64);
                mma16(a[(2 * i) % QCH], w[2 * i], bf[0], bf[1]);
                mma16(a[(2 * i + 1) % QCH], w[2 * i + 1], bf[2], bf[3]);
            }
#pragma unroll
            for (int i = 0; i < 4; i++) {
                if (QCH == 4) a[0][i] = (a[2][i] + a[3][i]) + (a[0][i] + a[1][i]);
                if (QCH == 3) a[0][i] = (a[0][i] + a[1][i]) + a[2][i];
                if (QCH == 2) a[0][i] += a[1][i];
            }
            const uint32_t w0 = pack2(a[0][0], a[0][2]), w1 = pack2(a[0][1], a[0][3]);
            sts32(ldst, w0); sts32(ldst + 32, w1);
            if (!isv) bar_arrive(8, nq * 64 + 96);
            PROF(1);
            if (isv && s + 1 < NSEG) {
                uint32_t snd = (g & 1) ? w0 : w1, keep = (g & 1) ? w1 : w0;
                uint32_t rcv = __shfl_xor_sync(0xffffffffu, snd, 4);
                uint32_t lo = (g & 1) ? rcv : keep, hi = (g & 1) ? keep : rcv;
                uint32_t olo = __shfl_xor_sync(0xffffffffu, lo, 8), ohi = __shfl_xor_sync(0xffffffffu, hi, 8);
                stas4(rdst, (g & 2) ? olo : lo, (g & 2) ? ohi : hi, (g & 2) ? lo : olo, (g & 2) ? hi : ohi, rbar);
                __syncwarp();
                if (lane == 0) mbar_arrive(bV);
            }
            const uint32_t xd = xdesc(st);
            if (s + 2 < NSEG) {
                mbar_wait(bXF + 8 * st, ((s + 2) >> 1) & 1);
                if (FA) {
                    bar_sync(10, 352);
                    fill_a(xd);
                    wg_wait<0>();
                }
            }
            fence_async();
            bar_arrive(7, 288);
            if (warp == 1) bar_sync(6, 256); else bar_arrive(6, 256);
            if (warp < 2) {
                if (s + 1 < NSEG) { mbar_wait(bS, st); mbar_wait(bV, st); }
                if (lane == 0) {
                    if (warp == 0) {
                        if (s >= 1 && s + 3 < NSEG) {
                            mbar_expect(bXF + 8 * (st ^ 1), XT);
                            for (int j = 0; j < 3; j++)
                                tma2d_mc(sb + SM_X + (st ^ 1) * XT + (c * 3 + j) * 4096, &tmx, (c * 3 + j) * 64, (s + 3) * 32, bXF + 8 * (st ^ 1), 7);
                        }
                    } else {
                        if (s + 2 < NSEG) fwd_v(st ^ 1, s3n);
                    }
                }
                __syncwarp();
            }
            PROFT(13, 96);
            PROFDUMP();
            if (s + 2 < NSEG) {
                bar_sync(5, 384);
                fill_b(xd, s3p);
                PROF(4);
            } else {
                bar_sync(5, 384);
            }
            s3 = s3n;
        }
    } else {
        asm volatile("setmaxnreg.dec.sync.aligned.u32 120;");
        const int wq = warp - 8, wt = tid - 256;
        uint32_t woa = sb + SM_WO + wt * 16;
        uint32_t am0 = 0;
        {
            const bf16* W = p.Wo + (size_t)(h * DH + 2 * t) * DM + c * 192 + wq * 16 + 2 * g;
#pragma unroll
            for (int j = 0; j < 3; j++) {
                uint32_t wo[8][4];
#pragma unroll
                for (int k = 0; k < 8; k++) {
                    const uint32_t* q = reinterpret_cast<const uint32_t*>(W + k * 16 * DM + j * 64);
                    wo[k][0] = __ldg(q); wo[k][1] = __ldg(q + DM / 2);
                    wo[k][2] = __ldg(q + 4 * DM); wo[k][3] = __ldg(q + 4 * DM + DM / 2);
                }
#pragma unroll
                for (int k = 0; k < 8; k++) {
                    uint32_t a = wo[k][0], b = wo[k][1], d = wo[k][2], e = wo[k][3];
                    wo[k][0] = __byte_perm(a, b, 0x5410); wo[k][1] = __byte_perm(a, b, 0x7632);
                    wo[k][2] = __byte_perm(d, e, 0x5410); wo[k][3] = __byte_perm(d, e, 0x7632);
                    sts128(woa + (j * 8 + k) * 2048, wo[k]);
                }
            }
            for (int i = wt; i < 8 * 72; i += 128) {
                const int r = i / 72, cc = i % 72;
                uint4 v = __ldg(reinterpret_cast<const uint4*>(p.mem0 + r * DM) + cc);
                am0 = __vmaxu2(__vmaxu2(am0, __vmaxu2(v.x & 0x7fff7fffu, v.y & 0x7fff7fffu)), __vmaxu2(v.z & 0x7fff7fffu, v.w & 0x7fff7fffu));
                asm volatile("st.shared.v4.u32 [%0],{%1,%2,%3,%4};" ::"r"(sb + SM_MEM + r * MP + cc * 16), "r"(v.x), "r"(v.y), "r"(v.z), "r"(v.w) : "memory");
            }
        }
        if (wt == 0) {
            unsigned v; int it = 0;
            do { asm volatile("ld.acquire.gpu.global.u32 %0,[%1];" : "=r"(v) : "l"(g_sync) : "memory"); if (++it > (1 << 22)) __trap(); } while (v < 96);
        }
        cluster_sync();
        if (lane == 0) mbar_arrive(bC);
        uint32_t wa[8][4], wb[8][4];
#pragma unroll
        for (int k = 0; k < 8; k++) lds128(wa[k], woa + k * 2048);
#pragma unroll
        for (int k = 0; k < 8; k++) lds128(wb[k], woa + (8 + k) * 2048);

        int ex;
        {
            const uint32_t m = __reduce_max_sync(0xffffffffu, max(am0 & 0xffffu, am0 >> 16));
            ex = m ? min(max(4 - ((int)(m >> 7) - 127), -60), 60) : 0;
        }
        const float SC = 0.08838834764831845f * 1.4426950408889634f;
        uint32_t L16 = lane * 16;
        uint32_t AB = (l3 >> 1) * 256 + l7 * 32 + (((l3 & 1) ^ (l7 >> 2)) << 4);
        uint32_t AA = (l3 & 1) * 256 + l7 * 32 + (((l3 >> 1) ^ (l7 >> 2)) << 4);
        const uint32_t scu = sb + SM_SC + c * 1536 + (wq == 0 ? 1024 : (wq - 1) * 512);
        const uint32_t sc1 = mapa(scu, peer1), sc2 = mapa(scu, peer2), sb1 = mapa(bS, peer1), sb2 = mapa(bS, peer2);
        const uint32_t wou = sb + SM_WO + wq * 512;
        const int vs = vslot(c, 2 * wq);
        auto publish = [&](int xs, int stg) {
            if (xs >= 2) {
                asm volatile("cp.async.bulk.wait_group 0;" ::: "memory");
                asm volatile("red.relaxed.gpu.global.add.u32 [%0],1;" ::"l"(g_flagA + xs - 2) : "memory");
            }
            if (xs < NSEG) bulk_store(reinterpret_cast<uint8_t*>(g_xr) + (size_t)(xs * 96 + blockIdx.x) * 8192, sb + SM_XR + stg * XR_STAGE, 8192);
            if (xs >= 1 && xs <= NSEG)
                bulk_store(reinterpret_cast<uint8_t*>(g_mr) + (size_t)((xs - 1) * 96 + blockIdx.x) * 2048, sb + SM_MR + (stg == 0 ? 2 : stg - 1) * MR_STAGE, 2048);
            asm volatile("cp.async.bulk.commit_group;" ::: "memory");
        };
        int s3 = 0;
        for (int s = 0; s + 1 < NSEG; s++) {
            const int st = s & 1;
            const uint32_t xr = sb + SM_XR + s3 * XR_STAGE, mr = sb + SM_MR + s3 * MR_STAGE;
            PIN(L16); PIN(AB); PIN(AA);
            if (wq < 3) {
                uint32_t kf[3][4], q0[4], q1[4];
                float ca[4] = {0.f, 0.f, 0.f, 0.f}, cb[4] = {0.f, 0.f, 0.f, 0.f};
                if (wq) {
                    const uint32_t ka = xr + nq * 1024 + (wq - 1) * 512 + AB;
                    ldsm4(kf[0], ka); ldsm4(kf[1], ka + 1024); ldsm4(kf[2], ka + 2048);
                    bar_sync(8, nq * 64 + 96);
                    ldsm4(q0, mr + AA); ldsm4(q1, mr + 512 + AA);
                    float da[4] = {0.f, 0.f, 0.f, 0.f}, db[4] = {0.f, 0.f, 0.f, 0.f};
                    mma16(ca, q0, kf[0][0], kf[0][1]); mma16(da, q0, kf[0][2], kf[0][3]);
                    mma16(cb, q0, kf[1][0], kf[1][1]); mma16(db, q0, kf[1][2], kf[1][3]);
                    if (nq == 3) { mma16(ca, q1, kf[2][0], kf[2][1]); mma16(da, q1, kf[2][2], kf[2][3]); }
                    const uint32_t rr[4] = {__float_as_uint(ca[0] + cb[2]), __float_as_uint(ca[1] + cb[3]),
                                            __float_as_uint(da[0] + db[2]), __float_as_uint(da[1] + db[3])};
                    stas4(sc1 + L16, rr[0], rr[1], rr[2], rr[3], sb1); stas4(sc2 + L16, rr[0], rr[1], rr[2], rr[3], sb2);
                    sts128(scu + L16, rr);
                } else {
                    bar_sync(8, nq * 64 + 96);
                    ldsm4(q0, mr + AA); ldsm4(kf[0], mr + nq * 256 + AB); ldsm4(q1, mr + 512 + AA); ldsm4(kf[1], mr + nq * 256 + 512 + AB);
                    mma16(ca, q0, kf[0][0], kf[0][1]); mma16(cb, q0, kf[0][2], kf[0][3]);
                    if (nq == 3) mma16(ca, q1, kf[1][0], kf[1][1]);
                    const uint32_t r0 = __float_as_uint(ca[0] + cb[2]), r1 = __float_as_uint(ca[1] + cb[3]);
                    stas2(sc1 + L16, r0, r1, sb1); stas2(sc2 + L16, r0, r1, sb2);
                    asm volatile("st.shared.v2.u32 [%0],{%1,%2};" ::"r"(scu + L16), "r"(r0), "r"(r1) : "memory");
                }
                __syncwarp();
                if (L16 == 0) mbar_arrive(bS);
                if (FA && s + 2 < NSEG) bar_arrive(10, 352);
                PROF(3);
            } else {
                if (lane == 0) publish(s, s3);
                __syncwarp();
            }
            uint32_t va[2][2][4], vb[4];
            mbar_wait(bVX + 8 * st, (s >> 1) & 1);
            const uint32_t v0a = xr + vs * 1024 + AB;
            ldsm4t(va[0][0], v0a); ldsm4t(va[1][0], v0a + 1024);
            uint4* rl = g_redh + (((s >> 3) * 96 + c * 32 + wq * 4) * 9 + (s & 7)) * 8 + (L16 >> 7) * 72 + ((L16 >> 4) & 7);
            PINL(rl);
            mbar_wait(bV, s & 1);
            mbar_wait(bS, s & 1);
            PROF(5);
            float4 sa, sbb; float2 sm2;
            {
                const uint32_t scl = sb + SM_SC + L16;
                const float4 a0 = lds128f(scl), a1 = lds128f(scl + 1536), a2 = lds128f(scl + 3072);
                const float4 b0 = lds128f(scl + 512), b1 = lds128f(scl + 2048), b2 = lds128f(scl + 3584);
                const float2 m0 = lds64f(scl + 1024), m1 = lds64f(scl + 2560), m2 = lds64f(scl + 4096);
                sa.x = a0.x + a1.x + a2.x; sa.y = a0.y + a1.y + a2.y; sa.z = a0.z + a1.z + a2.z; sa.w = a0.w + a1.w + a2.w;
                sbb.x = b0.x + b1.x + b2.x; sbb.y = b0.y + b1.y + b2.y; sbb.z = b0.z + b1.z + b2.z; sbb.w = b0.w + b1.w + b2.w;
                sm2.x = m0.x + m1.x + m2.x; sm2.y = m0.y + m1.y + m2.y;
            }
            float mx = fmaxf(fmaxf(fmaxf(sa.x, sa.y), fmaxf(sa.z, sa.w)), fmaxf(fmaxf(sbb.x, sbb.y), fmaxf(sbb.z, sbb.w)));
            mx = fmaxf(mx, fmaxf(sm2.x, sm2.y));
            {
                const float x1 = __shfl_xor_sync(0xffffffffu, mx, 1), x2 = __shfl_xor_sync(0xffffffffu, mx, 2), x3 = __shfl_xor_sync(0xffffffffu, mx, 3);
                ldsm4t(va[0][1], v0a + 512); ldsm4t(va[1][1], v0a + 1024 + 512);
                ldsm4t(vb, mr + vs * 256 + AB);
                mx = fmaxf(fmaxf(mx, x1), fmaxf(x2, x3));
            }
            PROF(6);
            uint32_t ws[8][4];
#pragma unroll
            for (int k = 0; k < WO_PRE2; k++) lds128(ws[k], wou + L16 + (16 + k) * 2048);
            const float mo = mx * SC;
            const float e0 = ex2(fmaf(sa.x, SC, -mo)), e1 = ex2(fmaf(sa.y, SC, -mo)), e2 = ex2(fmaf(sa.z, SC, -mo)), e3 = ex2(fmaf(sa.w, SC, -mo));
            float o0[4] = {0.f, 0.f, 0.f, 0.f}, o1[4] = {0.f, 0.f, 0.f, 0.f}, o2[4] = {0.f, 0.f, 0.f, 0.f};
            const uint32_t one = 0x3f803f80u;
            { const uint32_t p0 = pack2(e0, e1), p1 = pack2(e2, e3); mma16(o0, va[0][0], p0, p1); mma16(o1, va[1][0], p0, p1); mma8(o2, one, one, p0); mma8(o2, one, one, p1); }
            const float e4 = ex2(fmaf(sbb.x, SC, -mo)), e5 = ex2(fmaf(sbb.y, SC, -mo)), e6 = ex2(fmaf(sbb.z, SC, -mo)), e7 = ex2(fmaf(sbb.w, SC, -mo));
            { const uint32_t p0 = pack2(e4, e5), p1 = pack2(e6, e7); mma16(o0, va[0][1], p0, p1); mma16(o1, va[1][1], p0, p1); mma8(o2, one, one, p0); mma8(o2, one, one, p1); }
            const float e8 = ex2(fmaf(sm2.x, SC, -mo)), e9 = ex2(fmaf(sm2.y, SC, -mo));
            { const uint32_t p0 = pack2(e8, e9); mma8(o0, vb[0], vb[1], p0); mma8(o1, vb[2], vb[3], p0); mma8(o2, one, one, p0); }
            {
                const uint32_t oa = sb + SM_OB + wq * 512 + (L16 >> 2);
                sts32(oa, pack2(o0[0], o0[1])); sts32(oa + 128, pack2(o0[2], o0[3]));
                sts32(oa + 256, pack2(o1[0], o1[1])); sts32(oa + 384, pack2(o1[2], o1[3]));
            }
            bar_sync(4, 128);
            uint32_t ob[4][4];
#pragma unroll
            for (int j = 0; j < 4; j++) ldsm4t(ob[j], sb + SM_OB + L16 + 512 * j);
            const float fs = __int_as_float((127 + ex) << 23);
            const float i0 = rcp_fast(o2[0]) * fs, i1 = rcp_fast(o2[1]) * fs;
            PROF(7);
            float v[12];
            {
                float r[6][4];
#pragma unroll
                for (int i = 0; i < 6; i++) { r[i][0] = 0.f; r[i][1] = 0.f; r[i][2] = 0.f; r[i][3] = 0.f; }
#pragma unroll
                for (int k = WO_PRE2; k < WO_PRE3; k++) lds128(ws[k], wou + L16 + (16 + k) * 2048);
#pragma unroll
                for (int i = 0; i < 8; i++) {
                    mma16v(r[(WCH > 3 && (i & 1)) ? 3 : 0], wa[i], ob[i >> 1][(i & 1) * 2], ob[i >> 1][(i & 1) * 2 + 1]);
                    mma16v(r[(WCH > 4 && (i & 1)) ? 4 : 1], wb[i], ob[i >> 1][(i & 1) * 2], ob[i >> 1][(i & 1) * 2 + 1]);
                    mma16v(r[(WCH > 5 && (i & 1)) ? 5 : 2], ws[i], ob[i >> 1][(i & 1) * 2], ob[i >> 1][(i & 1) * 2 + 1]);
                    if (i + WO_PRE3 < 8) lds128(ws[i + WO_PRE3], wou + L16 + (16 + i + WO_PRE3) * 2048);
                }
                bar_arrive(5, 384);
#pragma unroll
                for (int j = 0; j < 3; j++) {
                    if (WCH > 3 + j) { r[j][0] += r[3 + j][0]; r[j][1] += r[3 + j][1]; r[j][2] += r[3 + j][2]; r[j][3] += r[3 + j][3]; }
                    v[4 * j] = r[j][0] * i0; v[4 * j + 1] = r[j][2] * i0; v[4 * j + 2] = r[j][1] * i1; v[4 * j + 3] = r[j][3] * i1;
                }
                const float m8 = maxn(maxn(maxn(v[0], v[1]), maxn(v[2], v[3])), maxn(maxn(v[4], v[5]), maxn(v[6], v[7])));
                const float m = maxn(maxn(maxn(v[8], v[9]), maxn(v[10], v[11])), m8);
                const uint32_t tag = m < 1024.f ? (m >= 0.00390625f ? 0x3c003c00u : 0x00003c00u) : 0x54003c00u;
                redh4(rl, v, tag);
                redh4(rl + 16 * 72, v + 6, tag);
            }
            const unsigned tred = clk32();
            if (wq == 3) bar_sync(7, 288);
            PROF(8);
            if (wt == 0) {
                if (s + 2 < NSEG) { mbar_expect(bS, 2560); mbar_expect(bV, (8 - nv) * 256); }
                if (s + 3 < NSEG) mbar_expect(bVX + 8 * st, (8 - nv) * 1024);
            }
            {
                const uint4* gl = rl - c * 32 * 72;
                uint32_t ma = sb + SM_MEM + wq * 32 + ((L16 >> 4) & 3) * (2 * MP) + (L16 >> 6) * 4;
                PINL(gl); PIN(ma);
                unsigned tl = tred + p.d0;
                while ((int)(clk32() - tl) < 0) {}
                PROF(9);
                uint4 u[2][3];
#pragma unroll
                for (int j = 0; j < 2; j++)
#pragma unroll
                    for (int cc = 0; cc < 3; cc++) u[j][cc] = ld_relaxed4u(gl + (cc * 32 + j * 16) * 72);
                const uint32_t rebias = (uint32_t)(112 - ex) * 0x00800080u;
                int it = 0;
                auto cvt = [&](uint32_t x) { return ((((x + 0x00040004u) & 0x7ff87ff8u) >> 3) + rebias) | (x & 0x80008000u); };
                auto put = [&](int j, int cc) {
                    sts32(ma + (cc * 192 + ((3 * j) >> 1) * 64) * 2 + ((3 * j) & 1) * MP, u[j][cc].x);
                    sts32(ma + (cc * 192 + ((3 * j + 1) >> 1) * 64) * 2 + ((3 * j + 1) & 1) * MP, u[j][cc].y);
                    sts32(ma + (cc * 192 + ((3 * j + 2) >> 1) * 64) * 2 + ((3 * j + 2) & 1) * MP, u[j][cc].z);
                };
#pragma unroll
                for (int j = 0; j < 2; j++)
#pragma unroll
                    for (int cc = 0; cc < 3; cc++) {
                        u[j][cc].x = cvt(u[j][cc].x); u[j][cc].y = cvt(u[j][cc].y); u[j][cc].z = cvt(u[j][cc].z);
                        put(j, cc);
                    }
                {
                    const uint32_t bad = ((u[0][0].w ^ 0x5000u) | (u[0][1].w ^ 0x5000u) | (u[0][2].w ^ 0x5000u)) |
                                         ((u[1][0].w ^ 0x5000u) | (u[1][1].w ^ 0x5000u) | (u[1][2].w ^ 0x5000u));
                    const uint32_t tg = max(max(max(u[0][0].w, u[0][1].w), u[0][2].w), max(max(u[1][0].w, u[1][1].w), u[1][2].w));
                    const bool clean = __all_sync(0xffffffffu, (bad & 0xffffu) == 0 && tg < 0x54000000u);
                    const bool big = __any_sync(0xffffffffu, tg >= 0x3c000000u);
                    if (__builtin_expect(!(clean && big), 0)) {
                        while (true) {
                            bool ok = true;
#pragma unroll
                            for (int j = 0; j < 2; j++)
#pragma unroll
                                for (int cc = 0; cc < 3; cc++) ok = ok && (u[j][cc].w & 0xffffu) == 0x5000u;
                            if (__all_sync(0xffffffffu, ok)) break;
                            if (++it > (1 << 20)) __trap();
                            uint32_t redo = 0;
#pragma unroll
                            for (int j = 0; j < 2; j++)
#pragma unroll
                                for (int cc = 0; cc < 3; cc++) {
                                    if ((u[j][cc].w & 0xffffu) != 0x5000u) redo |= 1u << (j * 3 + cc);
                                    reld_relaxed4u(u[j][cc], gl + (cc * 32 + j * 16) * 72);
                                }
#pragma unroll
                            for (int j = 0; j < 2; j++)
#pragma unroll
                                for (int cc = 0; cc < 3; cc++) {
                                    const bool rd = (redo >> (j * 3 + cc)) & 1;
                                    u[j][cc].x = rd ? cvt(u[j][cc].x) : u[j][cc].x; u[j][cc].y = rd ? cvt(u[j][cc].y) : u[j][cc].y;
                                    u[j][cc].z = rd ? cvt(u[j][cc].z) : u[j][cc].z;
                                    put(j, cc);
                                }
                        }
                        const uint32_t t2 = max(max(max(u[0][0].w, u[0][1].w), u[0][2].w), max(max(u[1][0].w, u[1][1].w), u[1][2].w));
                        if (__any_sync(0xffffffffu, t2 >= 0x54000000u) || !__any_sync(0xffffffffu, t2 >= 0x3c000000u)) {
                            const float isc = __int_as_float((127 - ex) << 23);
                            float* fl = red_line(s, c * 64 + wq * 4 + (L16 >> 7)) + ((L16 >> 2) & 28);
#pragma unroll
                            for (int i = 0; i < 4; i++) red4(fl + i * 16 * 256, v[3 * i], v[3 * i + 1], v[3 * i + 2], 1.0f);
                            const float* fg = fl - c * 64 * 256;
#pragma unroll
                            for (int j = 0; j < 2; j++)
#pragma unroll
                                for (int cc = 0; cc < 3; cc++) {
                                    float4 a, b;
                                    while (true) {
                                        a = ld_relaxed4(fg + (cc * 64 + j * 32) * 256); b = ld_relaxed4(fg + (cc * 64 + j * 32 + 16) * 256);
                                        if (__all_sync(0xffffffffu, a.w == 32.f && b.w == 32.f)) break;
                                        if (++it > (1 << 20)) __trap();
                                    }
                                    u[j][cc].x = pack2(a.x * isc, a.y * isc); u[j][cc].y = pack2(a.z * isc, b.x * isc); u[j][cc].z = pack2(b.y * isc, b.z * isc);
                                    put(j, cc);
                                }
                        }
                    }
                }
                __syncwarp();
                if (L16 == 0) mbar_arrive(bC);
                PROF(11);
                uint32_t am = max(max(u[0][0].x << 1, u[0][1].y << 1), max(u[1][1].x << 1, u[1][2].y << 1));
                am = __reduce_max_sync(0xffffffffu, am >> 24);
                if (am) ex = min(max(4 - ((int)am - 127), -60), 60);
                s3 = s3 == 2 ? 0 : s3 + 1;
            }
        }
        if (wt == 96) publish(NSEG - 1, 0);
        __syncwarp();
        if (wq < 3) bar_sync(8, nq * 64 + 96);
        bar_arrive(5, 384);
        if (wq == 3) bar_sync(7, 288);
        if (wt == 96) { publish(NSEG, 1); publish(NSEG + 1, 2); }
    }
    cluster_sync();
}

constexpr int H_STAGES = 5, H_STAGE = 45056;
constexpr int HELP_SMEM = H_STAGES * H_STAGE + 1024 + 256;
enum { T_EXIT = 0, T_GATE, T_G0, T_F, T_AB, T_AA };
enum { C_HAA = 0, C_HB = 32, C_GATE = 33, C_G0 = 48, C_AB = 64, C_AA = 80, C_HF = 96, C_F = 128, C_TOTAL = 128 + 16 * 3 * 8 };
constexpr int NB_UNITS = 16 + 144 + 256;
constexpr int NAA_UNITS = NSEG * 4;
__host__ __device__ constexpr int f_split(int m) { return m < F_FIRST_SPLIT ? 1 : (m < 12 ? 2 : (m < 14 ? 4 : (m < 15 ? 8 : 12))); }
__host__ __device__ constexpr int f_units() { int n = 0; for (int m = 0; m < 16; m++) n += 3 * f_split(m); return n; }

__device__ __forceinline__ unsigned ld_acq(const unsigned* q) {
    unsigned v; asm volatile("ld.acquire.gpu.global.u32 %0,[%1];" : "=r"(v) : "l"(q) : "memory"); return v;
}
__device__ __forceinline__ void wait_ge(const unsigned* q, unsigned target) {
    int it = 0;
    while (ld_acq(q) < target) { __nanosleep(100); if (++it > (1 << 22)) __trap(); }
}
__device__ __forceinline__ void signal(unsigned* q, int lane) {
    __threadfence();
    __syncwarp();
    if (lane == 0) asm volatile("red.relaxed.gpu.global.add.u32 [%0],1;" ::"l"(q) : "memory");
}

__device__ __forceinline__ int pos_q(int d) { return (d / 3) * 8 + d % 3; }
__device__ __forceinline__ int pos_k(int d) { return (d / 3) * 8 + d % 3 + (d < 6 ? 3 : 2); }
__device__ __forceinline__ int pos_v(int d) { return d < 2 ? 6 + d : (d < 4 ? 12 + d : 16 + d); }

__device__ __forceinline__ uint4 quad_tr(const uint32_t* v, int t) {
    uint32_t a0 = (t & 1) ? v[0] : v[1], a1 = (t & 1) ? v[2] : v[3];
    a0 = __shfl_xor_sync(0xffffffffu, a0, 1); a1 = __shfl_xor_sync(0xffffffffu, a1, 1);
    const uint32_t b0 = (t & 1) ? a0 : v[0], b1 = (t & 1) ? v[1] : a0, b2 = (t & 1) ? a1 : v[2], b3 = (t & 1) ? v[3] : a1;
    uint32_t c0 = (t & 2) ? b0 : b2, c1 = (t & 2) ? b1 : b3;
    c0 = __shfl_xor_sync(0xffffffffu, c0, 2); c1 = __shfl_xor_sync(0xffffffffu, c1, 2);
    uint4 o;
    o.x = (t & 2) ? c0 : b0; o.y = (t & 2) ? c1 : b1; o.z = (t & 2) ? b2 : c0; o.w = (t & 2) ? b3 : c1;
    return o;
}
__device__ __forceinline__ void store_tile(const float* acc, bf16* q, int pitch, int t) {
#pragma unroll
    for (int j = 0; j < 6; j++) {
        uint32_t lo[4], hi[4];
#pragma unroll
        for (int i = 0; i < 4; i++) {
            lo[i] = pack2(acc[16 * j + 4 * i], acc[16 * j + 4 * i + 1]); hi[i] = pack2(acc[16 * j + 4 * i + 2], acc[16 * j + 4 * i + 3]);
        }
        *reinterpret_cast<uint4*>(q + j * 32 + t * 8) = quad_tr(lo, t);
        *reinterpret_cast<uint4*>(q + (size_t)8 * pitch + j * 32 + t * 8) = quad_tr(hi, t);
    }
}

__device__ __forceinline__ void attnA_unit(uint32_t xr, int s, int h, int wq, int lane) {
    const int g = lane >> 2, t = lane & 3, l7 = lane & 7, l3 = lane >> 3;
    const uint32_t mr = xr + 24 * 1024;
    const float SC = 0.08838834764831845f * 1.4426950408889634f;
    const int mt = wq & 1, dh = wq >> 1;
    const uint32_t offA = (l7 + (l3 & 1) * 8) * 32 + (((l3 >> 1) ^ (l7 >> 2)) << 4);
    const uint32_t offB = (l7 + (l3 >> 1) * 8) * 32 + (((l3 & 1) ^ (l7 >> 2)) << 4);
    float sa[5][4];
#pragma unroll
    for (int n = 0; n < 5; n++)
#pragma unroll
        for (int i = 0; i < 4; i++) sa[n][i] = 0.f;
#pragma unroll
    for (int hf = 0; hf < 2; hf++) {
        uint32_t qf[4][4], k0[4][4], k1[4][4], km[4][2];
#pragma unroll
        for (int i = 0; i < 4; i++) {
            const int d = hf * 4 + i;
            ldsm4(qf[i], xr + pos_q(d) * 1024 + mt * 512 + offA);
            ldsm2(km[i], mr + pos_k(d) * 256 + (offB & 255));
            ldsm4(k0[i], xr + pos_k(d) * 1024 + offB); ldsm4(k1[i], xr + pos_k(d) * 1024 + 512 + offB);
        }
#pragma unroll
        for (int i = 0; i < 4; i++) {
            mma16(sa[0], qf[i], km[i][0], km[i][1]);
            mma16(sa[1], qf[i], k0[i][0], k0[i][1]); mma16(sa[2], qf[i], k0[i][2], k0[i][3]);
            mma16(sa[3], qf[i], k1[i][0], k1[i][1]); mma16(sa[4], qf[i], k1[i][2], k1[i][3]);
        }
    }
    uint32_t f0[4][4], f1[4][4], f2[4][2];
#pragma unroll
    for (int n2 = 0; n2 < 4; n2++) {
        const int pv = dh ? pos_v(4 + n2) : pos_v(n2);
        ldsm4t(f0[n2], xr + pv * 1024 + offA); ldsm4t(f1[n2], xr + pv * 1024 + 512 + offA); ldsm2t(f2[n2], mr + pv * 256 + (offB & 255));
    }
    const int q0i = mt * 16 + g, q1i = q0i + 8;
    float m0 = fmaxf(sa[0][0], sa[0][1]), m1 = fmaxf(sa[0][2], sa[0][3]);
#pragma unroll
    for (int n = 1; n < 5; n++) {
        const int kx = (n - 1) * 8 + 2 * t;
        if (kx > q0i) sa[n][0] = -INFINITY;
        if (kx + 1 > q0i) sa[n][1] = -INFINITY;
        if (kx > q1i) sa[n][2] = -INFINITY;
        if (kx + 1 > q1i) sa[n][3] = -INFINITY;
        m0 = fmaxf(m0, fmaxf(sa[n][0], sa[n][1])); m1 = fmaxf(m1, fmaxf(sa[n][2], sa[n][3]));
    }
    m0 = fmaxf(m0, __shfl_xor_sync(0xffffffffu, m0, 1)); m1 = fmaxf(m1, __shfl_xor_sync(0xffffffffu, m1, 1));
    m0 = fmaxf(m0, __shfl_xor_sync(0xffffffffu, m0, 2)); m1 = fmaxf(m1, __shfl_xor_sync(0xffffffffu, m1, 2));
    m0 *= SC; m1 *= SC;
    uint32_t pa[5][2]; float s0 = 0.f, s1 = 0.f;
#pragma unroll
    for (int n = 0; n < 5; n++) {
        float e0 = ex2(fmaf(sa[n][0], SC, -m0)), e1 = ex2(fmaf(sa[n][1], SC, -m0));
        float e2 = ex2(fmaf(sa[n][2], SC, -m1)), e3 = ex2(fmaf(sa[n][3], SC, -m1));
        pa[n][0] = pack2(e0, e1); pa[n][1] = pack2(e2, e3); s0 += e0 + e1; s1 += e2 + e3;
    }
    s0 += __shfl_xor_sync(0xffffffffu, s0, 1); s1 += __shfl_xor_sync(0xffffffffu, s1, 1);
    s0 += __shfl_xor_sync(0xffffffffu, s0, 2); s1 += __shfl_xor_sync(0xffffffffu, s1, 2);
    s0 = rcp_fast(s0); s1 = rcp_fast(s1);
    const uint32_t p0[4] = {pa[1][0], pa[1][1], pa[2][0], pa[2][1]}, p1[4] = {pa[3][0], pa[3][1], pa[4][0], pa[4][1]};
    uint32_t lo[8], hi[8];
#pragma unroll
    for (int n2 = 0; n2 < 4; n2++) {
        float oa0[4] = {0.f, 0.f, 0.f, 0.f}, oa1[4] = {0.f, 0.f, 0.f, 0.f};
        mma16(oa0, p0, f0[n2][0], f0[n2][1]); mma16(oa1, p0, f0[n2][2], f0[n2][3]);
        mma16(oa0, p1, f1[n2][0], f1[n2][1]); mma16(oa1, p1, f1[n2][2], f1[n2][3]);
        mma8(oa0, pa[0][0], pa[0][1], f2[n2][0]); mma8(oa1, pa[0][0], pa[0][1], f2[n2][1]);
        lo[2 * n2] = pack2(oa0[0] * s0, oa0[1] * s0); hi[2 * n2] = pack2(oa0[2] * s1, oa0[3] * s1);
        lo[2 * n2 + 1] = pack2(oa1[0] * s0, oa1[1] * s0); hi[2 * n2 + 1] = pack2(oa1[2] * s1, oa1[3] * s1);
    }
    bf16* op = g_O + (size_t)(s * 32 + mt * 16 + g) * OK + h * DH + dh * 64 + t * 8;
#pragma unroll
    for (int q = 0; q < 2; q++) {
        *reinterpret_cast<uint4*>(op + q * 32) = quad_tr(lo + 4 * q, t);
        *reinterpret_cast<uint4*>(op + (size_t)8 * OK + q * 32) = quad_tr(hi + 4 * q, t);
    }
}

__device__ __forceinline__ void attnB_unit(uint32_t sQ, int q0, int hh, int wq, int lane) {
    const int g = lane >> 2, t = lane & 3, l7 = lane & 7, l3 = lane >> 3;
    const uint32_t sK = sQ + 128 * 48, sV = sK + 384 * 48;
    const int sh = (hh & 3) * 2;
    uint32_t qa[2][4], qb[2][2];
#pragma unroll
    for (int m = 0; m < 2; m++) {
        ldsm4(qa[m], sQ + (wq * 32 + m * 16 + l7 + (l3 & 1) * 8) * 48 + (l3 >> 1) * 16);
        ldsm2(qb[m], sQ + (wq * 32 + m * 16 + l7 + (l3 & 1) * 8) * 48 + 32);
        if (2 * t < sh) { qa[m][0] = 0u; qa[m][1] = 0u; }
        if (16 + 2 * t >= sh + 18) { qb[m][0] = 0u; qb[m][1] = 0u; }
    }
    const bool one0 = (sh == 6 && g == 0), one2 = (sh != 6 && g == 7);
    const float SC = 0.23570226039551584f * 1.4426950408889634f;
    float o[2][3][4];
    float mx[2][2];
#pragma unroll
    for (int m = 0; m < 2; m++) {
        mx[m][0] = -INFINITY; mx[m][1] = -INFINITY;
#pragma unroll
        for (int n = 0; n < 3; n++)
#pragma unroll
            for (int i = 0; i < 4; i++) o[m][n][i] = 0.f;
    }
    const int tfirst = max(0, (256 - q0) / 16 - 2 * wq);
    const uint32_t kb0 = sK + (wq * 32 + l7 + (l3 >> 1) * 8) * 48 + (l3 & 1) * 16;
    const uint32_t kb1 = sK + (wq * 32 + l7 + (l3 & 1) * 8) * 48 + 32;
    const uint32_t vb0 = sV + (wq * 32 + l7 + (l3 & 1) * 8) * 48 + (l3 >> 1) * 16;
    const uint32_t vb1 = sV + (wq * 32 + l7 + (l3 & 1) * 8) * 48 + 32;
    constexpr int CH = 3;
#pragma unroll 1
    for (int c0 = 18 - CH; c0 >= 0; c0 -= CH) {
        if (c0 + CH <= tfirst) break;
        float sc[2][CH][2][4];
#pragma unroll
        for (int u = 0; u < CH; u++) {
            uint32_t kf[4], kg[2];
            const int ti = max(c0 + u, tfirst);
            ldsm4(kf, kb0 + ti * 768); ldsm2(kg, kb1 + ti * 768);
#pragma unroll
            for (int m = 0; m < 2; m++) {
#pragma unroll
                for (int n = 0; n < 2; n++) {
#pragma unroll
                    for (int i = 0; i < 4; i++) sc[m][u][n][i] = 0.f;
                    mma16(sc[m][u][n], qa[m], kf[2 * n], kf[2 * n + 1]);
                    mma8(sc[m][u][n], qb[m][0], qb[m][1], kg[n]);
                }
            }
        }
        if (c0 == 18 - CH || c0 == 0 || c0 < tfirst) {
#pragma unroll
            for (int m = 0; m < 2; m++)
#pragma unroll
                for (int u = 0; u < CH; u++)
#pragma unroll
                    for (int n = 0; n < 2; n++)
#pragma unroll
                        for (int i = 0; i < 4; i++) {
                            const int d = 256 + m * 16 + g + (i >> 1) * 8 - ((c0 + u) * 16 + n * 8 + 2 * t + (i & 1));
                            if (d < 0 || d >= 256 || c0 + u < tfirst) sc[m][u][n][i] = -INFINITY;
                        }
        }
        float bs[2][2];
#pragma unroll
        for (int m = 0; m < 2; m++) {
            float n0 = mx[m][0], n1 = mx[m][1];
#pragma unroll
            for (int u = 0; u < CH; u++)
#pragma unroll
                for (int n = 0; n < 2; n++) {
                    n0 = fmaxf(n0, fmaxf(sc[m][u][n][0], sc[m][u][n][1])); n1 = fmaxf(n1, fmaxf(sc[m][u][n][2], sc[m][u][n][3]));
                }
            n0 = fmaxf(n0, __shfl_xor_sync(0xffffffffu, n0, 1)); n1 = fmaxf(n1, __shfl_xor_sync(0xffffffffu, n1, 1));
            n0 = fmaxf(n0, __shfl_xor_sync(0xffffffffu, n0, 2)); n1 = fmaxf(n1, __shfl_xor_sync(0xffffffffu, n1, 2));
            const float f0 = ex2((mx[m][0] - n0) * SC), f1 = ex2((mx[m][1] - n1) * SC);
            mx[m][0] = n0; mx[m][1] = n1;
            bs[m][0] = n0 * SC; bs[m][1] = n1 * SC;
#pragma unroll
            for (int n = 0; n < 3; n++) { o[m][n][0] *= f0; o[m][n][1] *= f0; o[m][n][2] *= f1; o[m][n][3] *= f1; }
        }
#pragma unroll
        for (int u = 0; u < CH; u++) {
            uint32_t vf[4], vg[2];
            const int ti = max(c0 + u, tfirst);
            ldsm4t(vf, vb0 + ti * 768); ldsm2t(vg, vb1 + ti * 768);
            if (one0) { vf[0] = 0x3f803f80u; vf[1] = 0x3f803f80u; }
            if (one2) { vg[0] = 0x3f803f80u; vg[1] = 0x3f803f80u; }
#pragma unroll
            for (int m = 0; m < 2; m++) {
                uint32_t pa[4];
#pragma unroll
                for (int n = 0; n < 2; n++) {
                    pa[2 * n] = pack2(ex2(fmaf(sc[m][u][n][0], SC, -bs[m][0])), ex2(fmaf(sc[m][u][n][1], SC, -bs[m][0])));
                    pa[2 * n + 1] = pack2(ex2(fmaf(sc[m][u][n][2], SC, -bs[m][1])), ex2(fmaf(sc[m][u][n][3], SC, -bs[m][1])));
                }
                mma16(o[m][0], pa, vf[0], vf[1]); mma16(o[m][1], pa, vf[2], vf[3]); mma16(o[m][2], pa, vg[0], vg[1]);
            }
        }
    }
#pragma unroll
    for (int m = 0; m < 2; m++) {
        const int src = sh == 6 ? (lane & ~3) : (lane | 3);
        const float s0 = __shfl_sync(0xffffffffu, sh == 6 ? o[m][0][0] : o[m][2][1], src);
        const float s1 = __shfl_sync(0xffffffffu, sh == 6 ? o[m][0][2] : o[m][2][3], src);
        const int r = q0 + wq * 32 + m * 16 + g;
        const float i0 = (1.f - __ldcg(g_gate + r)) / s0, i1 = (1.f - __ldcg(g_gate + r + 8)) / s1;
        bf16* op = g_O + (size_t)r * OK + HD + hh * BD + 2 * t - sh;
#pragma unroll
        for (int n = 0; n < 3; n++) {
            const int col = n * 8 + 2 * t;
            if (col >= sh && col < sh + 18) {
                *reinterpret_cast<uint32_t*>(op + n * 8) = pack2(o[m][n][0] * i0, o[m][n][1] * i0);
                *reinterpret_cast<uint32_t*>(op + n * 8 + 8 * OK) = pack2(o[m][n][2] * i1, o[m][n][3] * i1);
            }
        }
    }
}

#define LOG_BEGIN()
#define LOG_END()
struct HelpMaps { CUtensorMap x, wqkv, O, Wo, wo, qkv; };

__global__ void __launch_bounds__(512, 1) k_help(const __grid_constant__ HelpMaps tm, const bf16* __restrict__ x,
                                                  const bf16* __restrict__ gw, bf16* __restrict__ out) {
    extern __shared__ uint8_t smem_raw[];
    const uint32_t sb = (s2u(smem_raw) + 1023) & ~1023u;
    const uint32_t bF = sb + H_STAGES * H_STAGE, bE = bF + 8 * H_STAGES, dsc = bF + 128;
    const int tid = threadIdx.x, warp = __shfl_sync(0xffffffffu, tid >> 5, 0), lane = tid & 31;
    if (tid == 0) {
        for (int i = 0; i < H_STAGES; i++) { mbar_init(bF + 8 * i, 1); mbar_init(bE + 8 * i, 12); }
        asm volatile("fence.mbarrier_init.release.cluster;" ::: "memory");
    }
    __syncthreads();
    if (warp >= 12) {
        asm volatile("setmaxnreg.dec.sync.aligned.u32 56;");
        if (tid != 384) return;
        int sg = 0, ph = 1;
        auto next = [&](int ty, int a, int b, int c2) {
            mbar_wait(bE + 8 * sg, ph);
            asm volatile("st.shared.v4.u32 [%0],{%1,%2,%3,%4};" ::"r"(dsc + 16 * sg), "r"(ty), "r"(a), "r"(b), "r"(c2) : "memory");
        };
        auto adv = [&]() { if (++sg == H_STAGES) { sg = 0; ph ^= 1; } };
        auto gemm = [&](int ty, int m, int n, int kb0, int kb1) {
            for (int kb = kb0; kb < kb1; kb++) {
                next(ty, m, n, kb0 | (kb1 << 8));
                const uint32_t a = sb + sg * H_STAGE, b = a + 16384, bar = bF + 8 * sg;
                mbar_expect(bar, 40960);
                tma2d(a, ty == T_G0 ? &tm.x : &tm.O, kb * 64, m * 128, bar);
                const CUtensorMap* mb = ty == T_G0 ? &tm.wqkv : (kb >= 64 ? &tm.wo : &tm.Wo);
                const int kr = (kb >= 64 ? kb - 64 : kb) * 64;
                for (int j = 0; j < 3; j++) tma2d(b + j * 8192, mb, n * 192 + j * 64, kr, bar);
                adv();
            }
        };
        bool bdone = false;
        int idle = 0, fm = 0, rr = 0;
        while (true) {
            unsigned ha = ld_acq(g_ctr + C_HAA);
            if (ha < NAA_UNITS && ld_acq(g_flagA + (ha >> 2)) >= 96) {
                ha = atomicAdd(g_ctr + C_HAA, 1);
                if (ha < NAA_UNITS) {
                    const int seg = ha >> 2, h0 = (ha & 3) * 8;
                    wait_ge(g_flagA + seg, 96);
                    asm volatile("fence.proxy.async.global;" ::: "memory");
                    for (int i = 0; i < 8; i++) {
                        next(T_AA, seg, h0 + i, rr | (i >= 5 ? 4 : 0)); rr = rr == 2 ? 0 : rr + 1;
                        const uint32_t a = sb + sg * H_STAGE, bar = bF + 8 * sg;
                        mbar_expect(bar, 30720);
                        bulk_load(a, reinterpret_cast<uint8_t*>(g_xr) + (size_t)(seg * 32 + h0 + i) * 24576, 24576, bar);
                        bulk_load(a + 24576, reinterpret_cast<uint8_t*>(g_mr) + (size_t)(seg * 32 + h0 + i) * 6144, 6144, bar);
                        adv();
                    }
                }
                continue;
            }
            while (fm < 16 && ld_acq(g_ctr + C_HF + fm) >= (unsigned)(3 * f_split(fm))) fm++;
            if (fm < 16 && ld_acq(g_ctr + C_AA + fm) >= 192 && ld_acq(g_ctr + C_AB + fm) >= 128) {
                const unsigned u = atomicAdd(g_ctr + C_HF + fm, 1);
                const int ks = f_split(fm);
                if (u < (unsigned)(3 * ks)) {
                    asm volatile("fence.proxy.async.global;" ::: "memory");
                    const int kp = u / 3;
                    gemm(T_F, fm, u % 3, kp * 73 / ks, (kp + 1) * 73 / ks);
                }
                continue;
            }
            if (!bdone) {
                const unsigned u = atomicAdd(g_ctr + C_HB, 1);
                if (u < 16) {
                    next(T_GATE, u, 0, 0); mbar_arrive(bF + 8 * sg); adv();
                } else if (u < 160) {
                    gemm(T_G0, (u - 16) / 9, (u - 16) % 9, 0, 9);
                } else if (u < NB_UNITS) {
                    const int m = (u - 160) >> 4, h0 = ((u - 160) & 15) * 2;
                    for (int mm = max(0, m - 2); mm <= m; mm++) wait_ge(g_ctr + C_G0 + mm, 72);
                    wait_ge(g_ctr + C_GATE, 192);
                    asm volatile("fence.proxy.async.global;" ::: "memory");
                    for (int i = 0; i < 2; i++) {
                        next(T_AB, m, h0 + i, rr); rr = rr == 2 ? 0 : rr + 1;
                        const uint32_t a = sb + sg * H_STAGE, bar = bF + 8 * sg;
                        const int col = ((h0 + i) >> 2) * 72 + ((h0 + i) & 3) * 16;
                        mbar_expect(bar, 7 * 6144);
                        tma2d(a, &tm.qkv, col, m * 128, bar);
                        for (int j = 0; j < 3; j++) {
                            tma2d(a + (1 + j) * 6144, &tm.qkv, DM + col, (m - 2 + j) * 128, bar);
                            tma2d(a + (4 + j) * 6144, &tm.qkv, 2 * DM + col, (m - 2 + j) * 128, bar);
                        }
                        adv();
                    }
                } else bdone = true;
                continue;
            }
            if (fm >= 16) break;
            __nanosleep(200);
            if (++idle > (1 << 22)) __trap();
        }
        next(T_EXIT, 0, 0, 0); mbar_arrive(bF + 8 * sg);
    } else {
        asm volatile("setmaxnreg.inc.sync.aligned.u32 152;");
        const int wg = warp >> 2, wq = warp & 3, g = lane >> 2, t = lane & 3;
        int sg = 0, ph = 0;
        auto release = [&](int q) { __syncwarp(); if (lane == 0) mbar_arrive(bE + 8 * q); };
        auto adv = [&]() { if (++sg == H_STAGES) { sg = 0; ph ^= 1; } };
        while (true) {
            { int it = 0; while (!mbar_try(bF + 8 * sg, ph)) { if (++it > (1 << 26)) __trap(); } }
            uint32_t d[4];
            lds128(d, dsc + 16 * sg);
            const int ty = d[0];
            LOG_BEGIN();
            if (ty == T_EXIT) { LOG_END(); break; }
            if ((ty == T_G0 || ty == T_F) && wg == 2) {
                release(sg); adv();
            } else if (ty == T_G0 || ty == T_F) {
                const int m0 = d[1] * 128, n0 = d[2] * 192, kb0 = d[3] & 255, kb1 = d[3] >> 8;
                const int r0 = m0 + wg * 64 + wq * 16 + g;
                float acc[96];
#pragma unroll
                for (int i = 0; i < 96; i++) acc[i] = 0.f;
                int prev = -1;
                for (int kb = kb0; kb < kb1; kb++) {
                    if (kb > kb0) mbar_wait(bF + 8 * sg, ph);
                    const uint32_t a = sb + sg * H_STAGE + wg * 8192, b = sb + sg * H_STAGE + 16384;
                    if (ty == T_F && kb == 64 && kb0 < 64) {
                        wg_wait<0>();
                        const float g0 = __ldcg(g_gate + r0), g1 = __ldcg(g_gate + r0 + 8);
#pragma unroll
                        for (int i = 0; i < 24; i++) { acc[4 * i] *= g0; acc[4 * i + 1] *= g0; acc[4 * i + 2] *= g1; acc[4 * i + 3] *= g1; }
                    }
                    const uint64_t da = desc_sw128(a, 16, 1024), db = desc_sw128(b, 8192, 1024);
                    wg_fence();
#pragma unroll
                    for (int k = 0; k < 4; k++) wgmma_ss_n192(acc, da + (uint64_t)(k * 2), db + (uint64_t)(k * 128), 1);
                    wg_commit();
                    wg_wait<1>();
                    if (prev >= 0) release(prev);
                    prev = sg;
                    adv();
                }
                wg_wait<0>();
                release(prev);
                if (ty == T_G0) {
                    store_tile(acc, g_qkvB + (size_t)r0 * (3 * DM) + n0, 3 * DM, t);
                    signal(g_ctr + C_G0 + d[1], lane);
                } else {
                    if (kb1 <= 64) {
                        const float g0 = __ldcg(g_gate + r0), g1 = __ldcg(g_gate + r0 + 8);
#pragma unroll
                        for (int i = 0; i < 24; i++) { acc[4 * i] *= g0; acc[4 * i + 1] *= g0; acc[4 * i + 2] *= g1; acc[4 * i + 3] *= g1; }
                    }
                    const int ks = f_split(d[1]);
                    bool fin = true;
                    if (ks > 1) {
                        float* ga = g_acc + (size_t)r0 * DM + n0 + 2 * t;
#pragma unroll
                        for (int i = 0; i < 24; i++) {
                            asm volatile("red.relaxed.gpu.global.add.v2.f32 [%0],{%1,%2};" ::"l"(ga + i * 8), "f"(acc[4 * i]), "f"(acc[4 * i + 1]) : "memory");
                            asm volatile("red.relaxed.gpu.global.add.v2.f32 [%0],{%1,%2};" ::"l"(ga + i * 8 + 8 * DM), "f"(acc[4 * i + 2]), "f"(acc[4 * i + 3]) : "memory");
                        }
                        __threadfence();
                        __syncwarp();
                        unsigned old = 0;
                        if (lane == 0) old = atomicAdd(g_ctr + C_F + (d[1] * 3 + d[2]) * 8 + warp, 1);
                        old = __shfl_sync(0xffffffffu, old, 0);
                        fin = (old == (unsigned)ks - 1);
                        if (fin) {
                            __threadfence();
#pragma unroll
                            for (int i = 0; i < 24; i++) {
                                const float2 u0 = __ldcg(reinterpret_cast<const float2*>(ga + i * 8));
                                const float2 u1 = __ldcg(reinterpret_cast<const float2*>(ga + i * 8 + 8 * DM));
                                acc[4 * i] = u0.x; acc[4 * i + 1] = u0.y; acc[4 * i + 2] = u1.x; acc[4 * i + 3] = u1.y;
                            }
                        }
                    }
                    if (fin) store_tile(acc, out + (size_t)r0 * DM + n0, DM, t);
                    if (d[1] == 15 && tid == 0) g_sync[0] = 0;
                }
                LOG_END();
            } else if (ty == T_GATE) {
                release(sg); adv();
                const int m0 = d[1] * 128;
                float2 gv[9];
#pragma unroll
                for (int i = 0; i < 9; i++) gv[i] = __bfloat1622float2(reinterpret_cast<const __nv_bfloat162*>(gw)[lane + 32 * i]);
                for (int r0 = warp * 4; r0 < 128; r0 += 48) {
                    float acc[4];
#pragma unroll
                    for (int j = 0; j < 4; j++) {
                        acc[j] = 0.f;
                        const __nv_bfloat162* xr = reinterpret_cast<const __nv_bfloat162*>(x + (size_t)(m0 + r0 + j) * DM);
#pragma unroll
                        for (int i = 0; i < 9; i++) {
                            const float2 a = __bfloat1622float2(xr[lane + 32 * i]);
                            acc[j] += a.x * gv[i].x + a.y * gv[i].y;
                        }
                    }
#pragma unroll
                    for (int o = 16; o; o >>= 1)
#pragma unroll
                        for (int j = 0; j < 4; j++) acc[j] += __shfl_xor_sync(0xffffffffu, acc[j], o);
                    if (lane < 4) {
                        const float a = lane == 0 ? acc[0] : (lane == 1 ? acc[1] : (lane == 2 ? acc[2] : acc[3]));
                        g_gate[m0 + r0 + lane] = 1.f / (1.f + __expf(-a));
                    }
                }
                signal(g_ctr + C_GATE, lane);
                LOG_END();
            } else {
                if ((int)(d[3] & 3) == wg) {
                    if (ty == T_AA) {
                        attnA_unit(sb + sg * H_STAGE, d[1], d[2], wq, lane);
                        release(sg);
                        if (d[3] & 4) signal(g_ctr + C_AA + (d[1] >> 2), lane);
                    } else {
                        attnB_unit(sb + sg * H_STAGE, d[1] * 128, d[2], wq, lane);
                        release(sg);
                        signal(g_ctr + C_AB + d[1], lane);
                    }
                    LOG_END();
                } else {
                    release(sg);
                }
                adv();
            }
        }
    }
}

typedef CUresult (*EncodeFn)(CUtensorMap*, CUtensorMapDataType, cuuint32_t, void*, const cuuint64_t*, const cuuint64_t*,
                             const cuuint32_t*, const cuuint32_t*, CUtensorMapInterleave, CUtensorMapSwizzle,
                             CUtensorMapL2promotion, CUtensorMapFloatOOBfill);

static void make_map(EncodeFn fn, CUtensorMap* m, const void* ptr, uint64_t cols, uint64_t rows, uint32_t bc, uint32_t br,
                     CUtensorMapSwizzle sw = CU_TENSOR_MAP_SWIZZLE_128B) {
    cuuint64_t dims[2] = {cols, rows};
    cuuint64_t strides[1] = {cols * 2};
    cuuint32_t box[2] = {bc, br};
    cuuint32_t es[2] = {1, 1};
    fn(m, CU_TENSOR_MAP_DATA_TYPE_BFLOAT16, 2, const_cast<void*>(ptr), dims, strides, box, es, CU_TENSOR_MAP_INTERLEAVE_NONE,
       sw, sw == CU_TENSOR_MAP_SWIZZLE_NONE ? CU_TENSOR_MAP_L2_PROMOTION_NONE : CU_TENSOR_MAP_L2_PROMOTION_L2_256B, CU_TENSOR_MAP_FLOAT_OOB_FILL_NONE);
}

#define REC_D0 800
#define REC_DD 0
int g_d0 = REC_D0, g_dd = REC_DD, g_dsend = 0;

extern "C" void kernel_launch(void* const* d_in, const int* in_sizes, int n_in, void* d_out, int out_size) {
    const bf16* x = (const bf16*)d_in[0];
    const bf16* mem0 = (const bf16*)d_in[1];
    const bf16* Wq = (const bf16*)d_in[2];
    const bf16* Wk = (const bf16*)d_in[3];
    const bf16* Wv = (const bf16*)d_in[4];
    const bf16* Wo = (const bf16*)d_in[5];
    const bf16* wqkv = (const bf16*)d_in[8];
    const bf16* wo = (const bf16*)d_in[9];
    const bf16* gw = (const bf16*)d_in[10];
    bf16* out = (bf16*)d_out;

    void* fp = nullptr;
    cudaDriverEntryPointQueryResult qr;
    cudaGetDriverEntryPoint("cuTensorMapEncodeTiled", &fp, cudaEnableDefault, &qr);
    EncodeFn enc = (EncodeFn)fp;
    void* pO = nullptr;
    cudaGetSymbolAddress(&pO, g_O);
    CUtensorMap tx32;
    HelpMaps hm;
    make_map(enc, &tx32, x, DM, SEQ, 64, 32);
    make_map(enc, &hm.x, x, DM, SEQ, 64, 128);
    make_map(enc, &hm.wqkv, wqkv, 3 * DM, DM, 64, 64);
    make_map(enc, &hm.O, pO, OK, SEQ, 64, 128);
    make_map(enc, &hm.Wo, Wo, DM, HD, 64, 64);
    make_map(enc, &hm.wo, wo, DM, DM, 64, 64);
    void* pQ = nullptr;
    cudaGetSymbolAddress(&pQ, g_qkvB);
    make_map(enc, &hm.qkv, pQ, 3 * DM, SEQ, 24, 128, CU_TENSOR_MAP_SWIZZLE_NONE);
    cudaFuncSetAttribute(k_rec, cudaFuncAttributeMaxDynamicSharedMemorySize, REC_SMEM);
    cudaFuncSetAttribute(k_help, cudaFuncAttributeMaxDynamicSharedMemorySize, HELP_SMEM);

    cudaStream_t st = cudaStreamPerThread;
    {
        RecParams p{mem0, Wq, Wk, Wv, Wo, g_d0, g_dd, g_dsend};
        cudaLaunchConfig_t cfg = {};
        cfg.gridDim = dim3(96); cfg.blockDim = dim3(384); cfg.dynamicSmemBytes = REC_SMEM; cfg.stream = st;
        cudaLaunchAttribute at[1];
        at[0].id = cudaLaunchAttributeClusterDimension;
        at[0].val.clusterDim.x = 3; at[0].val.clusterDim.y = 1; at[0].val.clusterDim.z = 1;
        cfg.attrs = at; cfg.numAttrs = 1;
        cudaLaunchKernelEx(&cfg, k_rec, tx32, p);
    }
    {
        cudaLaunchConfig_t cfg = {};
        cfg.gridDim = dim3(132); cfg.blockDim = dim3(512); cfg.dynamicSmemBytes = HELP_SMEM; cfg.stream = st;
        cudaLaunchAttribute at[1];
        at[0].id = cudaLaunchAttributeProgrammaticStreamSerialization;
        at[0].val.programmaticStreamSerializationAllowed = 1;
        cfg.attrs = at; cfg.numAttrs = (g_dsend & 1) ? 0 : 1;
        cudaLaunchKernelEx(&cfg, k_help, hm, x, gw, out);
    }
}
```

```cpp
#include <cuda_runtime.h>
#include <cuda_bf16.h>
#include <cuda_fp16.h>
#include <cuda.h>
#include <stdint.h>

typedef __nv_bfloat16 bf16;

constexpr int SEQ = 2048, DM = 576, NH = 32, DH = 128, NMEM = 8, SEG = 32, NSEG = 64;
constexpr int HD = NH * DH;
constexpr int OK = HD + DM;
constexpr int BH = 32, BD = 18, BDP = 24, WIN = 256;

__device__ bf16 g_O[SEQ * OK];
__device__ bf16 g_qkvB[SEQ * 3 * DM];
__device__ float g_acc[SEQ * DM];
__device__ float g_gate[SEQ];
__device__ float g_red[8 * 192 * 256];
__device__ uint4 g_redh[8 * 96 * 72];
__device__ unsigned g_sync[32];
__device__ unsigned g_ctr[1920];
#define PROF(i)
#define PROFT(i, th)
#define PROFW(i)
#define PROFDUMP()

__device__ __forceinline__ uint32_t s2u(const void* p) { return (uint32_t)__cvta_generic_to_shared(p); }
__device__ __forceinline__ uint32_t mapa(uint32_t a, uint32_t r) {
    uint32_t o; asm volatile("mapa.shared::cluster.u32 %0,%1,%2;" : "=r"(o) : "r"(a), "r"(r)); return o;
}
__device__ __forceinline__ void mbar_init(uint32_t a, int c) {
    asm volatile("mbarrier.init.shared::cta.b64 [%0],%1;" ::"r"(a), "r"(c) : "memory");
}
__device__ __forceinline__ void mbar_expect(uint32_t a, int bytes) {
    asm volatile("mbarrier.arrive.expect_tx.shared::cta.b64 _,[%0],%1;" ::"r"(a), "r"(bytes) : "memory");
}
__device__ __forceinline__ void mbar_arrive(uint32_t a) {
    asm volatile("mbarrier.arrive.shared::cta.b64 _,[%0];" ::"r"(a) : "memory");
}
__device__ __forceinline__ bool mbar_try(uint32_t a, int ph) {
    uint32_t ok;
    asm volatile("{.reg .pred p; mbarrier.try_wait.parity.shared::cta.b64 p,[%1],%2; selp.u32 %0,1,0,p;}"
                 : "=r"(ok) : "r"(a), "r"(ph) : "memory");
    return ok;
}
__device__ __forceinline__ bool mbar_try_cl(uint32_t a, int ph) {
    uint32_t ok;
    asm volatile("{.reg .pred p; mbarrier.try_wait.parity.acquire.cluster.shared::cta.b64 p,[%1],%2; selp.u32 %0,1,0,p;}"
                 : "=r"(ok) : "r"(a), "r"(ph) : "memory");
    return ok;
}
__device__ __forceinline__ void mbar_wait(uint32_t a, int ph) {
    asm volatile("{.reg .pred p; .reg .u32 n; mov.u32 n,0;\n"
                 "WL%=: mbarrier.try_wait.parity.shared::cta.b64 p,[%0],%1; @p bra.uni WD%=;\n"
                 "add.u32 n,n,1; setp.lt.u32 p,n,4194304; @p bra.uni WL%=; trap;\n"
                 "WD%=: }" ::"r"(a), "r"(ph) : "memory");
}
__device__ __forceinline__ void mbar_wait_cl(uint32_t a, int ph) {
    int it = 0;
    while (!mbar_try_cl(a, ph)) { if (++it > (1 << 22)) __trap(); }
}
__device__ __forceinline__ void bar_sync(int id, int n) { asm volatile("bar.sync %0,%1;" ::"r"(id), "r"(n) : "memory"); }
__device__ __forceinline__ void bar_arrive(int id, int n) { asm volatile("bar.arrive %0,%1;" ::"r"(id), "r"(n) : "memory"); }
__device__ __forceinline__ void cluster_sync() {
    asm volatile("barrier.cluster.arrive.release.aligned; barrier.cluster.wait.acquire.aligned;" ::: "memory");
}
__device__ __forceinline__ void fence_async() { asm volatile("fence.proxy.async.shared::cta;" ::: "memory"); }
__device__ __forceinline__ void ldsm4(uint32_t* r, uint32_t a) {
    asm volatile("ldmatrix.sync.aligned.m8n8.x4.shared.b16 {%0,%1,%2,%3},[%4];"
                 : "=r"(r[0]), "=r"(r[1]), "=r"(r[2]), "=r"(r[3]) : "r"(a) : "memory");
}
__device__ __forceinline__ void ldsm4t(uint32_t* r, uint32_t a) {
    asm volatile("ldmatrix.sync.aligned.m8n8.x4.trans.shared.b16 {%0,%1,%2,%3},[%4];"
                 : "=r"(r[0]), "=r"(r[1]), "=r"(r[2]), "=r"(r[3]) : "r"(a) : "memory");
}
__device__ __forceinline__ void ldsm2(uint32_t* r, uint32_t a) {
    asm volatile("ldmatrix.sync.aligned.m8n8.x2.shared.b16 {%0,%1},[%2];" : "=r"(r[0]), "=r"(r[1]) : "r"(a) : "memory");
}
__device__ __forceinline__ void ldsm2t(uint32_t* r, uint32_t a) {
    asm volatile("ldmatrix.sync.aligned.m8n8.x2.trans.shared.b16 {%0,%1},[%2];" : "=r"(r[0]), "=r"(r[1]) : "r"(a) : "memory");
}
__device__ __forceinline__ void mma16(float* c, const uint32_t* a, uint32_t b0, uint32_t b1) {
    asm("mma.sync.aligned.m16n8k16.row.col.f32.bf16.bf16.f32 {%0,%1,%2,%3},{%4,%5,%6,%7},{%8,%9},{%0,%1,%2,%3};"
                 : "+f"(c[0]), "+f"(c[1]), "+f"(c[2]), "+f"(c[3])
                 : "r"(a[0]), "r"(a[1]), "r"(a[2]), "r"(a[3]), "r"(b0), "r"(b1));
}
__device__ __forceinline__ void mma16v(float* c, const uint32_t* a, uint32_t b0, uint32_t b1) {
    asm volatile("mma.sync.aligned.m16n8k16.row.col.f32.bf16.bf16.f32 {%0,%1,%2,%3},{%4,%5,%6,%7},{%8,%9},{%0,%1,%2,%3};"
                 : "+f"(c[0]), "+f"(c[1]), "+f"(c[2]), "+f"(c[3])
                 : "r"(a[0]), "r"(a[1]), "r"(a[2]), "r"(a[3]), "r"(b0), "r"(b1));
}
__device__ __forceinline__ void mma8(float* c, uint32_t a0, uint32_t a1, uint32_t b0) {
    asm("mma.sync.aligned.m16n8k8.row.col.f32.bf16.bf16.f32 {%0,%1,%2,%3},{%4,%5},{%6},{%0,%1,%2,%3};"
                 : "+f"(c[0]), "+f"(c[1]), "+f"(c[2]), "+f"(c[3]) : "r"(a0), "r"(a1), "r"(b0));
}
__device__ __forceinline__ uint32_t pack2(float lo, float hi) {
    uint32_t r; asm("cvt.rn.bf16x2.f32 %0,%1,%2;" : "=r"(r) : "f"(hi), "f"(lo)); return r;
}
__device__ __forceinline__ float ex2(float x) { float y; asm("ex2.approx.ftz.f32 %0,%1;" : "=f"(y) : "f"(x)); return y; }
__device__ __forceinline__ void sts32(uint32_t a, uint32_t v) { asm volatile("st.shared.u32 [%0],%1;" ::"r"(a), "r"(v) : "memory"); }
__device__ __forceinline__ void sts32f(uint32_t a, float v) { asm volatile("st.shared.f32 [%0],%1;" ::"r"(a), "f"(v) : "memory"); }
__device__ __forceinline__ void sts128(uint32_t a, const uint32_t* v) {
    asm volatile("st.shared.v4.u32 [%0],{%1,%2,%3,%4};" ::"r"(a), "r"(v[0]), "r"(v[1]), "r"(v[2]), "r"(v[3]) : "memory");
}
__device__ __forceinline__ void lds128(uint32_t* v, uint32_t a) {
    asm volatile("ld.shared.v4.u32 {%0,%1,%2,%3},[%4];" : "=r"(v[0]), "=r"(v[1]), "=r"(v[2]), "=r"(v[3]) : "r"(a) : "memory");
}
__device__ __forceinline__ float2 lds64f(uint32_t a) {
    float2 v; asm volatile("ld.shared.v2.f32 {%0,%1},[%2];" : "=f"(v.x), "=f"(v.y) : "r"(a) : "memory"); return v;
}
__device__ __forceinline__ void tma2d(uint32_t dst, const CUtensorMap* m, int c0, int c1, uint32_t bar) {
    asm volatile("cp.async.bulk.tensor.2d.shared::cluster.global.mbarrier::complete_tx::bytes [%0],[%1,{%3,%4}],[%2];"
                 ::"r"(dst), "l"(m), "r"(bar), "r"(c0), "r"(c1) : "memory");
}
__device__ __forceinline__ void tma2d_mc(uint32_t dst, const CUtensorMap* m, int c0, int c1, uint32_t bar, uint16_t mask) {
    asm volatile("cp.async.bulk.tensor.2d.shared::cluster.global.mbarrier::complete_tx::bytes.multicast::cluster [%0],[%1,{%3,%4}],[%2],%5;"
                 ::"r"(dst), "l"(m), "r"(bar), "r"(c0), "r"(c1), "h"(mask) : "memory");
}
__device__ __forceinline__ uint64_t desc_sw128(uint32_t addr, uint32_t lbo, uint32_t sbo) {
    return (uint64_t)((addr & 0x3FFFF) >> 4) | ((uint64_t)(lbo >> 4) << 16) | ((uint64_t)(sbo >> 4) << 32) | (1ull << 62);
}
__device__ __forceinline__ void wg_fence() { asm volatile("wgmma.fence.sync.aligned;" ::: "memory"); }
__device__ __forceinline__ void wg_commit() { asm volatile("wgmma.commit_group.sync.aligned;" ::: "memory"); }
template <int N> __device__ __forceinline__ void wg_wait() { asm volatile("wgmma.wait_group.sync.aligned %0;" ::"n"(N) : "memory"); }

__device__ __forceinline__ void wgmma_rs_n32(float* d, const uint32_t* a, uint32_t dlo, int acc) {
    asm volatile("{.reg .pred p; .reg .b64 dd; setp.ne.b32 p,%21,0; mov.b64 dd,{%20,0x40000040};\n"
                 "wgmma.mma_async.sync.aligned.m64n32k16.f32.bf16.bf16 "
                 "{%0,%1,%2,%3,%4,%5,%6,%7,%8,%9,%10,%11,%12,%13,%14,%15},{%16,%17,%18,%19},dd,p,1,1,0;}"
                 : "+f"(d[0]), "+f"(d[1]), "+f"(d[2]), "+f"(d[3]), "+f"(d[4]), "+f"(d[5]), "+f"(d[6]), "+f"(d[7]),
                   "+f"(d[8]), "+f"(d[9]), "+f"(d[10]), "+f"(d[11]), "+f"(d[12]), "+f"(d[13]), "+f"(d[14]), "+f"(d[15])
                 : "r"(a[0]), "r"(a[1]), "r"(a[2]), "r"(a[3]), "r"(dlo), "r"(acc));
}

__device__ __forceinline__ void wgmma_ss_n32(float* d, uint32_t alo, uint32_t dlo, int acc) {
    asm volatile("{.reg .pred p; .reg .b64 da,dd; setp.ne.b32 p,%18,0; mov.b64 da,{%16,0x00000008}; mov.b64 dd,{%17,0x40000040};\n"
                 "wgmma.mma_async.sync.aligned.m64n32k16.f32.bf16.bf16 "
                 "{%0,%1,%2,%3,%4,%5,%6,%7,%8,%9,%10,%11,%12,%13,%14,%15},da,dd,p,1,1,0,0;}"
                 : "+f"(d[0]), "+f"(d[1]), "+f"(d[2]), "+f"(d[3]), "+f"(d[4]), "+f"(d[5]), "+f"(d[6]), "+f"(d[7]),
                   "+f"(d[8]), "+f"(d[9]), "+f"(d[10]), "+f"(d[11]), "+f"(d[12]), "+f"(d[13]), "+f"(d[14]), "+f"(d[15])
                 : "r"(alo), "r"(dlo), "r"(acc));
}

#define R8(b) "+f"(d[b]), "+f"(d[b + 1]), "+f"(d[b + 2]), "+f"(d[b + 3]), "+f"(d[b + 4]), "+f"(d[b + 5]), "+f"(d[b + 6]), "+f"(d[b + 7])
__device__ __forceinline__ void wgmma_ss_n192(float* d, uint64_t da, uint64_t db, int acc) {
    asm volatile("{.reg .pred p; setp.ne.b32 p,%98,0;\n"
                 "wgmma.mma_async.sync.aligned.m64n192k16.f32.bf16.bf16 "
                 "{%0,%1,%2,%3,%4,%5,%6,%7,%8,%9,%10,%11,%12,%13,%14,%15,%16,%17,%18,%19,%20,%21,%22,%23,"
                 "%24,%25,%26,%27,%28,%29,%30,%31,%32,%33,%34,%35,%36,%37,%38,%39,%40,%41,%42,%43,%44,%45,%46,%47,"
                 "%48,%49,%50,%51,%52,%53,%54,%55,%56,%57,%58,%59,%60,%61,%62,%63,%64,%65,%66,%67,%68,%69,%70,%71,"
                 "%72,%73,%74,%75,%76,%77,%78,%79,%80,%81,%82,%83,%84,%85,%86,%87,%88,%89,%90,%91,%92,%93,%94,%95},"
                 "%96,%97,p,1,1,0,1;}"
                 : R8(0), R8(8), R8(16), R8(24), R8(32), R8(40), R8(48), R8(56), R8(64), R8(72), R8(80), R8(88)
                 : "l"(da), "l"(db), "r"(acc));
}

#define NSS 1
#define WRES 2
#define QD 4
#define WCH 6
#define FA 0
#define QCH 4
#define WO_PRE3 4
#define WO_PRE 8
#define WO_PRE2 3
__device__ __forceinline__ void wgmma_ss_n64(float* d, uint64_t da, uint64_t db) {
    asm volatile("wgmma.mma_async.sync.aligned.m64n64k16.f32.bf16.bf16 "
                 "{%0,%1,%2,%3,%4,%5,%6,%7,%8,%9,%10,%11,%12,%13,%14,%15,%16,%17,%18,%19,%20,%21,%22,%23,"
                 "%24,%25,%26,%27,%28,%29,%30,%31},%32,%33,1,1,1,0,1;"
                 : R8(0), R8(8), R8(16), R8(24) : "l"(da), "l"(db));
}

constexpr int MP = 1168;
constexpr int XT = 36864;
constexpr int XR_STAGE = 14 * 1024;
constexpr int MR_STAGE = 14 * 256;
constexpr int SM_X = 0;
constexpr int SM_XR = 2 * XT;
constexpr int SM_MR = SM_XR + 3 * XR_STAGE;
constexpr int SM_MEM = SM_MR + 3 * MR_STAGE;
constexpr int SM_SC = SM_MEM + 8 * MP;
constexpr int SM_OB = SM_SC + 3 * 1536;
constexpr int SM_ZERO = SM_OB + 2048;
constexpr int SM_WO = SM_ZERO + 512;
constexpr int SM_WS = SM_WO + 49152;
constexpr int SM_BAR = SM_WS + NSS * 4096;
constexpr int REC_SMEM = SM_BAR + 512 + 1024;

__device__ uint4 g_xr[NSEG * NH * 24 * 64];
__device__ uint4 g_mr[NSEG * NH * 16 * 16];
__device__ unsigned g_flagA[NSEG];

#define FSP 0x111234a333ull
__host__ __device__ constexpr int f_split(int m) { return m < 3 ? 1 : (int)((FSP >> (4 * (12 - m))) & 15); }
constexpr int F_FIRST_SPLIT = f_split(3) > 1 ? 3 : (f_split(4) > 1 ? 4 : (f_split(5) > 1 ? 5 : 6));
struct RecParams {
    const bf16* mem0; const bf16* Wq; const bf16* Wk; const bf16* Wv; const bf16* Wo; const bf16* x; const bf16* wqkv;
    int d0, dv;
};

__device__ __forceinline__ float* red_line(int s, int line) { return g_red + ((s >> 3) * 192 + line) * 256 + (s & 7) * 32; }

#define PIN(x) asm volatile("" : "+r"(x))
#define PINL(x) asm volatile("" : "+l"(x))
__device__ __forceinline__ float4 ld_relaxed4(const float* q) {
    float4 v;
    asm volatile("ld.relaxed.gpu.global.v4.f32 {%0,%1,%2,%3},[%4];" : "=f"(v.x), "=f"(v.y), "=f"(v.z), "=f"(v.w) : "l"(q) : "memory");
    return v;
}
__device__ __forceinline__ void reld_relaxed4(float4& v, const float* q) {
    asm volatile("{.reg .pred p; setp.neu.f32 p,%3,0f42000000;\n"
                 "@p ld.relaxed.gpu.global.v4.f32 {%0,%1,%2,%3},[%4];}"
                 : "+f"(v.x), "+f"(v.y), "+f"(v.z), "+f"(v.w) : "l"(q) : "memory");
}
__device__ __forceinline__ unsigned ld_acq(const unsigned* q) {
    unsigned v; asm volatile("ld.acquire.gpu.global.u32 %0,[%1];" : "=r"(v) : "l"(q) : "memory"); return v;
}
__device__ __forceinline__ unsigned ld_relaxed1(const unsigned* q) {
    unsigned v; asm volatile("ld.relaxed.gpu.global.u32 %0,[%1];" : "=r"(v) : "l"(q) : "memory"); return v;
}
__device__ __forceinline__ uint4 ld_relaxed4u(const uint4* q) {
    uint4 v;
    asm volatile("ld.relaxed.gpu.global.v4.u32 {%0,%1,%2,%3},[%4];" : "=r"(v.x), "=r"(v.y), "=r"(v.z), "=r"(v.w) : "l"(q) : "memory");
    return v;
}
__device__ __forceinline__ void reld_relaxed4u(uint4& v, const uint4* q) {
    asm volatile("{.reg .pred p; .reg .b32 q; and.b32 q,%3,0xffff; setp.ne.u32 p,q,0x5000;\n"
                 "@p ld.relaxed.gpu.global.v4.u32 {%0,%1,%2,%3},[%4];}"
                 : "+r"(v.x), "+r"(v.y), "+r"(v.z), "+r"(v.w) : "l"(q) : "memory");
}
__device__ __forceinline__ uint32_t packh2(float lo, float hi) {
    uint32_t r; asm("cvt.rn.f16x2.f32 %0,%1,%2;" : "=r"(r) : "f"(hi), "f"(lo)); return r;
}
__device__ __forceinline__ float maxn(float a, float b) {
    float r; asm("max.NaN.f32 %0,%1,%2;" : "=f"(r) : "f"(fabsf(a)), "f"(fabsf(b))); return r;
}
__device__ __forceinline__ void redh4(uint4* q, const float* v, uint32_t tag) {
    asm volatile("red.relaxed.gpu.global.add.noftz.v4.f16x2 [%0],{%1,%2,%3,%4};"
                 ::"l"(q), "r"(packh2(v[0], v[1])), "r"(packh2(v[2], v[3])), "r"(packh2(v[4], v[5])), "r"(tag) : "memory");
}
__device__ __forceinline__ void red4(float* q, float a, float b, float c2, float d) {
    asm volatile("red.relaxed.gpu.global.add.v4.f32 [%0],{%1,%2,%3,%4};" ::"l"(q), "f"(a), "f"(b), "f"(c2), "f"(d) : "memory");
}
__device__ __forceinline__ unsigned clk32() { return (unsigned)clock64(); }
__device__ __forceinline__ void spin_until(unsigned tl) {
    asm volatile("{.reg .pred p; .reg .u64 c; .reg .u32 lo,hi; .reg .s32 d;\n"
                 "SP%=: mov.u64 c,%%clock64; mov.b64 {lo,hi},c; sub.s32 d,lo,%0; setp.lt.s32 p,d,0; @p bra.uni SP%=;}" ::"r"(tl) : "memory");
}
__device__ __forceinline__ unsigned gtime() { unsigned v; asm volatile("mov.u32 %0,%%globaltimer_lo;" : "=r"(v)); return v; }
__device__ __forceinline__ float rcp_fast(float x) { float y; asm("rcp.approx.ftz.f32 %0,%1;" : "=f"(y) : "f"(x)); return y; }
__device__ __forceinline__ void bulk_store(void* gdst, uint32_t src, int bytes) {
    asm volatile("cp.async.bulk.global.shared::cta.bulk_group [%0],[%1],%2;" ::"l"(gdst), "r"(src), "r"(bytes) : "memory");
}
__device__ __forceinline__ void bulk_load(uint32_t dst, const void* gsrc, int bytes, uint32_t bar) {
    asm volatile("cp.async.bulk.shared::cluster.global.mbarrier::complete_tx::bytes [%0],[%1],%2,[%3];"
                 ::"r"(dst), "l"(gsrc), "r"(bytes), "r"(bar) : "memory");
}
__device__ __forceinline__ void bulk_load_mc(uint32_t dst, const void* gsrc, int bytes, uint32_t bar, uint16_t mask) {
    asm volatile("cp.async.bulk.shared::cluster.global.mbarrier::complete_tx::bytes.multicast::cluster [%0],[%1],%2,[%3],%4;"
                 ::"r"(dst), "l"(gsrc), "r"(bytes), "r"(bar), "h"(mask) : "memory");
}

__device__ __forceinline__ void bulk_s2s(uint32_t rdst, uint32_t src, int bytes, uint32_t rbar) {
    asm volatile("cp.async.bulk.shared::cluster.shared::cta.mbarrier::complete_tx::bytes [%0],[%1],%2,[%3];"
                 ::"r"(rdst), "r"(src), "r"(bytes), "r"(rbar) : "memory");
}
__device__ __forceinline__ void stas4(uint32_t rdst, uint32_t a, uint32_t b, uint32_t c2, uint32_t d, uint32_t rbar) {
    asm volatile("st.async.weak.shared::cluster.mbarrier::complete_tx::bytes.v4.b32 [%0],{%1,%2,%3,%4},[%5];"
                 ::"r"(rdst), "r"(a), "r"(b), "r"(c2), "r"(d), "r"(rbar) : "memory");
}
__device__ __forceinline__ void stas2(uint32_t rdst, uint32_t a, uint32_t b, uint32_t rbar) {
    asm volatile("st.async.weak.shared::cluster.mbarrier::complete_tx::bytes.v2.b32 [%0],{%1,%2},[%3];"
                 ::"r"(rdst), "r"(a), "r"(b), "r"(rbar) : "memory");
}
__device__ __forceinline__ float4 lds128f(uint32_t a) {
    float4 v; asm volatile("ld.shared.v4.f32 {%0,%1,%2,%3},[%4];" : "=f"(v.x), "=f"(v.y), "=f"(v.z), "=f"(v.w) : "r"(a) : "memory"); return v;
}

__device__ __forceinline__ void flag_seg(int seg) {
    asm volatile("cp.async.bulk.wait_group 0;" ::: "memory");
    asm volatile("red.relaxed.gpu.global.add.u32 [%0],1;" ::"l"(g_flagA + seg) : "memory");
}

__global__ void __launch_bounds__(384, 1) k_rec(const __grid_constant__ CUtensorMap tmx, const RecParams p) {
    extern __shared__ uint8_t smem_raw[];
    const uint32_t sb = (s2u(smem_raw) + 1023) & ~1023u;
    const int tid = threadIdx.x, warp = __shfl_sync(0xffffffffu, tid >> 5, 0), lane = tid & 31, g = lane >> 2, t = lane & 3;
    const int l7 = lane & 7, l3 = lane >> 3;
    const int c = blockIdx.x % 3, h = blockIdx.x / 3;
    const int nq = c < 2 ? 3 : 2, nv = 8 - 2 * nq, v0 = 2 * c;
    const uint32_t bXF = sb + SM_BAR, bVX = bXF + 16, bS = bVX + 16, bV = bS + 8, bC = bV + 8;
    const uint32_t peer1 = (c + 1) % 3, peer2 = (c + 2) % 3;
    auto vslot = [](int r, int d) { return (r < 2 ? 6 : 4) + ((d - 2 * r) & 7); };

    if (tid == 1) asm volatile("cp.async.bulk.prefetch.L2.global [%0],20736;" ::"l"(reinterpret_cast<const uint8_t*>(p.wqkv) + (size_t)blockIdx.x * 20736) : "memory");
    if (tid == 33) asm volatile("cp.async.bulk.prefetch.L2.global [%0],9216;" ::"l"(reinterpret_cast<const uint8_t*>(p.x) + (size_t)blockIdx.x * 9216) : "memory");
    __syncthreads();
    if (lane == 0) {
        const int wsel = warp / 3;
        const bf16* W = wsel == 0 ? p.Wq : (wsel == 1 ? p.Wk : (wsel == 2 ? p.Wv : p.Wo));
        asm volatile("cp.async.bulk.prefetch.L2.global [%0],16384;" ::"l"(reinterpret_cast<const uint8_t*>(W) + (size_t)((warp % 3) * 96 + blockIdx.x) * 16384) : "memory");
    }
    if (tid == 0) {
        for (int i = 0; i < 2; i++) { mbar_init(bXF + 8 * i, 1); mbar_init(bVX + 8 * i, 1); }
        mbar_init(bS, 4); mbar_init(bV, nv + 1);
        asm volatile("fence.mbarrier_init.release.cluster;" ::: "memory");
        for (int i = 0; i < 2; i++) { mbar_expect(bXF + 8 * i, XT); mbar_expect(bVX + 8 * i, (8 - nv) * 1024); }
        mbar_expect(bS, 2560); mbar_expect(bV, (8 - nv) * 256);
    }
    if (blockIdx.x == 0) {
        for (int i = tid; i < 1920; i += 384) g_ctr[i] = 0;
        if (tid < NSEG) g_flagA[tid] = 0;
        __threadfence();
    }
    __syncthreads();
    asm volatile("griddepcontrol.launch_dependents;" ::: "memory");
    cluster_sync();

    if (warp < 8) {
        asm volatile("setmaxnreg.inc.sync.aligned.u32 %0;" ::"n"(NSS == 3 ? 176 : 184));
        if (tid == 0) {
            for (int sl = 0; sl < 2; sl++)
                for (int j = 0; j < 3; j++)
                    tma2d_mc(sb + SM_X + sl * XT + (c * 3 + j) * 4096, &tmx, (c * 3 + j) * 64, sl * 32, bXF + 8 * sl, 7);
        }
        const bool isv = warp >= 2 * nq;
        const int slot = warp;
        uint32_t w[36][4];
        {
            const int dt = isv ? v0 + warp - 2 * nq : 3 * c + (warp >= nq ? warp - nq : warp);
            const bf16* W = (isv ? p.Wv : (warp >= nq ? p.Wk : p.Wq)) + h * DH + dt * 16 + 2 * g + (size_t)(2 * t) * HD;
#pragma unroll
            for (int k = 0; k < 36; k++) {
                const uint32_t* q = reinterpret_cast<const uint32_t*>(W + (size_t)k * 16 * HD);
                w[k][0] = __ldg(q); w[k][1] = __ldg(q + HD / 2); w[k][2] = __ldg(q + 4 * HD); w[k][3] = __ldg(q + 4 * HD + HD / 2);
            }
#pragma unroll
            for (int k = 0; k < 36; k++) {
                uint32_t a = w[k][0], b = w[k][1], d = w[k][2], e = w[k][3];
                w[k][0] = __byte_perm(a, b, 0x5410); w[k][1] = __byte_perm(a, b, 0x7632);
                w[k][2] = __byte_perm(d, e, 0x5410); w[k][3] = __byte_perm(d, e, 0x7632);
            }
#pragma unroll
            for (int k = 0; k < NSS; k++) {
                const uint32_t a = sb + SM_WS + k * 4096 + (warp >> 2) * 2048 + (warp & 3) * 256 + lane * 4;
                sts32(a, w[36 - NSS + k][0]); sts32(a + 128, w[36 - NSS + k][1]);
                sts32(a + 1024, w[36 - NSS + k][2]); sts32(a + 1152, w[36 - NSS + k][3]);
            }
            fence_async();
            bar_sync(9, 256);
        }
        const uint32_t wsd = (((sb + SM_WS + (warp >> 2) * 2048) & 0x3FFFF) >> 4) | (64u << 16);
        const uint32_t woff = 2 * t * 32 + (((g >> 2) ^ (t >> 1)) << 4) + (g & 3) * 4;

        float d[16];
        auto xdesc = [&](int sl) { return __shfl_sync(0xffffffffu, (((sb + SM_X + sl * XT) & 0x3FFFF) >> 4) | 0x10000u, 0); };
        auto fill_a = [&](uint32_t xd) {
            wg_fence();
#pragma unroll
            for (int k = 0; k < FA; k++) wgmma_rs_n32(d, w[k], xd + ((k >> 2) * 256 + (k & 3) * 2), k > 0);
            wg_commit();
        };
        auto fill_b = [&](uint32_t xd, int stg) {
            wg_fence();
#pragma unroll
            for (int k = 36 - NSS; k < 36; k++) wgmma_ss_n32(d, wsd + (k - 36 + NSS) * 256, xd + ((k >> 2) * 256 + (k & 3) * 2), FA > 0 || k > 36 - NSS);
#pragma unroll
            for (int k = FA; k < 36 - NSS; k++) wgmma_rs_n32(d, w[k], xd + ((k >> 2) * 256 + (k & 3) * 2), 1);
            wg_commit();
            wg_wait<0>();
            const uint32_t dst = sb + SM_XR + stg * XR_STAGE + slot * 1024 + woff;
#pragma unroll
            for (int j = 0; j < 4; j++) {
                sts32(dst + j * 256, pack2(d[4 * j], d[4 * j + 2]));
                sts32(dst + j * 256 + 32, pack2(d[4 * j + 1], d[4 * j + 3]));
            }
        };
        auto fwd_v = [&](int sl, int stg) {
            const uint32_t base = sb + SM_XR + stg * XR_STAGE;
            bulk_s2s(mapa(base + vslot(peer1, v0) * 1024, peer1), base + 2 * nq * 1024, nv * 1024, mapa(bVX + 8 * sl, peer1));
            bulk_s2s(mapa(base + vslot(peer2, v0) * 1024, peer2), base + 2 * nq * 1024, nv * 1024, mapa(bVX + 8 * sl, peer2));
        };

        mbar_wait(bXF, 0);
        if (FA) fill_a(xdesc(0));
        fill_b(xdesc(0), 0);
        fence_async();
        bar_sync(9, 256);
        if (tid == 32) fwd_v(0, 0);
        __syncwarp();
        mbar_wait(bXF + 8, 0);
        if (FA) fill_a(xdesc(1));
        fill_b(xdesc(1), 1);
        bar_sync(9, 256);
        if (tid == 0) { mbar_expect(bXF, XT); mbar_expect(bXF + 8, XT); }
        cluster_sync();
        if (tid == 0) {
            for (int sl = 0; sl < 2; sl++)
                for (int j = 0; j < 3; j++)
                    tma2d_mc(sb + SM_X + sl * XT + (c * 3 + j) * 4096, &tmx, (c * 3 + j) * 64, (2 + sl) * 32, bXF + 8 * sl, 7);
        }
        __syncwarp();
        uint32_t mema = sb + SM_MEM + l7 * MP + l3 * 16;
        const uint32_t xpeer = (g & 2) ? peer2 : peer1;
        const uint32_t rdst0 = mapa(sb + SM_MR + vslot(xpeer, v0 + warp - 2 * nq) * 256 + (2 * t + (g & 1)) * 32 + (((g >> 2) ^ (t >> 1)) << 4), xpeer);
        uint32_t rbar = mapa(bV, xpeer);
        int s3 = 0;
        for (int s = 0; s < NSEG; s++) {
            const int st = s & 1, s3n = s3 == 2 ? 0 : s3 + 1, s3p = s3 == 0 ? 2 : s3 - 1;
            uint32_t rdst = rdst0 + s3 * MR_STAGE;
            uint32_t ldst = sb + SM_MR + s3 * MR_STAGE + slot * 256 + woff;
            PIN(rdst); PIN(rbar); PIN(ldst); PIN(mema);
            float a[QCH][4];
#pragma unroll
            for (int i = 0; i < QCH; i++) { a[i][0] = 0.f; a[i][1] = 0.f; a[i][2] = 0.f; a[i][3] = 0.f; }
            uint32_t wx[NSS][4];
#pragma unroll
            for (int k = 0; k < NSS; k++)
                ldsm4(wx[k], sb + SM_WS + k * 4096 + (warp >> 2) * 2048 + (warp & 3) * 256 + (l3 >> 1) * 1024 + (l3 & 1) * 128 + l7 * 16);
            bar_sync(1, 384);
            if (isv) spin_until(clk32() + p.dv);
            PROFT(24, 0);
            uint32_t bf[18][4];
#pragma unroll
            for (int ii = 0; ii < QD; ii++) ldsm4(bf[17 - ii], mema + (17 - ii) * 64);
#pragma unroll
            for (int ii = 0; ii < 18; ii++) {
                const int i = 17 - ii;
                mma16v(a[(2 * i) % QCH], 2 * i >= 36 - NSS ? wx[2 * i - 36 + NSS] : w[2 * i], bf[i][0], bf[i][1]);
                mma16v(a[(2 * i + 1) % QCH], 2 * i + 1 >= 36 - NSS ? wx[2 * i + 1 - 36 + NSS] : w[2 * i + 1], bf[i][2], bf[i][3]);
                if (i - QD >= 0) ldsm4(bf[i - QD], mema + (i - QD) * 64);
            }
#pragma unroll
            for (int i = 0; i < 4; i++) {
                if (QCH == 4) a[0][i] = (a[2][i] + a[3][i]) + (a[0][i] + a[1][i]);
                if (QCH == 3) a[0][i] = (a[0][i] + a[1][i]) + a[2][i];
                if (QCH == 2) a[0][i] += a[1][i];
            }
            const uint32_t w0 = pack2(a[0][0], a[0][2]), w1 = pack2(a[0][1], a[0][3]);
            sts32(ldst, w0); sts32(ldst + 32, w1);
            if (!isv) bar_arrive(8, nq * 64 + 96);
            PROF(1);
            if (isv && s + 1 < NSEG) {
                uint32_t snd = (g & 1) ? w0 : w1, keep = (g & 1) ? w1 : w0;
                uint32_t rcv = __shfl_xor_sync(0xffffffffu, snd, 4);
                uint32_t lo = (g & 1) ? rcv : keep, hi = (g & 1) ? keep : rcv;
                uint32_t olo = __shfl_xor_sync(0xffffffffu, lo, 8), ohi = __shfl_xor_sync(0xffffffffu, hi, 8);
                stas4(rdst, (g & 2) ? olo : lo, (g & 2) ? ohi : hi, (g & 2) ? lo : olo, (g & 2) ? hi : ohi, rbar);
                __syncwarp();
                if (lane == 0) mbar_arrive(bV);
            }
            const uint32_t xd = xdesc(st);
            if (s + 2 < NSEG) {
                mbar_wait(bXF + 8 * st, ((s + 2) >> 1) & 1);
                if (FA) {
                    bar_sync(10, 352);
                    fill_a(xd);
                    wg_wait<0>();
                }
            }
            fence_async();
            bar_arrive(7, 288);
            if (warp == 1) bar_sync(6, 256); else bar_arrive(6, 256);
            if (warp < 2) {
                if (s + 1 < NSEG) { mbar_wait(bS, st); mbar_wait(bV, st); }
                if (lane == 0) {
                    if (warp == 0) {
                        if (s >= 1 && s + 3 < NSEG) {
                            mbar_expect(bXF + 8 * (st ^ 1), XT);
                            for (int j = 0; j < 3; j++)
                                tma2d_mc(sb + SM_X + (st ^ 1) * XT + (c * 3 + j) * 4096, &tmx, (c * 3 + j) * 64, (s + 3) * 32, bXF + 8 * (st ^ 1), 7);
                        }
                    } else {
                        if (s >= 1) flag_seg(s - 1);
                        bulk_store(reinterpret_cast<uint8_t*>(g_mr) + (size_t)(s * 32 + h) * 4096 + c * 1280,
                                   sb + SM_MR + s3 * MR_STAGE + nq * 256, (8 - nq) * 256);
                        asm volatile("cp.async.bulk.commit_group;" ::: "memory");
                        if (s + 2 < NSEG) fwd_v(st ^ 1, s3n);
                    }
                }
                __syncwarp();
            }
            PROFT(13, 96);
            PROFDUMP();
            if (s + 2 < NSEG) {
                bar_sync(5, 384);
                fill_b(xd, s3p);
                PROF(4);
            } else {
                bar_sync(5, 384);
            }
            s3 = s3n;
        }
        if (tid == 32) flag_seg(NSEG - 1);
    } else {
        asm volatile("setmaxnreg.dec.sync.aligned.u32 %0;" ::"n"(NSS == 3 ? 152 : 136));
        const int wq = warp - 8, wt = tid - 256;
        uint32_t woa = sb + SM_WO + wt * 16;
        uint32_t am0 = 0;
        {
            for (int i = wt; i < 576; i += 128) g_redh[blockIdx.x * 576 + i] = make_uint4(0u, 0u, 0u, 0u);
            float4* z = reinterpret_cast<float4*>(g_red) + blockIdx.x * 1024;
            for (int i = wt; i < 1024; i += 128) z[i] = make_float4(0.f, 0.f, 0.f, 0.f);
            constexpr int ZN = (SEQ - F_FIRST_SPLIT * 192) * (DM / 4) / 96;
            float4* za = reinterpret_cast<float4*>(g_acc + F_FIRST_SPLIT * 192 * DM) + blockIdx.x * ZN;
            for (int i = wt; i < ZN; i += 128) za[i] = make_float4(0.f, 0.f, 0.f, 0.f);
            __threadfence();
            bar_sync(4, 128);
            if (wt == 0) asm volatile("red.relaxed.gpu.global.add.u32 [%0],1;" ::"l"(g_sync) : "memory");
        }
        {
            const bf16* W = p.Wo + (size_t)(h * DH + 2 * t) * DM + c * 192 + wq * 16 + 2 * g;
            uint32_t wo[24][4];
#pragma unroll
            for (int k = 0; k < 24; k++) {
                const uint32_t* q = reinterpret_cast<const uint32_t*>(W + (k & 7) * 16 * DM + (k >> 3) * 64);
                wo[k][0] = __ldg(q); wo[k][1] = __ldg(q + DM / 2);
                wo[k][2] = __ldg(q + 4 * DM); wo[k][3] = __ldg(q + 4 * DM + DM / 2);
            }
#pragma unroll
            for (int k = 0; k < 24; k++) {
                uint32_t a = wo[k][0], b = wo[k][1], d = wo[k][2], e = wo[k][3];
                wo[k][0] = __byte_perm(a, b, 0x5410); wo[k][1] = __byte_perm(a, b, 0x7632);
                wo[k][2] = __byte_perm(d, e, 0x5410); wo[k][3] = __byte_perm(d, e, 0x7632);
                sts128(woa + k * 2048, wo[k]);
            }
            sts32(sb + SM_ZERO + wt * 4, 0u);
            for (int i = wt; i < 8 * 72; i += 128) {
                const int r = i / 72, cc = i % 72;
                uint4 v = __ldg(reinterpret_cast<const uint4*>(p.mem0 + r * DM) + cc);
                am0 = __vmaxu2(__vmaxu2(am0, __vmaxu2(v.x & 0x7fff7fffu, v.y & 0x7fff7fffu)), __vmaxu2(v.z & 0x7fff7fffu, v.w & 0x7fff7fffu));
                asm volatile("st.shared.v4.u32 [%0],{%1,%2,%3,%4};" ::"r"(sb + SM_MEM + r * MP + cc * 16), "r"(v.x), "r"(v.y), "r"(v.z), "r"(v.w) : "memory");
            }
        }
        cluster_sync();
        bar_arrive(1, 384);
        uint32_t wa[8][4], wb[8][4], wc[WRES + 1][4];
#pragma unroll
        for (int k = 0; k < 8; k++) lds128(wa[k], woa + k * 2048);
#pragma unroll
        for (int k = 0; k < 8; k++) lds128(wb[k], woa + (8 + k) * 2048);
#pragma unroll
        for (int k = 0; k < WRES; k++) lds128(wc[k], woa + (16 + k) * 2048);

        int ex;
        {
            const uint32_t m = __reduce_max_sync(0xffffffffu, max(am0 & 0xffffu, am0 >> 16));
            ex = m ? min(max(4 - ((int)(m >> 7) - 127), -60), 60) : 0;
        }
        const float SC = 0.08838834764831845f * 1.4426950408889634f;
        uint32_t L16 = lane * 16;
        uint32_t AB = (l3 >> 1) * 256 + l7 * 32 + (((l3 & 1) ^ (l7 >> 2)) << 4);
        uint32_t AA = (l3 & 1) * 256 + l7 * 32 + (((l3 >> 1) ^ (l7 >> 2)) << 4);
        const uint32_t scu = sb + SM_SC + c * 1536 + (wq == 0 ? 1024 : (wq - 1) * 512);
        const uint32_t sc1 = mapa(scu, peer1), sc2 = mapa(scu, peer2), sb1 = mapa(bS, peer1), sb2 = mapa(bS, peer2);
        const uint32_t wou = sb + SM_WO + wq * 512;
        const int vs = vslot(c, 2 * wq);
        auto publish = [&](int xs, int stg) {
            if (xs >= 1) flag_seg(xs - 1);
            if (xs < NSEG) {
                bulk_store(reinterpret_cast<uint8_t*>(g_xr) + (size_t)(xs * 96 + blockIdx.x) * 8192, sb + SM_XR + stg * XR_STAGE, 8192);
                asm volatile("cp.async.bulk.commit_group;" ::: "memory");
            }
        };
        int s3 = 0;
        for (int s = 0; s + 1 < NSEG; s++) {
            const int st = s & 1;
            const uint32_t xr = sb + SM_XR + s3 * XR_STAGE, mr = sb + SM_MR + s3 * MR_STAGE;
            PIN(L16); PIN(AB); PIN(AA);
            if (wq < 3) {
                uint32_t kf[3][4], q0[4], q1[4];
                float ca[4] = {0.f, 0.f, 0.f, 0.f}, cb[4] = {0.f, 0.f, 0.f, 0.f}, cc[4] = {0.f, 0.f, 0.f, 0.f};
                if (wq) {
                    const uint32_t ka = xr + nq * 1024 + (wq - 1) * 512 + AB;
                    ldsm4(kf[0], ka); ldsm4(kf[1], ka + 1024); ldsm4(kf[2], nq == 3 ? ka + 2048 : sb + SM_ZERO + AB);
                    uint32_t da1 = sc1 + L16, da2 = sc2 + L16, qa = mr + AA;
                    PIN(da1); PIN(da2); PIN(qa);
                    bar_sync(8, nq * 64 + 96);
                    ldsm4(q0, qa); ldsm4(q1, qa + 512);
                    float da[4] = {0.f, 0.f, 0.f, 0.f}, db[4] = {0.f, 0.f, 0.f, 0.f}, dc[4] = {0.f, 0.f, 0.f, 0.f};
                    mma16(ca, q0, kf[0][0], kf[0][1]); mma16(da, q0, kf[0][2], kf[0][3]);
                    mma16(cb, q0, kf[1][0], kf[1][1]); mma16(db, q0, kf[1][2], kf[1][3]);
                    mma16(cc, q1, kf[2][0], kf[2][1]); mma16(dc, q1, kf[2][2], kf[2][3]);
                    const uint32_t rr[4] = {__float_as_uint((ca[0] + cb[2]) + cc[0]), __float_as_uint((ca[1] + cb[3]) + cc[1]),
                                            __float_as_uint((da[0] + db[2]) + dc[0]), __float_as_uint((da[1] + db[3]) + dc[1])};
                    stas4(da1, rr[0], rr[1], rr[2], rr[3], sb1); stas4(da2, rr[0], rr[1], rr[2], rr[3], sb2);
                    sts128(scu + L16, rr);
                } else {
                    uint32_t da1 = sc1 + (L16 >> 1), da2 = sc2 + (L16 >> 1), qa = mr + AA, ka = mr + nq * 256 + AB;
                    uint32_t kb = nq == 3 ? ka + 512 : sb + SM_ZERO + AB;
                    PIN(da1); PIN(da2); PIN(qa); PIN(ka); PIN(kb);
                    bar_sync(8, nq * 64 + 96);
                    ldsm4(q0, qa); ldsm4(kf[0], ka); ldsm4(q1, qa + 512); ldsm2(kf[1], kb);
                    mma16(ca, q0, kf[0][0], kf[0][1]); mma16(cb, q0, kf[0][2], kf[0][3]); mma16(cc, q1, kf[1][0], kf[1][1]);
                    const uint32_t r0 = __float_as_uint((ca[0] + cb[2]) + cc[0]), r1 = __float_as_uint((ca[1] + cb[3]) + cc[1]);
                    stas2(da1, r0, r1, sb1); stas2(da2, r0, r1, sb2);
                    asm volatile("st.shared.v2.u32 [%0],{%1,%2};" ::"r"(scu + (L16 >> 1)), "r"(r0), "r"(r1) : "memory");
                }
                __syncwarp();
                if (L16 == 0) mbar_arrive(bS);
                if (FA && s + 2 < NSEG) bar_arrive(10, 352);
                PROF(3);
            } else {
                if (lane == 0) {
                    asm volatile("prefetch.global.L2 [%0];" ::"l"(g_redh + ((((s + 3) & 63) >> 3) * 96 + blockIdx.x) * 72 + ((s + 3) & 7) * 8));
                    publish(s, s3);
                    if (s == 0) {
                        int it = 0;
                        while (ld_acq(g_sync) < 96) { if (++it > (1 << 22)) __trap(); }
                    }
                }
                __syncwarp();
            }
            uint32_t va[2][2][4], vb[4];
            mbar_wait(bVX + 8 * st, (s >> 1) & 1);
            const uint32_t v0a = xr + vs * 1024 + AB;
            ldsm4t(va[0][0], v0a); ldsm4t(va[1][0], v0a + 1024);
            uint4* rl = g_redh + (((s >> 3) * 96 + c * 32 + wq * 4) * 9 + (s & 7)) * 8 + (L16 >> 7) * 72 + ((L16 >> 4) & 7);
            PINL(rl);
            mbar_wait(bS, s & 1);
            PROF(5);
            float4 sa, sbb; float2 sm2;
            {
                const uint32_t scl = sb + SM_SC + L16;
                const float4 a0 = lds128f(scl), a1 = lds128f(scl + 1536), a2 = lds128f(scl + 3072);
                const float4 b0 = lds128f(scl + 512), b1 = lds128f(scl + 2048), b2 = lds128f(scl + 3584);
                const uint32_t scm = sb + SM_SC + 1024 + (L16 >> 1);
                const float2 m0 = lds64f(scm), m1 = lds64f(scm + 1536), m2 = lds64f(scm + 3072);
                sa.x = a0.x + a1.x + a2.x; sa.y = a0.y + a1.y + a2.y; sa.z = a0.z + a1.z + a2.z; sa.w = a0.w + a1.w + a2.w;
                sbb.x = b0.x + b1.x + b2.x; sbb.y = b0.y + b1.y + b2.y; sbb.z = b0.z + b1.z + b2.z; sbb.w = b0.w + b1.w + b2.w;
                sm2.x = m0.x + m1.x + m2.x; sm2.y = m0.y + m1.y + m2.y;
            }
            float mx = fmaxf(fmaxf(fmaxf(sa.x, sa.y), fmaxf(sa.z, sa.w)), fmaxf(fmaxf(sbb.x, sbb.y), fmaxf(sbb.z, sbb.w)));
            mx = fmaxf(mx, fmaxf(sm2.x, sm2.y));
            {
                const float x1 = __shfl_xor_sync(0xffffffffu, mx, 1), x2 = __shfl_xor_sync(0xffffffffu, mx, 2), x3 = __shfl_xor_sync(0xffffffffu, mx, 3);
                ldsm4t(va[0][1], v0a + 512); ldsm4t(va[1][1], v0a + 1024 + 512);
                mbar_wait(bV, s & 1);
                ldsm4t(vb, mr + vs * 256 + AB);
                mx = fmaxf(fmaxf(mx, x1), fmaxf(x2, x3));
            }
            PROF(6);
            uint32_t ws[8][4];
#pragma unroll
            for (int k = WRES; k < WRES + WO_PRE2 && k < 8; k++) lds128(ws[k], wou + L16 + (16 + k) * 2048);
            const float mo = mx * SC;
            const float e0 = ex2(fmaf(sa.x, SC, -mo)), e1 = ex2(fmaf(sa.y, SC, -mo)), e2 = ex2(fmaf(sa.z, SC, -mo)), e3 = ex2(fmaf(sa.w, SC, -mo));
            float o0[4] = {0.f, 0.f, 0.f, 0.f}, o1[4] = {0.f, 0.f, 0.f, 0.f}, o2[4] = {0.f, 0.f, 0.f, 0.f};
            const uint32_t one = 0x3f803f80u, one4[4] = {one, one, one, one};
            { const uint32_t p0 = pack2(e0, e1), p1 = pack2(e2, e3); mma16(o0, va[0][0], p0, p1); mma16(o1, va[1][0], p0, p1); mma16(o2, one4, p0, p1); }
            const float e4 = ex2(fmaf(sbb.x, SC, -mo)), e5 = ex2(fmaf(sbb.y, SC, -mo)), e6 = ex2(fmaf(sbb.z, SC, -mo)), e7 = ex2(fmaf(sbb.w, SC, -mo));
            { const uint32_t p0 = pack2(e4, e5), p1 = pack2(e6, e7); mma16(o0, va[0][1], p0, p1); mma16(o1, va[1][1], p0, p1); mma16(o2, one4, p0, p1); }
            const float e8 = ex2(fmaf(sm2.x, SC, -mo)), e9 = ex2(fmaf(sm2.y, SC, -mo));
            { const uint32_t p0 = pack2(e8, e9); mma8(o0, vb[0], vb[1], p0); mma8(o1, vb[2], vb[3], p0); mma8(o2, one, one, p0); }
            {
                const uint32_t oa = sb + SM_OB + wq * 512 + (L16 >> 2);
                sts32(oa, pack2(o0[0], o0[1])); sts32(oa + 128, pack2(o0[2], o0[3]));
                sts32(oa + 256, pack2(o1[0], o1[1])); sts32(oa + 384, pack2(o1[2], o1[3]));
            }
            bar_sync(4, 128);
            uint32_t ob[4][4];
#pragma unroll
            for (int j = 0; j < 4; j++) ldsm4t(ob[j], sb + SM_OB + L16 + 512 * j);
            const float fs = __int_as_float((127 + ex) << 23);
            const float i0 = rcp_fast(o2[0]) * fs, i1 = rcp_fast(o2[1]) * fs;
            PROF(7);
            float v[12];
            {
                float r[6][4];
#pragma unroll
                for (int i = 0; i < 6; i++) { r[i][0] = 0.f; r[i][1] = 0.f; r[i][2] = 0.f; r[i][3] = 0.f; }
#pragma unroll
                for (int k = WRES + WO_PRE2; k < WRES + WO_PRE3 && k < 8; k++) lds128(ws[k], wou + L16 + (16 + k) * 2048);
#pragma unroll
                for (int i = 0; i < 8; i++) {
                    mma16v(r[(WCH > 3 && (i & 1)) ? 3 : 0], wa[i], ob[i >> 1][(i & 1) * 2], ob[i >> 1][(i & 1) * 2 + 1]);
                    mma16v(r[(WCH > 4 && (i & 1)) ? 4 : 1], wb[i], ob[i >> 1][(i & 1) * 2], ob[i >> 1][(i & 1) * 2 + 1]);
                    mma16v(r[(WCH > 5 && (i & 1)) ? 5 : 2], i < WRES ? wc[i] : ws[i], ob[i >> 1][(i & 1) * 2], ob[i >> 1][(i & 1) * 2 + 1]);
                    if (i + WRES + WO_PRE3 < 8) lds128(ws[i + WRES + WO_PRE3], wou + L16 + (16 + i + WRES + WO_PRE3) * 2048);
                }
#pragma unroll
                for (int j = 0; j < 3; j++) {
                    if (WCH > 3 + j) { r[j][0] += r[3 + j][0]; r[j][1] += r[3 + j][1]; r[j][2] += r[3 + j][2]; r[j][3] += r[3 + j][3]; }
                    v[4 * j] = r[j][0] * i0; v[4 * j + 1] = r[j][2] * i0; v[4 * j + 2] = r[j][1] * i1; v[4 * j + 3] = r[j][3] * i1;
                }
                const float m8 = maxn(maxn(maxn(v[0], v[1]), maxn(v[2], v[3])), maxn(maxn(v[4], v[5]), maxn(v[6], v[7])));
                const float m = maxn(maxn(maxn(v[8], v[9]), maxn(v[10], v[11])), m8);
                const uint32_t tag = m < 1024.f ? (m >= 0.00390625f ? 0x3c003c00u : 0x00003c00u) : 0x54003c00u;
                redh4(rl, v, tag);
                bar_arrive(5, 384);
                redh4(rl + 16 * 72, v + 6, tag);
            }
            const unsigned tred = clk32();
            if (wq == 3) bar_sync(7, 288);
            PROF(8);
            if (wt == 0) {
                if (s + 2 < NSEG) { mbar_expect(bS, 2560); mbar_expect(bV, (8 - nv) * 256); }
                if (s + 3 < NSEG) mbar_expect(bVX + 8 * st, (8 - nv) * 1024);
            }
            {
                const uint4* gl = rl - c * 32 * 72;
                uint32_t ma = sb + SM_MEM + wq * 32 + ((L16 >> 4) & 3) * (2 * MP) + (L16 >> 6) * 4;
                PINL(gl); PIN(ma);
                unsigned tl = tred + p.d0;
                spin_until(tl);
                PROF(9);
                uint4 u[2][3];
#pragma unroll
                for (int j = 0; j < 2; j++)
#pragma unroll
                    for (int cc = 0; cc < 3; cc++) u[j][cc] = ld_relaxed4u(gl + (cc * 32 + j * 16) * 72);
                const uint32_t rebias = (uint32_t)(112 - ex) * 0x00800080u;
                int it = 0;
                auto cvt = [&](uint32_t x) { return ((((x + 0x00040004u) & 0x7ff87ff8u) >> 3) + rebias) | (x & 0x80008000u); };
                auto put = [&](int j, int cc) {
                    sts32(ma + (cc * 192 + ((3 * j) >> 1) * 64) * 2 + ((3 * j) & 1) * MP, u[j][cc].x);
                    sts32(ma + (cc * 192 + ((3 * j + 1) >> 1) * 64) * 2 + ((3 * j + 1) & 1) * MP, u[j][cc].y);
                    sts32(ma + (cc * 192 + ((3 * j + 2) >> 1) * 64) * 2 + ((3 * j + 2) & 1) * MP, u[j][cc].z);
                };
#pragma unroll
                for (int j = 0; j < 2; j++)
#pragma unroll
                    for (int cc = 0; cc < 3; cc++) {
                        u[j][cc].x = cvt(u[j][cc].x); u[j][cc].y = cvt(u[j][cc].y); u[j][cc].z = cvt(u[j][cc].z);
                        put(j, cc);
                    }
                {
                    const uint32_t bad = ((u[0][0].w ^ 0x5000u) | (u[0][1].w ^ 0x5000u) | (u[0][2].w ^ 0x5000u)) |
                                         ((u[1][0].w ^ 0x5000u) | (u[1][1].w ^ 0x5000u) | (u[1][2].w ^ 0x5000u));
                    const uint32_t tg = max(max(max(u[0][0].w, u[0][1].w), u[0][2].w), max(max(u[1][0].w, u[1][1].w), u[1][2].w));
                    const bool clean = __all_sync(0xffffffffu, (bad & 0xffffu) == 0 && tg < 0x54000000u);
                    const bool big = __any_sync(0xffffffffu, tg >= 0x3c000000u);
                    if (__builtin_expect(!(clean && big), 0)) {
                        while (true) {
                            bool ok = true;
#pragma unroll
                            for (int j = 0; j < 2; j++)
#pragma unroll
                                for (int cc = 0; cc < 3; cc++) ok = ok && (u[j][cc].w & 0xffffu) == 0x5000u;
                            if (__all_sync(0xffffffffu, ok)) break;
                            if (++it > (1 << 20)) __trap();
                            uint32_t redo = 0;
#pragma unroll
                            for (int j = 0; j < 2; j++)
#pragma unroll
                                for (int cc = 0; cc < 3; cc++) {
                                    if ((u[j][cc].w & 0xffffu) != 0x5000u) redo |= 1u << (j * 3 + cc);
                                    reld_relaxed4u(u[j][cc], gl + (cc * 32 + j * 16) * 72);
                                }
#pragma unroll
                            for (int j = 0; j < 2; j++)
#pragma unroll
                                for (int cc = 0; cc < 3; cc++) {
                                    const bool rd = (redo >> (j * 3 + cc)) & 1;
                                    u[j][cc].x = rd ? cvt(u[j][cc].x) : u[j][cc].x; u[j][cc].y = rd ? cvt(u[j][cc].y) : u[j][cc].y;
                                    u[j][cc].z = rd ? cvt(u[j][cc].z) : u[j][cc].z;
                                    put(j, cc);
                                }
                        }
                        const uint32_t t2 = max(max(max(u[0][0].w, u[0][1].w), u[0][2].w), max(max(u[1][0].w, u[1][1].w), u[1][2].w));
                        if (__any_sync(0xffffffffu, t2 >= 0x54000000u) || !__any_sync(0xffffffffu, t2 >= 0x3c000000u)) {
                            const float isc = __int_as_float((127 - ex) << 23);
                            float* fl = red_line(s, c * 64 + wq * 4 + (L16 >> 7)) + ((L16 >> 2) & 28);
#pragma unroll
                            for (int i = 0; i < 4; i++) red4(fl + i * 16 * 256, v[3 * i], v[3 * i + 1], v[3 * i + 2], 1.0f);
                            const float* fg = fl - c * 64 * 256;
#pragma unroll
                            for (int j = 0; j < 2; j++)
#pragma unroll
                                for (int cc = 0; cc < 3; cc++) {
                                    float4 a, b;
                                    while (true) {
                                        a = ld_relaxed4(fg + (cc * 64 + j * 32) * 256); b = ld_relaxed4(fg + (cc * 64 + j * 32 + 16) * 256);
                                        if (__all_sync(0xffffffffu, a.w == 32.f && b.w == 32.f)) break;
                                        if (++it > (1 << 20)) __trap();
                                    }
                                    u[j][cc].x = pack2(a.x * isc, a.y * isc); u[j][cc].y = pack2(a.z * isc, b.x * isc); u[j][cc].z = pack2(b.y * isc, b.z * isc);
                                    put(j, cc);
                                }
                        }
                    }
                }
                bar_arrive(1, 384);
                PROF(11);
                uint32_t am = max(max(u[0][0].x << 1, u[0][1].y << 1), max(u[1][1].x << 1, u[1][2].y << 1));
                am = __reduce_max_sync(0xffffffffu, am >> 24);
                if (am) ex = min(max(4 - ((int)am - 127), -60), 60);
                s3 = s3 == 2 ? 0 : s3 + 1;
            }
        }
        if (wt == 96) publish(NSEG - 1, 0);
        __syncwarp();
        if (wq < 3) bar_sync(8, nq * 64 + 96);
        bar_arrive(5, 384);
        if (wt == 96) publish(NSEG, 1);
        __syncwarp();
        if (wq == 3) bar_sync(7, 288);
    }
    cluster_sync();
}

constexpr int H_STAGES = 4, H_STAGE = 57344;
constexpr int HELP_SMEM = H_STAGES * H_STAGE + 1024 + 256;
constexpr int NBLK = 11;
enum { T_EXIT = 0, T_GATE, T_G0, T_F, T_AB, T_AA, T_FS };
enum { C_HG = 0, C_HB = 32, C_GATE = 33, C_G0 = 48, C_AB = 64, C_HF = 96, C_AA = 128, C_HAA = 160, C_F = 256 };
constexpr int NG0 = NBLK * 9;
constexpr int NB_UNITS = NG0 + 16 * 11;
__host__ __device__ constexpr int aa_units(int seg) { return seg < 36 ? 3 : 6; }
#define AA_CTAS 4
#define AA_CTAS2 8
#define AA_CTAS3 18
#define AA_B3 9
#define AA_LATE 61
constexpr int NFB = 13;
__host__ __device__ constexpr int f_row0(int m) { return m < 10 ? m * 192 : 1856 + (m - 10) * 64; }
__host__ __device__ constexpr int f_rows(int m) { return m < 9 ? 192 : (m < 10 ? 128 : 64); }
__host__ __device__ constexpr int f_blk(int seg) { return seg < 54 ? seg / 6 : (seg < 58 ? 9 : 10 + (seg - 58) / 2); }
__host__ __device__ constexpr int f_ntiles(int m) { return m < 10 ? 3 : 9; }

__device__ __forceinline__ void wait_ge(const unsigned* q, unsigned target) {
    int it = 0;
    while (ld_acq(q) < target) { __nanosleep(100); if (++it > (1 << 22)) __trap(); }
}
__device__ __forceinline__ void signal(unsigned* q, int lane, unsigned n = 1) {
    __syncwarp();
    if (lane == 0) asm volatile("red.release.gpu.global.add.u32 [%0],%1;" ::"l"(q), "r"(n) : "memory");
}

__device__ __forceinline__ int pos_q(int d) { return (d / 3) * 8 + d % 3; }
__device__ __forceinline__ int pos_k(int d) { return (d / 3) * 8 + d % 3 + (d < 6 ? 3 : 2); }
__device__ __forceinline__ int mpos_k(int d) { return (d / 3) * 5 + d % 3; }
__device__ __forceinline__ int mpos_v(int d) { return d < 2 ? 3 + d : (d < 4 ? 6 + d : 8 + d); }
__device__ __forceinline__ int pos_v(int d) { return d < 2 ? 6 + d : (d < 4 ? 12 + d : 16 + d); }

__device__ __forceinline__ uint4 quad_tr(const uint32_t* v, int t) {
    uint32_t a0 = (t & 1) ? v[0] : v[1], a1 = (t & 1) ? v[2] : v[3];
    a0 = __shfl_xor_sync(0xffffffffu, a0, 1); a1 = __shfl_xor_sync(0xffffffffu, a1, 1);
    const uint32_t b0 = (t & 1) ? a0 : v[0], b1 = (t & 1) ? v[1] : a0, b2 = (t & 1) ? a1 : v[2], b3 = (t & 1) ? v[3] : a1;
    uint32_t c0 = (t & 2) ? b0 : b2, c1 = (t & 2) ? b1 : b3;
    c0 = __shfl_xor_sync(0xffffffffu, c0, 2); c1 = __shfl_xor_sync(0xffffffffu, c1, 2);
    uint4 o;
    o.x = (t & 2) ? c0 : b0; o.y = (t & 2) ? c1 : b1; o.z = (t & 2) ? b2 : c0; o.w = (t & 2) ? b3 : c1;
    return o;
}
template <int BN>
__device__ __forceinline__ void store_tile(const float* acc, bf16* q, int pitch, int t) {
#pragma unroll
    for (int j = 0; j < BN / 32; j++) {
        uint32_t lo[4], hi[4];
#pragma unroll
        for (int i = 0; i < 4; i++) {
            lo[i] = pack2(acc[16 * j + 4 * i], acc[16 * j + 4 * i + 1]); hi[i] = pack2(acc[16 * j + 4 * i + 2], acc[16 * j + 4 * i + 3]);
        }
        *reinterpret_cast<uint4*>(q + j * 32 + t * 8) = quad_tr(lo, t);
        *reinterpret_cast<uint4*>(q + (size_t)8 * pitch + j * 32 + t * 8) = quad_tr(hi, t);
    }
}

template <int MT>
__device__ __forceinline__ void attnA_unit(uint32_t xr, uint32_t mr, int s, int h, int lane) {
    const int g = lane >> 2, t = lane & 3, l7 = lane & 7, l3 = lane >> 3;
    const float SC = 0.08838834764831845f * 1.4426950408889634f;
    constexpr int NT = MT ? 5 : 3;
    const uint32_t offA = (l7 + (l3 & 1) * 8) * 32 + (((l3 >> 1) ^ (l7 >> 2)) << 4);
    const uint32_t offB = (l7 + (l3 >> 1) * 8) * 32 + (((l3 & 1) ^ (l7 >> 2)) << 4);
    float sa[NT][4];
#pragma unroll
    for (int n = 0; n < NT; n++)
#pragma unroll
        for (int i = 0; i < 4; i++) sa[n][i] = 0.f;
#pragma unroll
    for (int hf = 0; hf < 2; hf++) {
        uint32_t qf[4][4], k0[4][4], k1[4][4], km[4][2];
#pragma unroll
        for (int i = 0; i < 4; i++) {
            const int d = hf * 4 + i;
            ldsm4(qf[i], xr + pos_q(d) * 1024 + MT * 512 + offA);
            ldsm2(km[i], mr + mpos_k(d) * 256 + (offB & 255));
            ldsm4(k0[i], xr + pos_k(d) * 1024 + offB);
            if (MT) ldsm4(k1[i], xr + pos_k(d) * 1024 + 512 + offB);
        }
#pragma unroll
        for (int i = 0; i < 4; i++) {
            mma16(sa[0], qf[i], km[i][0], km[i][1]);
            mma16(sa[1], qf[i], k0[i][0], k0[i][1]); mma16(sa[2], qf[i], k0[i][2], k0[i][3]);
            if (MT) { mma16(sa[NT - 2], qf[i], k1[i][0], k1[i][1]); mma16(sa[NT - 1], qf[i], k1[i][2], k1[i][3]); }
        }
    }
    if (2 * t > g) sa[NT - 2][0] = -INFINITY;
    if (2 * t + 1 > g) sa[NT - 2][1] = -INFINITY;
    sa[NT - 1][0] = -INFINITY; sa[NT - 1][1] = -INFINITY;
    if (2 * t > g) sa[NT - 1][2] = -INFINITY;
    if (2 * t + 1 > g) sa[NT - 1][3] = -INFINITY;
    float m0 = fmaxf(sa[0][0], sa[0][1]), m1 = fmaxf(sa[0][2], sa[0][3]);
#pragma unroll
    for (int n = 1; n < NT; n++) { m0 = fmaxf(m0, fmaxf(sa[n][0], sa[n][1])); m1 = fmaxf(m1, fmaxf(sa[n][2], sa[n][3])); }
    m0 = fmaxf(m0, __shfl_xor_sync(0xffffffffu, m0, 1)); m1 = fmaxf(m1, __shfl_xor_sync(0xffffffffu, m1, 1));
    m0 = fmaxf(m0, __shfl_xor_sync(0xffffffffu, m0, 2)); m1 = fmaxf(m1, __shfl_xor_sync(0xffffffffu, m1, 2));
    m0 *= SC; m1 *= SC;
    float s0 = 0.f, s1 = 0.f;
#pragma unroll
    for (int n = 0; n < NT; n++) {
        sa[n][0] = ex2(fmaf(sa[n][0], SC, -m0)); sa[n][1] = ex2(fmaf(sa[n][1], SC, -m0));
        sa[n][2] = ex2(fmaf(sa[n][2], SC, -m1)); sa[n][3] = ex2(fmaf(sa[n][3], SC, -m1));
        s0 += sa[n][0] + sa[n][1]; s1 += sa[n][2] + sa[n][3];
    }
    s0 += __shfl_xor_sync(0xffffffffu, s0, 1); s1 += __shfl_xor_sync(0xffffffffu, s1, 1);
    s0 += __shfl_xor_sync(0xffffffffu, s0, 2); s1 += __shfl_xor_sync(0xffffffffu, s1, 2);
    s0 = rcp_fast(s0); s1 = rcp_fast(s1);
    uint32_t pa[NT][2];
#pragma unroll
    for (int n = 0; n < NT; n++) { pa[n][0] = pack2(sa[n][0] * s0, sa[n][1] * s0); pa[n][1] = pack2(sa[n][2] * s1, sa[n][3] * s1); }
    const uint32_t p0[4] = {pa[1][0], pa[1][1], pa[2][0], pa[2][1]}, p1[4] = {pa[NT - 2][0], pa[NT - 2][1], pa[NT - 1][0], pa[NT - 1][1]};
    bf16* op = g_O + (size_t)(s * 32 + MT * 16 + g) * OK + h * DH + t * 8;
#pragma unroll
    for (int dh = 0; dh < 2; dh++) {
        uint32_t f0[4][4], f1[4][4], f2[4][2];
#pragma unroll
        for (int n2 = 0; n2 < 4; n2++) {
            const int d = dh * 4 + n2;
            ldsm4t(f0[n2], xr + pos_v(d) * 1024 + offA);
            if (MT) ldsm4t(f1[n2], xr + pos_v(d) * 1024 + 512 + offA);
            ldsm2t(f2[n2], mr + mpos_v(d) * 256 + (offB & 255));
        }
        uint32_t lo[8], hi[8];
#pragma unroll
        for (int n2 = 0; n2 < 4; n2++) {
            float oa0[4] = {0.f, 0.f, 0.f, 0.f}, oa1[4] = {0.f, 0.f, 0.f, 0.f};
            mma16(oa0, p0, f0[n2][0], f0[n2][1]); mma16(oa1, p0, f0[n2][2], f0[n2][3]);
            if (MT) { mma16(oa0, p1, f1[n2][0], f1[n2][1]); mma16(oa1, p1, f1[n2][2], f1[n2][3]); }
            mma8(oa0, pa[0][0], pa[0][1], f2[n2][0]); mma8(oa1, pa[0][0], pa[0][1], f2[n2][1]);
            lo[2 * n2] = pack2(oa0[0], oa0[1]); hi[2 * n2] = pack2(oa0[2], oa0[3]);
            lo[2 * n2 + 1] = pack2(oa1[0], oa1[1]); hi[2 * n2 + 1] = pack2(oa1[2], oa1[3]);
        }
#pragma unroll
        for (int q = 0; q < 2; q++) {
            *reinterpret_cast<uint4*>(op + dh * 64 + q * 32) = quad_tr(lo + 4 * q, t);
            *reinterpret_cast<uint4*>(op + (size_t)8 * OK + dh * 64 + q * 32) = quad_tr(hi + 4 * q, t);
        }
    }
}

__device__ __forceinline__ void attnB_unit(uint32_t sQ, int q0, int hh, int wq, int lane) {
    const int g = lane >> 2, t = lane & 3, l7 = lane & 7, l3 = lane >> 3;
    const uint32_t sK = sQ + 128 * 48, sV = sK + 384 * 48;
    const int sh = (hh & 3) * 2;
    uint32_t qa[2][4], qb[2][2];
#pragma unroll
    for (int m = 0; m < 2; m++) {
        ldsm4(qa[m], sQ + (wq * 32 + m * 16 + l7 + (l3 & 1) * 8) * 48 + (l3 >> 1) * 16);
        ldsm2(qb[m], sQ + (wq * 32 + m * 16 + l7 + (l3 & 1) * 8) * 48 + 32);
        if (2 * t < sh) { qa[m][0] = 0u; qa[m][1] = 0u; }
        if (16 + 2 * t >= sh + 18) { qb[m][0] = 0u; qb[m][1] = 0u; }
    }
    const bool one0 = (sh == 6 && g == 0), one2 = (sh != 6 && g == 7);
    float gt[2][2];
#pragma unroll
    for (int m = 0; m < 2; m++) { gt[m][0] = __ldcg(g_gate + q0 + wq * 32 + m * 16 + g); gt[m][1] = __ldcg(g_gate + q0 + wq * 32 + m * 16 + g + 8); }
    const float SC = 0.23570226039551584f * 1.4426950408889634f;
    float o[2][3][4];
    float mx[2][2];
#pragma unroll
    for (int m = 0; m < 2; m++) {
        mx[m][0] = -INFINITY; mx[m][1] = -INFINITY;
#pragma unroll
        for (int n = 0; n < 3; n++)
#pragma unroll
            for (int i = 0; i < 4; i++) o[m][n][i] = 0.f;
    }
    const int tfirst = max(0, (256 - q0) / 16 - 2 * wq);
    const uint32_t kb0 = sK + (wq * 32 + l7 + (l3 >> 1) * 8) * 48 + (l3 & 1) * 16;
    const uint32_t kb1 = sK + (wq * 32 + l7 + (l3 & 1) * 8) * 48 + 32;
    const uint32_t vb0 = sV + (wq * 32 + l7 + (l3 & 1) * 8) * 48 + (l3 >> 1) * 16;
    const uint32_t vb1 = sV + (wq * 32 + l7 + (l3 & 1) * 8) * 48 + 32;
    constexpr int CH = 3;
#pragma unroll 1
    for (int c0 = 18 - CH; c0 >= 0; c0 -= CH) {
        if (c0 + CH <= tfirst) break;
        float sc[2][CH][2][4];
#pragma unroll
        for (int u = 0; u < CH; u++) {
            uint32_t kf[4], kg[2];
            const int ti = max(c0 + u, tfirst);
            ldsm4(kf, kb0 + ti * 768); ldsm2(kg, kb1 + ti * 768);
#pragma unroll
            for (int m = 0; m < 2; m++) {
#pragma unroll
                for (int n = 0; n < 2; n++) {
#pragma unroll
                    for (int i = 0; i < 4; i++) sc[m][u][n][i] = 0.f;
                    mma16(sc[m][u][n], qa[m], kf[2 * n], kf[2 * n + 1]);
                    mma8(sc[m][u][n], qb[m][0], qb[m][1], kg[n]);
                }
            }
        }
        if (c0 == 18 - CH || c0 == 0 || c0 < tfirst) {
#pragma unroll
            for (int m = 0; m < 2; m++)
#pragma unroll
                for (int u = 0; u < CH; u++)
#pragma unroll
                    for (int n = 0; n < 2; n++)
#pragma unroll
                        for (int i = 0; i < 4; i++) {
                            const int d = 256 + m * 16 + g + (i >> 1) * 8 - ((c0 + u) * 16 + n * 8 + 2 * t + (i & 1));
                            if (d < 0 || d >= 256 || c0 + u < tfirst) sc[m][u][n][i] = -INFINITY;
                        }
        }
        float bs[2][2];
#pragma unroll
        for (int m = 0; m < 2; m++) {
            float n0 = mx[m][0], n1 = mx[m][1];
#pragma unroll
            for (int u = 0; u < CH; u++)
#pragma unroll
                for (int n = 0; n < 2; n++) {
                    n0 = fmaxf(n0, fmaxf(sc[m][u][n][0], sc[m][u][n][1])); n1 = fmaxf(n1, fmaxf(sc[m][u][n][2], sc[m][u][n][3]));
                }
            n0 = fmaxf(n0, __shfl_xor_sync(0xffffffffu, n0, 1)); n1 = fmaxf(n1, __shfl_xor_sync(0xffffffffu, n1, 1));
            n0 = fmaxf(n0, __shfl_xor_sync(0xffffffffu, n0, 2)); n1 = fmaxf(n1, __shfl_xor_sync(0xffffffffu, n1, 2));
            const float f0 = ex2((mx[m][0] - n0) * SC), f1 = ex2((mx[m][1] - n1) * SC);
            mx[m][0] = n0; mx[m][1] = n1;
            bs[m][0] = n0 * SC; bs[m][1] = n1 * SC;
#pragma unroll
            for (int n = 0; n < 3; n++) { o[m][n][0] *= f0; o[m][n][1] *= f0; o[m][n][2] *= f1; o[m][n][3] *= f1; }
        }
#pragma unroll
        for (int u = 0; u < CH; u++) {
            uint32_t vf[4], vg[2];
            const int ti = max(c0 + u, tfirst);
            ldsm4t(vf, vb0 + ti * 768); ldsm2t(vg, vb1 + ti * 768);
            if (one0) { vf[0] = 0x3f803f80u; vf[1] = 0x3f803f80u; }
            if (one2) { vg[0] = 0x3f803f80u; vg[1] = 0x3f803f80u; }
#pragma unroll
            for (int m = 0; m < 2; m++) {
                uint32_t pa[4];
#pragma unroll
                for (int n = 0; n < 2; n++) {
                    pa[2 * n] = pack2(ex2(fmaf(sc[m][u][n][0], SC, -bs[m][0])), ex2(fmaf(sc[m][u][n][1], SC, -bs[m][0])));
                    pa[2 * n + 1] = pack2(ex2(fmaf(sc[m][u][n][2], SC, -bs[m][1])), ex2(fmaf(sc[m][u][n][3], SC, -bs[m][1])));
                }
                mma16(o[m][0], pa, vf[0], vf[1]); mma16(o[m][1], pa, vf[2], vf[3]); mma16(o[m][2], pa, vg[0], vg[1]);
            }
        }
    }
#pragma unroll
    for (int m = 0; m < 2; m++) {
        const int src = sh == 6 ? (lane & ~3) : (lane | 3);
        const float s0 = __shfl_sync(0xffffffffu, sh == 6 ? o[m][0][0] : o[m][2][1], src);
        const float s1 = __shfl_sync(0xffffffffu, sh == 6 ? o[m][0][2] : o[m][2][3], src);
        const int r = q0 + wq * 32 + m * 16 + g;
        const float i0 = (1.f - gt[m][0]) * rcp_fast(s0), i1 = (1.f - gt[m][1]) * rcp_fast(s1);
        bf16* op = g_O + (size_t)r * OK + HD + hh * BD + 2 * t - sh;
#pragma unroll
        for (int n = 0; n < 3; n++) {
            const int col = n * 8 + 2 * t;
            if (col >= sh && col < sh + 18) {
                *reinterpret_cast<uint32_t*>(op + n * 8) = pack2(o[m][n][0] * i0, o[m][n][1] * i0);
                *reinterpret_cast<uint32_t*>(op + n * 8 + 8 * OK) = pack2(o[m][n][2] * i1, o[m][n][3] * i1);
            }
        }
    }
}

#define LOG_BEGIN()
#define LOG_END()
template <int BN>
__device__ __forceinline__ void gemm_unit(int ty, const uint32_t* d, uint32_t sb, uint32_t bF, uint32_t bE, int& sg, int& ph,
                                          int warp, int lane, bf16* __restrict__ out) {
    const int wg = warp >> 2, wq = warp & 3, g = lane >> 2, t = lane & 3;
    auto release = [&](int q) { __syncwarp(); if (lane == 0) mbar_arrive(bE + 8 * q); };
    const int n0 = d[2] * BN, kb0 = d[3] & 255, kb1 = d[3] >> 8;
    const int rb = (ty == T_G0 ? d[1] * 192 : f_row0(d[1])) + (BN == 64 ? wq : warp) * 16, r0 = rb + g;
    float g0 = 1.f, g1 = 1.f;
    if (ty != T_G0) { g0 = __ldcg(g_gate + r0); g1 = __ldcg(g_gate + r0 + 8); }
    if (ty != T_G0 && f_split(d[1]) > 1) {
        const float* pa = g_acc + (size_t)rb * DM + n0 * 16 + lane * 32;
#pragma unroll
        for (int i = 0; i < BN / 64; i++) asm volatile("prefetch.global.L2 [%0];" ::"l"(pa + i * 1024));
    }
    float acc[BN / 2];
#pragma unroll
    for (int i = 0; i < BN / 2; i++) acc[i] = 0.f;
    int prev = -1;
    constexpr int KPS = BN == 64 ? 3 : 1;
    for (int kb = kb0; kb < kb1;) {
        if (kb > kb0) mbar_wait(bF + 8 * sg, ph);
        for (int j = 0; j < KPS && kb < kb1; j++, kb++) {
            const uint32_t a = sb + sg * H_STAGE + (BN == 64 ? j * 16384 : wg * 8192), b = BN == 64 ? a + 8192 : sb + sg * H_STAGE + 24576;
            if (kb == 64 && kb0 < 64) {
                wg_wait<0>();
#pragma unroll
                for (int i = 0; i < BN / 8; i++) { acc[4 * i] *= g0; acc[4 * i + 1] *= g0; acc[4 * i + 2] *= g1; acc[4 * i + 3] *= g1; }
            }
            const uint64_t da = desc_sw128(a, 16, 1024), db = desc_sw128(b, 8192, 1024);
            wg_fence();
#pragma unroll
            for (int k = 0; k < 4; k++) {
                if (BN == 192) wgmma_ss_n192(acc, da + (uint64_t)(k * 2), db + (uint64_t)(k * 128), 1);
                else wgmma_ss_n64(acc, da + (uint64_t)(k * 2), db + (uint64_t)(k * 128));
            }
            wg_commit();
            wg_wait<1>();
            if (j == 0 && prev >= 0) release(prev);
        }
        prev = sg;
        if (++sg == H_STAGES) { sg = 0; ph ^= 1; }
    }
    wg_wait<0>();
    if (ty == T_G0) {
        release(prev);
        store_tile<BN>(acc, g_qkvB + (size_t)r0 * (3 * DM) + n0, 3 * DM, t);
        signal(g_ctr + C_G0 + d[1], lane);
        return;
    }
    if (kb1 <= 64) {
#pragma unroll
        for (int i = 0; i < BN / 8; i++) { acc[4 * i] *= g0; acc[4 * i + 1] *= g0; acc[4 * i + 2] *= g1; acc[4 * i + 3] *= g1; }
    }
    const int ks = f_split(d[1]);
    bool fin = true;
    if (ks == 1) release(prev);
    if (ks > 1) {
        float4* ga = reinterpret_cast<float4*>(g_acc + (size_t)rb * DM + n0 * 16) + lane;
#pragma unroll
        for (int i = 0; i < BN / 8; i++) red4(reinterpret_cast<float*>(ga + i * 32), acc[4 * i], acc[4 * i + 1], acc[4 * i + 2], acc[4 * i + 3]);
        release(prev);
        unsigned old = 0;
        if (lane == 0) asm volatile("atom.acq_rel.gpu.global.add.u32 %0,[%1],1;" : "=r"(old) : "l"(g_ctr + C_F + (d[1] * 9 + d[2]) * 12 + warp) : "memory");
        old = __shfl_sync(0xffffffffu, old, 0);
        fin = (old == (unsigned)ks - 1);
        if (fin) {
#pragma unroll
            for (int i = 0; i < BN / 8; i++) {
                const float4 u = __ldcg(ga + i * 32);
                acc[4 * i] = u.x; acc[4 * i + 1] = u.y; acc[4 * i + 2] = u.z; acc[4 * i + 3] = u.w;
            }
        }
    }
    if (fin) store_tile<BN>(acc, out + (size_t)r0 * DM + n0, DM, t);
}

struct HelpMaps { CUtensorMap x, wqkv, O, O64, Wo, wo, qkv; };

__global__ void __launch_bounds__(512, 1) k_help(const __grid_constant__ HelpMaps tm, const bf16* __restrict__ x,
                                                  const bf16* __restrict__ gw, bf16* __restrict__ out) {
    extern __shared__ uint8_t smem_raw[];
    const uint32_t sb = (s2u(smem_raw) + 1023) & ~1023u;
    const uint32_t bF = sb + H_STAGES * H_STAGE, bE = bF + 8 * H_STAGES, dsc = bF + 128;
    const int tid = threadIdx.x, warp = __shfl_sync(0xffffffffu, tid >> 5, 0), lane = tid & 31;
    if (tid == 0) {
        for (int i = 0; i < H_STAGES; i++) { mbar_init(bF + 8 * i, 1); mbar_init(bE + 8 * i, 12); }
        asm volatile("fence.mbarrier_init.release.cluster;" ::: "memory");
    }
    __syncthreads();
    if (warp >= 12) {
        asm volatile("setmaxnreg.dec.sync.aligned.u32 56;");
        if (warp != 12) {
            while (true) {
                unsigned u = 0;
                if (lane == 0) u = atomicAdd(g_ctr + C_HG, 1);
                u = __shfl_sync(0xffffffffu, u, 0);
                if (u >= SEQ / 16) return;
#pragma unroll 1
                for (int r0 = u * 16; r0 < u * 16 + 16; r0 += 2) {
                    float a0 = 0.f, a1 = 0.f;
                    const __nv_bfloat162* xr = reinterpret_cast<const __nv_bfloat162*>(x + (size_t)r0 * DM);
#pragma unroll
                    for (int i = 0; i < 9; i++) {
                        const float2 b = __bfloat1622float2(reinterpret_cast<const __nv_bfloat162*>(gw)[lane + 32 * i]);
                        const float2 y = __bfloat1622float2(xr[lane + 32 * i]), z = __bfloat1622float2(xr[DM / 2 + lane + 32 * i]);
                        a0 += y.x * b.x + y.y * b.y; a1 += z.x * b.x + z.y * b.y;
                    }
#pragma unroll
                    for (int o = 16; o; o >>= 1) { a0 += __shfl_xor_sync(0xffffffffu, a0, o); a1 += __shfl_xor_sync(0xffffffffu, a1, o); }
                    if (lane < 2) g_gate[r0 + lane] = 1.f / (1.f + __expf(-(lane ? a1 : a0)));
                }
                signal(g_ctr + C_GATE, lane);
            }
        }
        int sg = 0, ph = 1;
        auto next = [&](int ty, int a, int b, int c2) {
            mbar_wait(bE + 8 * sg, ph);
            if (lane == 0) asm volatile("st.shared.v4.u32 [%0],{%1,%2,%3,%4};" ::"r"(dsc + 16 * sg), "r"(ty), "r"(a), "r"(b), "r"(c2) : "memory");
        };
        auto adv = [&]() { __syncwarp(); if (++sg == H_STAGES) { sg = 0; ph ^= 1; } };
        auto acquire = [&]() { asm volatile("fence.acq_rel.gpu; fence.proxy.async.global;" ::: "memory"); };
        auto ticket = [&](unsigned* q) { unsigned u = 0; if (lane == 0) u = atomicAdd(q, 1); return __shfl_sync(0xffffffffu, u, 0); };
        auto gemm = [&](int ty, int m, int n, int kb0, int kb1) {
            for (int kb = kb0; kb < kb1; kb++) {
                next(ty, m, n, kb0 | (kb1 << 8));
                if (lane == 0) {
                    const uint32_t a = sb + sg * H_STAGE, b = a + 24576, bar = bF + 8 * sg;
                    mbar_expect(bar, 49152);
                    tma2d(a, ty == T_G0 ? &tm.x : &tm.O, kb * 64, m * 192, bar);
                    const CUtensorMap* mb = ty == T_G0 ? &tm.wqkv : (kb >= 64 ? &tm.wo : &tm.Wo);
                    const int kr = (kb >= 64 ? kb - 64 : kb) * 64;
                    for (int j = 0; j < 3; j++) tma2d(b + j * 8192, mb, n * 192 + j * 64, kr, bar);
                }
                adv();
            }
        };
        bool bdone = false;
        int idle = 0, rr = 0;
        const int fl = min(lane, 9);
        constexpr int NLATE = (NSEG - AA_LATE) * 6, N10 = 9 * f_split(10), N11 = N10 + 9 * f_split(11), NSMALL = N11 + 9 * f_split(12);
        auto attn_a = [&](int as, int u) {
            const int per = (15 + aa_units(as)) / aa_units(as), ns = min(per, 16 - u * per), h0 = u * per * 2;
            for (int i = 0; i < ns; i++) {
                next(T_AA, as, h0 + 2 * i, rr | (i + 3 >= ns ? 4 : 0)); rr = rr == 2 ? 0 : rr + 1;
                if (lane == 0) {
                    const uint32_t a = sb + sg * H_STAGE, bar = bF + 8 * sg;
                    mbar_expect(bar, 57344);
                    bulk_load(a, reinterpret_cast<uint8_t*>(g_xr) + (size_t)(as * 32 + h0 + 2 * i) * 24576, 49152, bar);
                    bulk_load(a + 49152, reinterpret_cast<uint8_t*>(g_mr) + (size_t)(as * 32 + h0 + 2 * i) * 4096, 8192, bar);
                }
                adv();
            }
        };
        auto spin_ge = [&](const unsigned* q, unsigned target) {
            int it = 0;
            while (ld_relaxed1(q) < target) { __nanosleep(20); if (++it > (1 << 22)) __trap(); }
            acquire();
        };
        auto drain = [&]() {
            const int ls = sg == 0 ? H_STAGES - 1 : sg - 1;
            mbar_wait(bE + 8 * ls, sg == 0 ? ph : ph ^ 1);
        };
        while (true) {
            const unsigned tk0 = ld_relaxed1(g_ctr + C_HAA + lane), tk1 = ld_relaxed1(g_ctr + C_HAA + 32 + lane);
            const unsigned f0 = ld_relaxed1(g_flagA + lane), f1 = ld_relaxed1(g_flagA + 32 + lane);
            const unsigned tkf = ld_relaxed1(g_ctr + C_HF + min(lane, 11)), ca = ld_relaxed1(g_ctr + C_AA + fl);
            const unsigned cb0 = ld_relaxed1(g_ctr + C_AB + (lane > 9 ? 14 : f_row0(fl) / 128));
            const unsigned cb1 = ld_relaxed1(g_ctr + C_AB + (lane > 9 ? 15 : (f_row0(fl) + f_rows(fl) - 1) / 128));
            const bool e0 = tk0 < (unsigned)aa_units(lane), e1 = 32 + lane < AA_LATE && tk1 < (unsigned)aa_units(32 + lane);
            const unsigned a0 = __ballot_sync(0xffffffffu, e0 && f0 >= 192), a1 = __ballot_sync(0xffffffffu, e1 && f1 >= 192);
            const bool early_left = __any_sync(0xffffffffu, e0 || e1);
            const unsigned tl = __shfl_sync(0xffffffffu, tkf, 10), ts = __shfl_sync(0xffffffffu, tkf, 11);
            const bool fleft = lane < 10 && tkf < (unsigned)(3 * f_split(fl));
            const unsigned fl_m = __ballot_sync(0xffffffffu, fleft);
            const bool may = blockIdx.x >= (fl >= AA_B3 ? AA_CTAS3 : (fl >= 6 ? AA_CTAS2 : AA_CTAS)) || tl >= NLATE;
            const unsigned fr = __ballot_sync(0xffffffffu, fleft && ca >= (unsigned)(2 * f_rows(fl)) && cb0 >= 128 && cb1 >= 128 && may);
            if (a0 | a1) {
                const int as = a0 ? __ffs(a0) - 1 : 31 + __ffs(a1);
                const unsigned u = ticket(g_ctr + C_HAA + as);
                if (u < (unsigned)aa_units(as)) { acquire(); attn_a(as, u); continue; }
            }
            if (tl < NLATE && !early_left) {
                const bool ready = __shfl_sync(0xffffffffu, f1, (AA_LATE - 32 + tl / 6) & 31) >= 192;
                if (ready || (blockIdx.x < AA_CTAS3 && bdone)) {
                    drain();
                    const unsigned u = ticket(g_ctr + C_HF + 10);
                    if (u < NLATE) { spin_ge(g_flagA + AA_LATE + u / 6, 192); attn_a(AA_LATE + u / 6, u % 6); continue; }
                }
            }
            if (fr) {
                const int fm = __ffs(fr) - 1;
                const unsigned u = ticket(g_ctr + C_HF + fm);
                const int ks = f_split(fm);
                if (u < (unsigned)(3 * ks)) {
                    const int kp = u / 3;
                    acquire();
                    gemm(T_F, fm, u % 3, kp * 73 / ks, (kp + 1) * 73 / ks);
                    drain();
                    continue;
                }
            }
            if (ts < NSMALL && tl >= NLATE && fl_m == fr && __shfl_sync(0xffffffffu, cb0 >= 128 && cb1 >= 128, 10)) {
                const unsigned u = ticket(g_ctr + C_HF + 11);
                if (u < NSMALL) {
                    const int fm = u < N10 ? 10 : (u < N11 ? 11 : 12), v = u - (u < N10 ? 0 : (u < N11 ? N10 : N11));
                    const int nn = v % 9, kp = v / 9, kb0 = kp * 73 / f_split(fm), kb1 = (kp + 1) * 73 / f_split(fm);
                    for (int k0 = kb0; k0 < kb1; k0 += 3 * H_STAGES) {
                        const int sg0 = sg, k1 = min(kb1, k0 + 3 * H_STAGES);
                        for (int kb = k0; kb < k1; kb += 3) {
                            next(T_FS, fm, nn, kb0 | (kb1 << 8));
                            const int kk = kb + lane;
                            if (lane == 0) mbar_expect(bF + 8 * sg, min(3, k1 - kb) * 16384);
                            __syncwarp();
                            if (lane < 3 && kk < k1) {
                                tma2d(sb + sg * H_STAGE + lane * 16384 + 8192, kk >= 64 ? &tm.wo : &tm.Wo, nn * 64, (kk >= 64 ? kk - 64 : kk) * 64, bF + 8 * sg);
                                if (k0 > kb0) tma2d(sb + sg * H_STAGE + lane * 16384, &tm.O64, kk * 64, f_row0(fm), bF + 8 * sg);
                            }
                            adv();
                        }
                        if (k0 == kb0) {
                            spin_ge(g_ctr + C_AA + fm, 128);
                            if (k0 + lane < k1) {
                                const int q = (sg0 + lane / 3) % H_STAGES;
                                tma2d(sb + q * H_STAGE + (lane % 3) * 16384, &tm.O64, (k0 + lane) * 64, f_row0(fm), bF + 8 * q);
                            }
                            __syncwarp();
                        }
                    }
                    drain();
                    continue;
                }
            }
            if (a0 | a1 | fr) continue;
            if (!bdone) {
                const unsigned u = ticket(g_ctr + C_HB);
                if (u < NG0) {
                    gemm(T_G0, u / 9, u % 9, 0, 9);
                } else if (u < NB_UNITS) {
                    const int m = (u - NG0) / 11, h0 = ((u - NG0) % 11) * 3;
                    const int mm = min(max(0, m * 128 - 256) / 192 + lane, (m * 128 + 127) / 192);
                    const unsigned* q = lane == 31 ? g_ctr + C_GATE : g_ctr + C_G0 + mm;
                    int it = 0;
                    while (!__all_sync(0xffffffffu, ld_relaxed1(q) >= (lane == 31 ? 128u : 108u))) { __nanosleep(100); if (++it > (1 << 22)) __trap(); }
                    acquire();
                    for (int hh = h0; hh < min(h0 + 3, BH); hh++) {
                        next(T_AB, m, hh, rr); rr = rr == 2 ? 0 : rr + 1;
                        if (lane == 0) {
                            const uint32_t a = sb + sg * H_STAGE, bar = bF + 8 * sg;
                            const int col = (hh >> 2) * 72 + (hh & 3) * 16;
                            mbar_expect(bar, 7 * 6144);
                            tma2d(a, &tm.qkv, col, m * 128, bar);
                            for (int j = 0; j < 3; j++) {
                                tma2d(a + (1 + j) * 6144, &tm.qkv, DM + col, (m - 2 + j) * 128, bar);
                                tma2d(a + (4 + j) * 6144, &tm.qkv, 2 * DM + col, (m - 2 + j) * 128, bar);
                            }
                        }
                        adv();
                    }
                } else bdone = true;
                continue;
            }
            if (fl_m == 0 && ts >= NSMALL) break;
            __nanosleep(150);
            if (++idle > (1 << 22)) __trap();
        }
        next(T_EXIT, 0, 0, 0);
        if (lane == 0) mbar_arrive(bF + 8 * sg);
    } else {
        asm volatile("setmaxnreg.inc.sync.aligned.u32 152;");
        const int wg = warp >> 2, wq = warp & 3, g = lane >> 2, t = lane & 3;
        int sg = 0, ph = 0, skip = 0;
        unsigned pend = 0;
        auto release = [&](int q) { __syncwarp(); if (lane == 0) mbar_arrive(bE + 8 * q); };
        auto adv = [&]() { if (++sg == H_STAGES) { sg = 0; ph ^= 1; } };
        while (true) {
            mbar_wait(bF + 8 * sg, ph);
            uint32_t d[4];
            lds128(d, dsc + 16 * sg);
            const int ty = d[0];
            LOG_BEGIN();
            if (ty == T_EXIT) { LOG_END(); break; }
            if ((ty == T_G0 && wg == 2 && d[1] == NBLK - 1) || (ty == T_F && wg == 2 && d[1] == 9) || (ty == T_FS && wg != 0)) {
                release(sg); adv();
                if (ty == T_G0 && ++skip == 9) { skip = 0; signal(g_ctr + C_G0 + d[1], lane); }
            } else if (ty == T_G0 || ty == T_F) {
                gemm_unit<192>(ty, d, sb, bF, bE, sg, ph, warp, lane, out);
                LOG_END();
            } else if (ty == T_FS) {
                gemm_unit<64>(ty, d, sb, bF, bE, sg, ph, warp, lane, out);
                if (tid == 0 && d[1] == NFB - 1) g_sync[0] = 0;
                LOG_END();
            } else {
                if ((int)(d[3] & 3) == wg) {
                    if (ty == T_AA) {
                        const uint32_t xr = sb + sg * H_STAGE + (wq >> 1) * 24576, mr = sb + sg * H_STAGE + 49152 + (wq >> 1) * 4096;
                        if ((wq + wg) & 1) attnA_unit<1>(xr, mr, d[1], d[2] + (wq >> 1), lane);
                        else attnA_unit<0>(xr, mr, d[1], d[2] + (wq >> 1), lane);
                        release(sg);
                        pend++;
                        if (d[3] & 4) { signal(g_ctr + C_AA + f_blk(d[1]), lane, pend); pend = 0; }
                    } else {
                        attnB_unit(sb + sg * H_STAGE, d[1] * 128, d[2], wq, lane);
                        release(sg);
                        signal(g_ctr + C_AB + d[1], lane);
                    }
                    LOG_END();
                } else {
                    release(sg);
                }
                adv();
            }
        }
    }
}

typedef CUresult (*EncodeFn)(CUtensorMap*, CUtensorMapDataType, cuuint32_t, void*, const cuuint64_t*, const cuuint64_t*,
                             const cuuint32_t*, const cuuint32_t*, CUtensorMapInterleave, CUtensorMapSwizzle,
                             CUtensorMapL2promotion, CUtensorMapFloatOOBfill);

static void make_map(EncodeFn fn, CUtensorMap* m, const void* ptr, uint64_t cols, uint64_t rows, uint32_t bc, uint32_t br,
                     CUtensorMapSwizzle sw = CU_TENSOR_MAP_SWIZZLE_128B) {
    cuuint64_t dims[2] = {cols, rows};
    cuuint64_t strides[1] = {cols * 2};
    cuuint32_t box[2] = {bc, br};
    cuuint32_t es[2] = {1, 1};
    fn(m, CU_TENSOR_MAP_DATA_TYPE_BFLOAT16, 2, const_cast<void*>(ptr), dims, strides, box, es, CU_TENSOR_MAP_INTERLEAVE_NONE,
       sw, sw == CU_TENSOR_MAP_SWIZZLE_NONE ? CU_TENSOR_MAP_L2_PROMOTION_NONE : CU_TENSOR_MAP_L2_PROMOTION_L2_256B, CU_TENSOR_MAP_FLOAT_OOB_FILL_NONE);
}

#define REC_D0 830
#define REC_DD 0
int g_d0 = REC_D0, g_dd = REC_DD, g_dsend = 230 << 4;

extern "C" void kernel_launch(void* const* d_in, const int* in_sizes, int n_in, void* d_out, int out_size) {
    const bf16* x = (const bf16*)d_in[0];
    const bf16* mem0 = (const bf16*)d_in[1];
    const bf16* Wq = (const bf16*)d_in[2];
    const bf16* Wk = (const bf16*)d_in[3];
    const bf16* Wv = (const bf16*)d_in[4];
    const bf16* Wo = (const bf16*)d_in[5];
    const bf16* wqkv = (const bf16*)d_in[8];
    const bf16* wo = (const bf16*)d_in[9];
    const bf16* gw = (const bf16*)d_in[10];
    bf16* out = (bf16*)d_out;

    void* fp = nullptr;
    cudaDriverEntryPointQueryResult qr;
    cudaGetDriverEntryPoint("cuTensorMapEncodeTiled", &fp, cudaEnableDefault, &qr);
    EncodeFn enc = (EncodeFn)fp;
    void* pO = nullptr;
    cudaGetSymbolAddress(&pO, g_O);
    CUtensorMap tx32;
    HelpMaps hm;
    make_map(enc, &tx32, x, DM, SEQ, 64, 32);
    make_map(enc, &hm.x, x, DM, SEQ, 64, 192);
    make_map(enc, &hm.wqkv, wqkv, 3 * DM, DM, 64, 64);
    make_map(enc, &hm.O, pO, OK, SEQ, 64, 192);
    make_map(enc, &hm.O64, pO, OK, SEQ, 64, 64);
    make_map(enc, &hm.Wo, Wo, DM, HD, 64, 64);
    make_map(enc, &hm.wo, wo, DM, DM, 64, 64);
    void* pQ = nullptr;
    cudaGetSymbolAddress(&pQ, g_qkvB);
    make_map(enc, &hm.qkv, pQ, 3 * DM, SEQ, 24, 128, CU_TENSOR_MAP_SWIZZLE_NONE);
    cudaFuncSetAttribute(k_rec, cudaFuncAttributeMaxDynamicSharedMemorySize, REC_SMEM);
    cudaFuncSetAttribute(k_help, cudaFuncAttributeMaxDynamicSharedMemorySize, HELP_SMEM);

    cudaStream_t st = cudaStreamPerThread;
    {
        RecParams p{mem0, Wq, Wk, Wv, Wo, x, wqkv, g_d0, g_dsend >> 4};
        cudaLaunchConfig_t cfg = {};
        cfg.gridDim = dim3(96); cfg.blockDim = dim3(384); cfg.dynamicSmemBytes = REC_SMEM; cfg.stream = st;
        cudaLaunchAttribute at[1];
        at[0].id = cudaLaunchAttributeClusterDimension;
        at[0].val.clusterDim.x = 3; at[0].val.clusterDim.y = 1; at[0].val.clusterDim.z = 1;
        cfg.attrs = at; cfg.numAttrs = 1;
        cudaLaunchKernelEx(&cfg, k_rec, tx32, p);
    }
    {
        cudaLaunchConfig_t cfg = {};
        cfg.gridDim = dim3(g_dd ? g_dd : 132); cfg.blockDim = dim3(512); cfg.dynamicSmemBytes = HELP_SMEM; cfg.stream = st;
        cudaLaunchAttribute at[1];
        at[0].id = cudaLaunchAttributeProgrammaticStreamSerialization;
        at[0].val.programmaticStreamSerializationAllowed = 1;
        cfg.attrs = at; cfg.numAttrs = (g_dsend & 1) ? 0 : 1;
        cudaLaunchKernelEx(&cfg, k_help, hm, x, gw, out);
    }
}
```

```cpp
#include <cuda_runtime.h>
#include <cuda_bf16.h>
#include <cuda_fp16.h>
#include <cuda.h>
#include <stdint.h>

typedef __nv_bfloat16 bf16;

constexpr int SEQ = 2048, DM = 576, NH = 32, DH = 128, NSEG = 64;
constexpr int HD = NH * DH;
constexpr int OK = HD + DM;
constexpr int BH = 32, BD = 18;

__device__ bf16 g_O[SEQ * OK];
__device__ bf16 g_qkvB[SEQ * 3 * DM];
__device__ float g_acc[SEQ * DM];
__device__ float g_gate[SEQ];
__device__ float g_red[8 * 192 * 256];
__device__ uint4 g_redh[8 * 96 * 72];
__device__ unsigned g_sync[32];
__device__ unsigned g_ctr[1920];

__device__ __forceinline__ uint32_t s2u(const void* p) { return (uint32_t)__cvta_generic_to_shared(p); }
__device__ __forceinline__ uint32_t mapa(uint32_t a, uint32_t r) {
    uint32_t o; asm volatile("mapa.shared::cluster.u32 %0,%1,%2;" : "=r"(o) : "r"(a), "r"(r)); return o;
}
__device__ __forceinline__ void mbar_init(uint32_t a, int c) {
    asm volatile("mbarrier.init.shared::cta.b64 [%0],%1;" ::"r"(a), "r"(c) : "memory");
}
__device__ __forceinline__ void mbar_expect(uint32_t a, int bytes) {
    asm volatile("mbarrier.arrive.expect_tx.shared::cta.b64 _,[%0],%1;" ::"r"(a), "r"(bytes) : "memory");
}
__device__ __forceinline__ void mbar_arrive(uint32_t a) {
    asm volatile("mbarrier.arrive.shared::cta.b64 _,[%0];" ::"r"(a) : "memory");
}
__device__ __forceinline__ void mbar_wait(uint32_t a, int ph) {
    asm volatile("{.reg .pred p; .reg .u32 n; mov.u32 n,0;\n"
                 "WL%=: mbarrier.try_wait.parity.shared::cta.b64 p,[%0],%1; @p bra.uni WD%=;\n"
                 "add.u32 n,n,1; setp.lt.u32 p,n,4194304; @p bra.uni WL%=; trap;\n"
                 "WD%=: }" ::"r"(a), "r"(ph) : "memory");
}
__device__ __forceinline__ void bar_sync(int id, int n) { asm volatile("bar.sync %0,%1;" ::"r"(id), "r"(n) : "memory"); }
__device__ __forceinline__ void bar_arrive(int id, int n) { asm volatile("bar.arrive %0,%1;" ::"r"(id), "r"(n) : "memory"); }
__device__ __forceinline__ void cluster_sync() {
    asm volatile("barrier.cluster.arrive.release.aligned; barrier.cluster.wait.acquire.aligned;" ::: "memory");
}
__device__ __forceinline__ void fence_async() { asm volatile("fence.proxy.async.shared::cta;" ::: "memory"); }
__device__ __forceinline__ void ldsm4(uint32_t* r, uint32_t a) {
    asm volatile("ldmatrix.sync.aligned.m8n8.x4.shared.b16 {%0,%1,%2,%3},[%4];"
                 : "=r"(r[0]), "=r"(r[1]), "=r"(r[2]), "=r"(r[3]) : "r"(a) : "memory");
}
__device__ __forceinline__ void ldsm4t(uint32_t* r, uint32_t a) {
    asm volatile("ldmatrix.sync.aligned.m8n8.x4.trans.shared.b16 {%0,%1,%2,%3},[%4];"
                 : "=r"(r[0]), "=r"(r[1]), "=r"(r[2]), "=r"(r[3]) : "r"(a) : "memory");
}
__device__ __forceinline__ void ldsm2(uint32_t* r, uint32_t a) {
    asm volatile("ldmatrix.sync.aligned.m8n8.x2.shared.b16 {%0,%1},[%2];" : "=r"(r[0]), "=r"(r[1]) : "r"(a) : "memory");
}
__device__ __forceinline__ void ldsm2t(uint32_t* r, uint32_t a) {
    asm volatile("ldmatrix.sync.aligned.m8n8.x2.trans.shared.b16 {%0,%1},[%2];" : "=r"(r[0]), "=r"(r[1]) : "r"(a) : "memory");
}
__device__ __forceinline__ void mma16(float* c, const uint32_t* a, uint32_t b0, uint32_t b1) {
    asm("mma.sync.aligned.m16n8k16.row.col.f32.bf16.bf16.f32 {%0,%1,%2,%3},{%4,%5,%6,%7},{%8,%9},{%0,%1,%2,%3};"
                 : "+f"(c[0]), "+f"(c[1]), "+f"(c[2]), "+f"(c[3])
                 : "r"(a[0]), "r"(a[1]), "r"(a[2]), "r"(a[3]), "r"(b0), "r"(b1));
}
__device__ __forceinline__ void mma16v(float* c, const uint32_t* a, uint32_t b0, uint32_t b1) {
    asm volatile("mma.sync.aligned.m16n8k16.row.col.f32.bf16.bf16.f32 {%0,%1,%2,%3},{%4,%5,%6,%7},{%8,%9},{%0,%1,%2,%3};"
                 : "+f"(c[0]), "+f"(c[1]), "+f"(c[2]), "+f"(c[3])
                 : "r"(a[0]), "r"(a[1]), "r"(a[2]), "r"(a[3]), "r"(b0), "r"(b1));
}
__device__ __forceinline__ void mma8(float* c, uint32_t a0, uint32_t a1, uint32_t b0) {
    asm("mma.sync.aligned.m16n8k8.row.col.f32.bf16.bf16.f32 {%0,%1,%2,%3},{%4,%5},{%6},{%0,%1,%2,%3};"
                 : "+f"(c[0]), "+f"(c[1]), "+f"(c[2]), "+f"(c[3]) : "r"(a0), "r"(a1), "r"(b0));
}
__device__ __forceinline__ uint32_t pack2(float lo, float hi) {
    uint32_t r; asm("cvt.rn.bf16x2.f32 %0,%1,%2;" : "=r"(r) : "f"(hi), "f"(lo)); return r;
}
__device__ __forceinline__ float ex2(float x) { float y; asm("ex2.approx.ftz.f32 %0,%1;" : "=f"(y) : "f"(x)); return y; }
__device__ __forceinline__ void sts32(uint32_t a, uint32_t v) { asm volatile("st.shared.u32 [%0],%1;" ::"r"(a), "r"(v) : "memory"); }
__device__ __forceinline__ void sts128(uint32_t a, const uint32_t* v) {
    asm volatile("st.shared.v4.u32 [%0],{%1,%2,%3,%4};" ::"r"(a), "r"(v[0]), "r"(v[1]), "r"(v[2]), "r"(v[3]) : "memory");
}
__device__ __forceinline__ void lds128(uint32_t* v, uint32_t a) {
    asm volatile("ld.shared.v4.u32 {%0,%1,%2,%3},[%4];" : "=r"(v[0]), "=r"(v[1]), "=r"(v[2]), "=r"(v[3]) : "r"(a) : "memory");
}
__device__ __forceinline__ float2 lds64f(uint32_t a) {
    float2 v; asm volatile("ld.shared.v2.f32 {%0,%1},[%2];" : "=f"(v.x), "=f"(v.y) : "r"(a) : "memory"); return v;
}
__device__ __forceinline__ void tma2d(uint32_t dst, const CUtensorMap* m, int c0, int c1, uint32_t bar) {
    asm volatile("cp.async.bulk.tensor.2d.shared::cluster.global.mbarrier::complete_tx::bytes [%0],[%1,{%3,%4}],[%2];"
                 ::"r"(dst), "l"(m), "r"(bar), "r"(c0), "r"(c1) : "memory");
}
__device__ __forceinline__ void tma2d_mc(uint32_t dst, const CUtensorMap* m, int c0, int c1, uint32_t bar, uint16_t mask) {
    asm volatile("cp.async.bulk.tensor.2d.shared::cluster.global.mbarrier::complete_tx::bytes.multicast::cluster [%0],[%1,{%3,%4}],[%2],%5;"
                 ::"r"(dst), "l"(m), "r"(bar), "r"(c0), "r"(c1), "h"(mask) : "memory");
}
__device__ __forceinline__ uint64_t desc_sw128(uint32_t addr, uint32_t lbo, uint32_t sbo) {
    return (uint64_t)((addr & 0x3FFFF) >> 4) | ((uint64_t)(lbo >> 4) << 16) | ((uint64_t)(sbo >> 4) << 32) | (1ull << 62);
}
__device__ __forceinline__ void wg_fence() { asm volatile("wgmma.fence.sync.aligned;" ::: "memory"); }
__device__ __forceinline__ void wg_commit() { asm volatile("wgmma.commit_group.sync.aligned;" ::: "memory"); }
template <int N> __device__ __forceinline__ void wg_wait() { asm volatile("wgmma.wait_group.sync.aligned %0;" ::"n"(N) : "memory"); }

__device__ __forceinline__ void wgmma_rs_n32(float* d, const uint32_t* a, uint32_t dlo, int acc) {
    asm volatile("{.reg .pred p; .reg .b64 dd; setp.ne.b32 p,%21,0; mov.b64 dd,{%20,0x40000040};\n"
                 "wgmma.mma_async.sync.aligned.m64n32k16.f32.bf16.bf16 "
                 "{%0,%1,%2,%3,%4,%5,%6,%7,%8,%9,%10,%11,%12,%13,%14,%15},{%16,%17,%18,%19},dd,p,1,1,0;}"
                 : "+f"(d[0]), "+f"(d[1]), "+f"(d[2]), "+f"(d[3]), "+f"(d[4]), "+f"(d[5]), "+f"(d[6]), "+f"(d[7]),
                   "+f"(d[8]), "+f"(d[9]), "+f"(d[10]), "+f"(d[11]), "+f"(d[12]), "+f"(d[13]), "+f"(d[14]), "+f"(d[15])
                 : "r"(a[0]), "r"(a[1]), "r"(a[2]), "r"(a[3]), "r"(dlo), "r"(acc));
}

__device__ __forceinline__ void wgmma_ss_n32(float* d, uint32_t alo, uint32_t dlo, int acc) {
    asm volatile("{.reg .pred p; .reg .b64 da,dd; setp.ne.b32 p,%18,0; mov.b64 da,{%16,0x00000008}; mov.b64 dd,{%17,0x40000040};\n"
                 "wgmma.mma_async.sync.aligned.m64n32k16.f32.bf16.bf16 "
                 "{%0,%1,%2,%3,%4,%5,%6,%7,%8,%9,%10,%11,%12,%13,%14,%15},da,dd,p,1,1,0,0;}"
                 : "+f"(d[0]), "+f"(d[1]), "+f"(d[2]), "+f"(d[3]), "+f"(d[4]), "+f"(d[5]), "+f"(d[6]), "+f"(d[7]),
                   "+f"(d[8]), "+f"(d[9]), "+f"(d[10]), "+f"(d[11]), "+f"(d[12]), "+f"(d[13]), "+f"(d[14]), "+f"(d[15])
                 : "r"(alo), "r"(dlo), "r"(acc));
}

#define R8(b) "+f"(d[b]), "+f"(d[b + 1]), "+f"(d[b + 2]), "+f"(d[b + 3]), "+f"(d[b + 4]), "+f"(d[b + 5]), "+f"(d[b + 6]), "+f"(d[b + 7])
__device__ __forceinline__ void wgmma_ss_n192(float* d, uint64_t da, uint64_t db, int acc) {
    asm volatile("{.reg .pred p; setp.ne.b32 p,%98,0;\n"
                 "wgmma.mma_async.sync.aligned.m64n192k16.f32.bf16.bf16 "
                 "{%0,%1,%2,%3,%4,%5,%6,%7,%8,%9,%10,%11,%12,%13,%14,%15,%16,%17,%18,%19,%20,%21,%22,%23,"
                 "%24,%25,%26,%27,%28,%29,%30,%31,%32,%33,%34,%35,%36,%37,%38,%39,%40,%41,%42,%43,%44,%45,%46,%47,"
                 "%48,%49,%50,%51,%52,%53,%54,%55,%56,%57,%58,%59,%60,%61,%62,%63,%64,%65,%66,%67,%68,%69,%70,%71,"
                 "%72,%73,%74,%75,%76,%77,%78,%79,%80,%81,%82,%83,%84,%85,%86,%87,%88,%89,%90,%91,%92,%93,%94,%95},"
                 "%96,%97,p,1,1,0,1;}"
                 : R8(0), R8(8), R8(16), R8(24), R8(32), R8(40), R8(48), R8(56), R8(64), R8(72), R8(80), R8(88)
                 : "l"(da), "l"(db), "r"(acc));
}

__device__ __forceinline__ void wgmma_ss_n64(float* d, uint64_t da, uint64_t db) {
    asm volatile("wgmma.mma_async.sync.aligned.m64n64k16.f32.bf16.bf16 "
                 "{%0,%1,%2,%3,%4,%5,%6,%7,%8,%9,%10,%11,%12,%13,%14,%15,%16,%17,%18,%19,%20,%21,%22,%23,"
                 "%24,%25,%26,%27,%28,%29,%30,%31},%32,%33,1,1,1,0,1;"
                 : R8(0), R8(8), R8(16), R8(24) : "l"(da), "l"(db));
}

constexpr int NSS = 1;
constexpr int QCH = 4, QD = 4;
constexpr int WRES = 2, WO_PRE2 = 3, WO_PRE3 = 4;
constexpr int MP = 1168;
constexpr int XT = 36864;
constexpr int XR_STAGE = 14 * 1024;
constexpr int MR_STAGE = 14 * 256;
constexpr int SM_X = 0;
constexpr int SM_XR = 2 * XT;
constexpr int SM_MR = SM_XR + 3 * XR_STAGE;
constexpr int SM_MEM = SM_MR + 3 * MR_STAGE;
constexpr int SM_SC = SM_MEM + 8 * MP;
constexpr int SM_OB = SM_SC + 3 * 1536;
constexpr int SM_ZERO = SM_OB + 2048;
constexpr int SM_WO = SM_ZERO + 512;
constexpr int SM_WS = SM_WO + 49152;
constexpr int SM_BAR = SM_WS + NSS * 4096;
constexpr int REC_SMEM = SM_BAR + 128 + 1024;

__device__ uint4 g_xr[NSEG * NH * 24 * 64];
__device__ uint4 g_mr[NSEG * NH * 16 * 16];
__device__ unsigned g_flagA[NSEG];

constexpr unsigned long long FSP = 0x111234a333ull;
__host__ __device__ constexpr int f_split(int m) { return m < 3 ? 1 : (int)((FSP >> (4 * (12 - m))) & 15); }
constexpr int F_FIRST_SPLIT = f_split(3) > 1 ? 3 : (f_split(4) > 1 ? 4 : (f_split(5) > 1 ? 5 : 6));
struct RecParams {
    const bf16* mem0; const bf16* Wq; const bf16* Wk; const bf16* Wv; const bf16* Wo; const bf16* x; const bf16* wqkv;
    int d0, dv;
};

__device__ __forceinline__ float* red_line(int s, int line) { return g_red + ((s >> 3) * 192 + line) * 256 + (s & 7) * 32; }

#define PIN(x) asm volatile("" : "+r"(x))
#define PINL(x) asm volatile("" : "+l"(x))
__device__ __forceinline__ float4 ld_relaxed4(const float* q) {
    float4 v;
    asm volatile("ld.relaxed.gpu.global.v4.f32 {%0,%1,%2,%3},[%4];" : "=f"(v.x), "=f"(v.y), "=f"(v.z), "=f"(v.w) : "l"(q) : "memory");
    return v;
}
__device__ __forceinline__ unsigned ld_acq(const unsigned* q) {
    unsigned v; asm volatile("ld.acquire.gpu.global.u32 %0,[%1];" : "=r"(v) : "l"(q) : "memory"); return v;
}
__device__ __forceinline__ unsigned ld_relaxed1(const unsigned* q) {
    unsigned v; asm volatile("ld.relaxed.gpu.global.u32 %0,[%1];" : "=r"(v) : "l"(q) : "memory"); return v;
}
__device__ __forceinline__ uint4 ld_relaxed4u(const uint4* q) {
    uint4 v;
    asm volatile("ld.relaxed.gpu.global.v4.u32 {%0,%1,%2,%3},[%4];" : "=r"(v.x), "=r"(v.y), "=r"(v.z), "=r"(v.w) : "l"(q) : "memory");
    return v;
}
__device__ __forceinline__ void reld_relaxed4u(uint4& v, const uint4* q) {
    asm volatile("{.reg .pred p; .reg .b32 q; and.b32 q,%3,0xffff; setp.ne.u32 p,q,0x5000;\n"
                 "@p ld.relaxed.gpu.global.v4.u32 {%0,%1,%2,%3},[%4];}"
                 : "+r"(v.x), "+r"(v.y), "+r"(v.z), "+r"(v.w) : "l"(q) : "memory");
}
__device__ __forceinline__ uint32_t packh2(float lo, float hi) {
    uint32_t r; asm("cvt.rn.f16x2.f32 %0,%1,%2;" : "=r"(r) : "f"(hi), "f"(lo)); return r;
}
__device__ __forceinline__ float maxn(float a, float b) {
    float r; asm("max.NaN.f32 %0,%1,%2;" : "=f"(r) : "f"(fabsf(a)), "f"(fabsf(b))); return r;
}
__device__ __forceinline__ void redh4(uint4* q, const float* v, uint32_t tag) {
    asm volatile("red.relaxed.gpu.global.add.noftz.v4.f16x2 [%0],{%1,%2,%3,%4};"
                 ::"l"(q), "r"(packh2(v[0], v[1])), "r"(packh2(v[2], v[3])), "r"(packh2(v[4], v[5])), "r"(tag) : "memory");
}
__device__ __forceinline__ void red4(float* q, float a, float b, float c2, float d) {
    asm volatile("red.relaxed.gpu.global.add.v4.f32 [%0],{%1,%2,%3,%4};" ::"l"(q), "f"(a), "f"(b), "f"(c2), "f"(d) : "memory");
}
__device__ __forceinline__ unsigned clk32() { return (unsigned)clock64(); }
__device__ __forceinline__ void spin_until(unsigned tl) {
    asm volatile("{.reg .pred p; .reg .u64 c; .reg .u32 lo,hi; .reg .s32 d;\n"
                 "SP%=: mov.u64 c,%%clock64; mov.b64 {lo,hi},c; sub.s32 d,lo,%0; setp.lt.s32 p,d,0; @p bra.uni SP%=;}" ::"r"(tl) : "memory");
}
__device__ __forceinline__ float rcp_fast(float x) { float y; asm("rcp.approx.ftz.f32 %0,%1;" : "=f"(y) : "f"(x)); return y; }
__device__ __forceinline__ void bulk_store(void* gdst, uint32_t src, int bytes) {
    asm volatile("cp.async.bulk.global.shared::cta.bulk_group [%0],[%1],%2;" ::"l"(gdst), "r"(src), "r"(bytes) : "memory");
}
__device__ __forceinline__ void bulk_load(uint32_t dst, const void* gsrc, int bytes, uint32_t bar) {
    asm volatile("cp.async.bulk.shared::cluster.global.mbarrier::complete_tx::bytes [%0],[%1],%2,[%3];"
                 ::"r"(dst), "l"(gsrc), "r"(bytes), "r"(bar) : "memory");
}
__device__ __forceinline__ void bulk_s2s(uint32_t rdst, uint32_t src, int bytes, uint32_t rbar) {
    asm volatile("cp.async.bulk.shared::cluster.shared::cta.mbarrier::complete_tx::bytes [%0],[%1],%2,[%3];"
                 ::"r"(rdst), "r"(src), "r"(bytes), "r"(rbar) : "memory");
}
__device__ __forceinline__ void stas4(uint32_t rdst, uint32_t a, uint32_t b, uint32_t c2, uint32_t d, uint32_t rbar) {
    asm volatile("st.async.weak.shared::cluster.mbarrier::complete_tx::bytes.v4.b32 [%0],{%1,%2,%3,%4},[%5];"
                 ::"r"(rdst), "r"(a), "r"(b), "r"(c2), "r"(d), "r"(rbar) : "memory");
}
__device__ __forceinline__ void stas2(uint32_t rdst, uint32_t a, uint32_t b, uint32_t rbar) {
    asm volatile("st.async.weak.shared::cluster.mbarrier::complete_tx::bytes.v2.b32 [%0],{%1,%2},[%3];"
                 ::"r"(rdst), "r"(a), "r"(b), "r"(rbar) : "memory");
}
__device__ __forceinline__ float4 lds128f(uint32_t a) {
    float4 v; asm volatile("ld.shared.v4.f32 {%0,%1,%2,%3},[%4];" : "=f"(v.x), "=f"(v.y), "=f"(v.z), "=f"(v.w) : "r"(a) : "memory"); return v;
}

__device__ __forceinline__ void flag_seg(int seg) {
    asm volatile("cp.async.bulk.wait_group 0;" ::: "memory");
    asm volatile("red.relaxed.gpu.global.add.u32 [%0],1;" ::"l"(g_flagA + seg) : "memory");
}

__global__ void __launch_bounds__(384, 1) k_rec(const __grid_constant__ CUtensorMap tmx, const RecParams p) {
    extern __shared__ uint8_t smem_raw[];
    const uint32_t sb = (s2u(smem_raw) + 1023) & ~1023u;
    const int tid = threadIdx.x, warp = __shfl_sync(0xffffffffu, tid >> 5, 0), lane = tid & 31, g = lane >> 2, t = lane & 3;
    const int l7 = lane & 7, l3 = lane >> 3;
    const int c = blockIdx.x % 3, h = blockIdx.x / 3;
    const int nq = c < 2 ? 3 : 2, nv = 8 - 2 * nq, v0 = 2 * c;
    const uint32_t bXF = sb + SM_BAR, bVX = bXF + 16, bS = bVX + 16, bV = bS + 8;
    const uint32_t peer1 = (c + 1) % 3, peer2 = (c + 2) % 3;
    auto vslot = [](int r, int d) { return (r < 2 ? 6 : 4) + ((d - 2 * r) & 7); };

    if (tid == 1) asm volatile("cp.async.bulk.prefetch.L2.global [%0],20736;" ::"l"(reinterpret_cast<const uint8_t*>(p.wqkv) + (size_t)blockIdx.x * 20736) : "memory");
    if (tid == 33) asm volatile("cp.async.bulk.prefetch.L2.global [%0],9216;" ::"l"(reinterpret_cast<const uint8_t*>(p.x) + (size_t)blockIdx.x * 9216) : "memory");
    __syncthreads();
    if (lane == 0) {
        const int wsel = warp / 3;
        const bf16* W = wsel == 0 ? p.Wq : (wsel == 1 ? p.Wk : (wsel == 2 ? p.Wv : p.Wo));
        asm volatile("cp.async.bulk.prefetch.L2.global [%0],16384;" ::"l"(reinterpret_cast<const uint8_t*>(W) + (size_t)((warp % 3) * 96 + blockIdx.x) * 16384) : "memory");
    }
    if (tid == 0) {
        for (int i = 0; i < 2; i++) { mbar_init(bXF + 8 * i, 1); mbar_init(bVX + 8 * i, 1); }
        mbar_init(bS, 4); mbar_init(bV, nv + 1);
        asm volatile("fence.mbarrier_init.release.cluster;" ::: "memory");
        for (int i = 0; i < 2; i++) { mbar_expect(bXF + 8 * i, XT); mbar_expect(bVX + 8 * i, (8 - nv) * 1024); }
        mbar_expect(bS, 2560); mbar_expect(bV, (8 - nv) * 256);
    }
    if (blockIdx.x == 0) {
        for (int i = tid; i < 1920; i += 384) g_ctr[i] = 0;
        if (tid < NSEG) g_flagA[tid] = 0;
        __threadfence();
    }
    __syncthreads();
    asm volatile("griddepcontrol.launch_dependents;" ::: "memory");
    cluster_sync();

    if (warp < 8) {
        asm volatile("setmaxnreg.inc.sync.aligned.u32 %0;" ::"n"(184));
        if (tid == 0) {
            for (int sl = 0; sl < 2; sl++)
                for (int j = 0; j < 3; j++)
                    tma2d_mc(sb + SM_X + sl * XT + (c * 3 + j) * 4096, &tmx, (c * 3 + j) * 64, sl * 32, bXF + 8 * sl, 7);
        }
        const bool isv = warp >= 2 * nq;
        const int slot = warp;
        uint32_t w[36][4];
        {
            const int dt = isv ? v0 + warp - 2 * nq : 3 * c + (warp >= nq ? warp - nq : warp);
            const bf16* W = (isv ? p.Wv : (warp >= nq ? p.Wk : p.Wq)) + h * DH + dt * 16 + 2 * g + (size_t)(2 * t) * HD;
#pragma unroll
            for (int k = 0; k < 36; k++) {
                const uint32_t* q = reinterpret_cast<const uint32_t*>(W + (size_t)k * 16 * HD);
                w[k][0] = __ldg(q); w[k][1] = __ldg(q + HD / 2); w[k][2] = __ldg(q + 4 * HD); w[k][3] = __ldg(q + 4 * HD + HD / 2);
            }
#pragma unroll
            for (int k = 0; k < 36; k++) {
                uint32_t a = w[k][0], b = w[k][1], d = w[k][2], e = w[k][3];
                w[k][0] = __byte_perm(a, b, 0x5410); w[k][1] = __byte_perm(a, b, 0x7632);
                w[k][2] = __byte_perm(d, e, 0x5410); w[k][3] = __byte_perm(d, e, 0x7632);
            }
#pragma unroll
            for (int k = 0; k < NSS; k++) {
                const uint32_t a = sb + SM_WS + k * 4096 + (warp >> 2) * 2048 + (warp & 3) * 256 + lane * 4;
                sts32(a, w[36 - NSS + k][0]); sts32(a + 128, w[36 - NSS + k][1]);
                sts32(a + 1024, w[36 - NSS + k][2]); sts32(a + 1152, w[36 - NSS + k][3]);
            }
            fence_async();
            bar_sync(9, 256);
        }
        const uint32_t wsd = (((sb + SM_WS + (warp >> 2) * 2048) & 0x3FFFF) >> 4) | (64u << 16);
        const uint32_t woff = 2 * t * 32 + (((g >> 2) ^ (t >> 1)) << 4) + (g & 3) * 4;

        float d[16];
        auto xdesc = [&](int sl) { return __shfl_sync(0xffffffffu, (((sb + SM_X + sl * XT) & 0x3FFFF) >> 4) | 0x10000u, 0); };
        auto filler = [&](uint32_t xd, int stg) {
            wg_fence();
#pragma unroll
            for (int k = 36 - NSS; k < 36; k++) wgmma_ss_n32(d, wsd + (k - 36 + NSS) * 256, xd + ((k >> 2) * 256 + (k & 3) * 2), k > 36 - NSS);
#pragma unroll
            for (int k = 0; k < 36 - NSS; k++) wgmma_rs_n32(d, w[k], xd + ((k >> 2) * 256 + (k & 3) * 2), 1);
            wg_commit();
            wg_wait<0>();
            const uint32_t dst = sb + SM_XR + stg * XR_STAGE + slot * 1024 + woff;
#pragma unroll
            for (int j = 0; j < 4; j++) {
                sts32(dst + j * 256, pack2(d[4 * j], d[4 * j + 2]));
                sts32(dst + j * 256 + 32, pack2(d[4 * j + 1], d[4 * j + 3]));
            }
        };
        auto fwd_v = [&](int sl, int stg) {
            const uint32_t base = sb + SM_XR + stg * XR_STAGE;
            bulk_s2s(mapa(base + vslot(peer1, v0) * 1024, peer1), base + 2 * nq * 1024, nv * 1024, mapa(bVX + 8 * sl, peer1));
            bulk_s2s(mapa(base + vslot(peer2, v0) * 1024, peer2), base + 2 * nq * 1024, nv * 1024, mapa(bVX + 8 * sl, peer2));
        };

        mbar_wait(bXF, 0);
        filler(xdesc(0), 0);
        fence_async();
        bar_sync(9, 256);
        if (tid == 32) fwd_v(0, 0);
        __syncwarp();
        mbar_wait(bXF + 8, 0);
        filler(xdesc(1), 1);
        bar_sync(9, 256);
        if (tid == 0) { mbar_expect(bXF, XT); mbar_expect(bXF + 8, XT); }
        cluster_sync();
        if (tid == 0) {
            for (int sl = 0; sl < 2; sl++)
                for (int j = 0; j < 3; j++)
                    tma2d_mc(sb + SM_X + sl * XT + (c * 3 + j) * 4096, &tmx, (c * 3 + j) * 64, (2 + sl) * 32, bXF + 8 * sl, 7);
        }
        __syncwarp();
        uint32_t mema = sb + SM_MEM + l7 * MP + l3 * 16;
        const uint32_t xpeer = (g & 2) ? peer2 : peer1;
        const uint32_t rdst0 = mapa(sb + SM_MR + vslot(xpeer, v0 + warp - 2 * nq) * 256 + (2 * t + (g & 1)) * 32 + (((g >> 2) ^ (t >> 1)) << 4), xpeer);
        uint32_t rbar = mapa(bV, xpeer);
        int s3 = 0;
        for (int s = 0; s < NSEG; s++) {
            const int st = s & 1, s3n = s3 == 2 ? 0 : s3 + 1, s3p = s3 == 0 ? 2 : s3 - 1;
            uint32_t rdst = rdst0 + s3 * MR_STAGE;
            uint32_t ldst = sb + SM_MR + s3 * MR_STAGE + slot * 256 + woff;
            PIN(rdst); PIN(rbar); PIN(ldst); PIN(mema);
            float a[QCH][4];
#pragma unroll
            for (int i = 0; i < QCH; i++) { a[i][0] = 0.f; a[i][1] = 0.f; a[i][2] = 0.f; a[i][3] = 0.f; }
            uint32_t wx[NSS][4];
#pragma unroll
            for (int k = 0; k < NSS; k++)
                ldsm4(wx[k], sb + SM_WS + k * 4096 + (warp >> 2) * 2048 + (warp & 3) * 256 + (l3 >> 1) * 1024 + (l3 & 1) * 128 + l7 * 16);
            bar_sync(1, 384);
            if (isv) spin_until(clk32() + p.dv);
            uint32_t bf[18][4];
#pragma unroll
            for (int ii = 0; ii < QD; ii++) ldsm4(bf[17 - ii], mema + (17 - ii) * 64);
#pragma unroll
            for (int ii = 0; ii < 18; ii++) {
                const int i = 17 - ii;
                mma16v(a[(2 * i) % QCH], 2 * i >= 36 - NSS ? wx[2 * i - 36 + NSS] : w[2 * i], bf[i][0], bf[i][1]);
                mma16v(a[(2 * i + 1) % QCH], 2 * i + 1 >= 36 - NSS ? wx[2 * i + 1 - 36 + NSS] : w[2 * i + 1], bf[i][2], bf[i][3]);
                if (i - QD >= 0) ldsm4(bf[i - QD], mema + (i - QD) * 64);
            }
#pragma unroll
            for (int i = 0; i < 4; i++) {
                a[0][i] = (a[2][i] + a[3][i]) + (a[0][i] + a[1][i]);
            }
            const uint32_t w0 = pack2(a[0][0], a[0][2]), w1 = pack2(a[0][1], a[0][3]);
            sts32(ldst, w0); sts32(ldst + 32, w1);
            if (!isv) bar_arrive(8, nq * 64 + 96);
            if (isv && s + 1 < NSEG) {
                uint32_t snd = (g & 1) ? w0 : w1, keep = (g & 1) ? w1 : w0;
                uint32_t rcv = __shfl_xor_sync(0xffffffffu, snd, 4);
                uint32_t lo = (g & 1) ? rcv : keep, hi = (g & 1) ? keep : rcv;
                uint32_t olo = __shfl_xor_sync(0xffffffffu, lo, 8), ohi = __shfl_xor_sync(0xffffffffu, hi, 8);
                stas4(rdst, (g & 2) ? olo : lo, (g & 2) ? ohi : hi, (g & 2) ? lo : olo, (g & 2) ? hi : ohi, rbar);
                __syncwarp();
                if (lane == 0) mbar_arrive(bV);
            }
            const uint32_t xd = xdesc(st);
            if (s + 2 < NSEG) {
                mbar_wait(bXF + 8 * st, ((s + 2) >> 1) & 1);
            }
            fence_async();
            bar_arrive(7, 288);
            if (warp == 1) bar_sync(6, 256); else bar_arrive(6, 256);
            if (warp < 2) {
                if (s + 1 < NSEG) { mbar_wait(bS, st); mbar_wait(bV, st); }
                if (lane == 0) {
                    if (warp == 0) {
                        if (s >= 1 && s + 3 < NSEG) {
                            mbar_expect(bXF + 8 * (st ^ 1), XT);
                            for (int j = 0; j < 3; j++)
                                tma2d_mc(sb + SM_X + (st ^ 1) * XT + (c * 3 + j) * 4096, &tmx, (c * 3 + j) * 64, (s + 3) * 32, bXF + 8 * (st ^ 1), 7);
                        }
                    } else {
                        if (s >= 1) flag_seg(s - 1);
                        bulk_store(reinterpret_cast<uint8_t*>(g_mr) + (size_t)(s * 32 + h) * 4096 + c * 1280,
                                   sb + SM_MR + s3 * MR_STAGE + nq * 256, (8 - nq) * 256);
                        asm volatile("cp.async.bulk.commit_group;" ::: "memory");
                        if (s + 2 < NSEG) fwd_v(st ^ 1, s3n);
                    }
                }
                __syncwarp();
            }
            if (s + 2 < NSEG) {
                bar_sync(5, 384);
                filler(xd, s3p);
            } else {
                bar_sync(5, 384);
            }
            s3 = s3n;
        }
        if (tid == 32) flag_seg(NSEG - 1);
    } else {
        asm volatile("setmaxnreg.dec.sync.aligned.u32 %0;" ::"n"(136));
        const int wq = warp - 8, wt = tid - 256;
        uint32_t woa = sb + SM_WO + wt * 16;
        uint32_t am0 = 0;
        {
            for (int i = wt; i < 576; i += 128) g_redh[blockIdx.x * 576 + i] = make_uint4(0u, 0u, 0u, 0u);
            float4* z = reinterpret_cast<float4*>(g_red) + blockIdx.x * 1024;
            for (int i = wt; i < 1024; i += 128) z[i] = make_float4(0.f, 0.f, 0.f, 0.f);
            constexpr int ZN = (SEQ - F_FIRST_SPLIT * 192) * (DM / 4) / 96;
            float4* za = reinterpret_cast<float4*>(g_acc + F_FIRST_SPLIT * 192 * DM) + blockIdx.x * ZN;
            for (int i = wt; i < ZN; i += 128) za[i] = make_float4(0.f, 0.f, 0.f, 0.f);
            __threadfence();
            bar_sync(4, 128);
            if (wt == 0) asm volatile("red.relaxed.gpu.global.add.u32 [%0],1;" ::"l"(g_sync) : "memory");
        }
        {
            const bf16* W = p.Wo + (size_t)(h * DH + 2 * t) * DM + c * 192 + wq * 16 + 2 * g;
            uint32_t wo[24][4];
#pragma unroll
            for (int k = 0; k < 24; k++) {
                const uint32_t* q = reinterpret_cast<const uint32_t*>(W + (k & 7) * 16 * DM + (k >> 3) * 64);
                wo[k][0] = __ldg(q); wo[k][1] = __ldg(q + DM / 2);
                wo[k][2] = __ldg(q + 4 * DM); wo[k][3] = __ldg(q + 4 * DM + DM / 2);
            }
#pragma unroll
            for (int k = 0; k < 24; k++) {
                uint32_t a = wo[k][0], b = wo[k][1], d = wo[k][2], e = wo[k][3];
                wo[k][0] = __byte_perm(a, b, 0x5410); wo[k][1] = __byte_perm(a, b, 0x7632);
                wo[k][2] = __byte_perm(d, e, 0x5410); wo[k][3] = __byte_perm(d, e, 0x7632);
                sts128(woa + k * 2048, wo[k]);
            }
            sts32(sb + SM_ZERO + wt * 4, 0u);
            for (int i = wt; i < 8 * 72; i += 128) {
                const int r = i / 72, cc = i % 72;
                uint4 v = __ldg(reinterpret_cast<const uint4*>(p.mem0 + r * DM) + cc);
                am0 = __vmaxu2(__vmaxu2(am0, __vmaxu2(v.x & 0x7fff7fffu, v.y & 0x7fff7fffu)), __vmaxu2(v.z & 0x7fff7fffu, v.w & 0x7fff7fffu));
                asm volatile("st.shared.v4.u32 [%0],{%1,%2,%3,%4};" ::"r"(sb + SM_MEM + r * MP + cc * 16), "r"(v.x), "r"(v.y), "r"(v.z), "r"(v.w) : "memory");
            }
        }
        cluster_sync();
        bar_arrive(1, 384);
        uint32_t wa[8][4], wb[8][4], wc[WRES + 1][4];
#pragma unroll
        for (int k = 0; k < 8; k++) lds128(wa[k], woa + k * 2048);
#pragma unroll
        for (int k = 0; k < 8; k++) lds128(wb[k], woa + (8 + k) * 2048);
#pragma unroll
        for (int k = 0; k < WRES; k++) lds128(wc[k], woa + (16 + k) * 2048);

        int ex;
        {
            const uint32_t m = __reduce_max_sync(0xffffffffu, max(am0 & 0xffffu, am0 >> 16));
            ex = m ? min(max(4 - ((int)(m >> 7) - 127), -60), 60) : 0;
        }
        const float SC = 0.08838834764831845f * 1.4426950408889634f;
        uint32_t L16 = lane * 16;
        uint32_t AB = (l3 >> 1) * 256 + l7 * 32 + (((l3 & 1) ^ (l7 >> 2)) << 4);
        uint32_t AA = (l3 & 1) * 256 + l7 * 32 + (((l3 >> 1) ^ (l7 >> 2)) << 4);
        const uint32_t scu = sb + SM_SC + c * 1536 + (wq == 0 ? 1024 : (wq - 1) * 512);
        const uint32_t sc1 = mapa(scu, peer1), sc2 = mapa(scu, peer2), sb1 = mapa(bS, peer1), sb2 = mapa(bS, peer2);
        const uint32_t wou = sb + SM_WO + wq * 512;
        const int vs = vslot(c, 2 * wq);
        auto publish = [&](int xs, int stg) {
            if (xs >= 1) flag_seg(xs - 1);
            if (xs < NSEG) {
                bulk_store(reinterpret_cast<uint8_t*>(g_xr) + (size_t)(xs * 96 + blockIdx.x) * 8192, sb + SM_XR + stg * XR_STAGE, 8192);
                asm volatile("cp.async.bulk.commit_group;" ::: "memory");
            }
        };
        int s3 = 0;
        for (int s = 0; s + 1 < NSEG; s++) {
            const int st = s & 1;
            const uint32_t xr = sb + SM_XR + s3 * XR_STAGE, mr = sb + SM_MR + s3 * MR_STAGE;
            PIN(L16); PIN(AB); PIN(AA);
            if (wq < 3) {
                uint32_t kf[3][4], q0[4], q1[4];
                float ca[4] = {0.f, 0.f, 0.f, 0.f}, cb[4] = {0.f, 0.f, 0.f, 0.f}, cc[4] = {0.f, 0.f, 0.f, 0.f};
                if (wq) {
                    const uint32_t ka = xr + nq * 1024 + (wq - 1) * 512 + AB;
                    ldsm4(kf[0], ka); ldsm4(kf[1], ka + 1024); ldsm4(kf[2], nq == 3 ? ka + 2048 : sb + SM_ZERO + AB);
                    uint32_t da1 = sc1 + L16, da2 = sc2 + L16, qa = mr + AA;
                    PIN(da1); PIN(da2); PIN(qa);
                    bar_sync(8, nq * 64 + 96);
                    ldsm4(q0, qa); ldsm4(q1, qa + 512);
                    float da[4] = {0.f, 0.f, 0.f, 0.f}, db[4] = {0.f, 0.f, 0.f, 0.f}, dc[4] = {0.f, 0.f, 0.f, 0.f};
                    mma16(ca, q0, kf[0][0], kf[0][1]); mma16(da, q0, kf[0][2], kf[0][3]);
                    mma16(cb, q0, kf[1][0], kf[1][1]); mma16(db, q0, kf[1][2], kf[1][3]);
                    mma16(cc, q1, kf[2][0], kf[2][1]); mma16(dc, q1, kf[2][2], kf[2][3]);
                    const uint32_t rr[4] = {__float_as_uint((ca[0] + cb[2]) + cc[0]), __float_as_uint((ca[1] + cb[3]) + cc[1]),
                                            __float_as_uint((da[0] + db[2]) + dc[0]), __float_as_uint((da[1] + db[3]) + dc[1])};
                    stas4(da1, rr[0], rr[1], rr[2], rr[3], sb1); stas4(da2, rr[0], rr[1], rr[2], rr[3], sb2);
                    sts128(scu + L16, rr);
                } else {
                    uint32_t da1 = sc1 + (L16 >> 1), da2 = sc2 + (L16 >> 1), qa = mr + AA, ka = mr + nq * 256 + AB;
                    uint32_t kb = nq == 3 ? ka + 512 : sb + SM_ZERO + AB;
                    PIN(da1); PIN(da2); PIN(qa); PIN(ka); PIN(kb);
                    bar_sync(8, nq * 64 + 96);
                    ldsm4(q0, qa); ldsm4(kf[0], ka); ldsm4(q1, qa + 512); ldsm2(kf[1], kb);
                    mma16(ca, q0, kf[0][0], kf[0][1]); mma16(cb, q0, kf[0][2], kf[0][3]); mma16(cc, q1, kf[1][0], kf[1][1]);
                    const uint32_t r0 = __float_as_uint((ca[0] + cb[2]) + cc[0]), r1 = __float_as_uint((ca[1] + cb[3]) + cc[1]);
                    stas2(da1, r0, r1, sb1); stas2(da2, r0, r1, sb2);
                    asm volatile("st.shared.v2.u32 [%0],{%1,%2};" ::"r"(scu + (L16 >> 1)), "r"(r0), "r"(r1) : "memory");
                }
                __syncwarp();
                if (L16 == 0) mbar_arrive(bS);
            } else {
                if (lane == 0) {
                    if (s >= 1 && s + 4 < NSEG)
                        asm volatile("prefetch.global.L2 [%0];" ::"l"(g_redh + (((s + 3) >> 3) * 96 + blockIdx.x) * 72 + ((s + 3) & 7) * 8));
                    publish(s, s3);
                    if (s == 0) {
                        int it = 0;
                        while (ld_acq(g_sync) < 96) { if (++it > (1 << 22)) __trap(); }
                    }
                }
                __syncwarp();
            }
            uint32_t va[2][2][4], vb[4];
            mbar_wait(bVX + 8 * st, (s >> 1) & 1);
            const uint32_t v0a = xr + vs * 1024 + AB;
            ldsm4t(va[0][0], v0a); ldsm4t(va[1][0], v0a + 1024);
            uint4* rl = g_redh + (((s >> 3) * 96 + c * 32 + wq * 4) * 9 + (s & 7)) * 8 + (L16 >> 7) * 72 + ((L16 >> 4) & 7);
            PINL(rl);
            mbar_wait(bS, s & 1);
            float4 sa, sbb; float2 sm2;
            {
                const uint32_t scl = sb + SM_SC + L16;
                const float4 a0 = lds128f(scl), a1 = lds128f(scl + 1536), a2 = lds128f(scl + 3072);
                const float4 b0 = lds128f(scl + 512), b1 = lds128f(scl + 2048), b2 = lds128f(scl + 3584);
                const uint32_t scm = sb + SM_SC + 1024 + (L16 >> 1);
                const float2 m0 = lds64f(scm), m1 = lds64f(scm + 1536), m2 = lds64f(scm + 3072);
                sa.x = a0.x + a1.x + a2.x; sa.y = a0.y + a1.y + a2.y; sa.z = a0.z + a1.z + a2.z; sa.w = a0.w + a1.w + a2.w;
                sbb.x = b0.x + b1.x + b2.x; sbb.y = b0.y + b1.y + b2.y; sbb.z = b0.z + b1.z + b2.z; sbb.w = b0.w + b1.w + b2.w;
                sm2.x = m0.x + m1.x + m2.x; sm2.y = m0.y + m1.y + m2.y;
            }
            float mx = fmaxf(fmaxf(fmaxf(sa.x, sa.y), fmaxf(sa.z, sa.w)), fmaxf(fmaxf(sbb.x, sbb.y), fmaxf(sbb.z, sbb.w)));
            mx = fmaxf(mx, fmaxf(sm2.x, sm2.y));
            {
                const float x1 = __shfl_xor_sync(0xffffffffu, mx, 1), x2 = __shfl_xor_sync(0xffffffffu, mx, 2), x3 = __shfl_xor_sync(0xffffffffu, mx, 3);
                ldsm4t(va[0][1], v0a + 512); ldsm4t(va[1][1], v0a + 1024 + 512);
                mbar_wait(bV, s & 1);
                ldsm4t(vb, mr + vs * 256 + AB);
                mx = fmaxf(fmaxf(mx, x1), fmaxf(x2, x3));
            }
            uint32_t ws[8][4];
#pragma unroll
            for (int k = WRES; k < WRES + WO_PRE2 && k < 8; k++) lds128(ws[k], wou + L16 + (16 + k) * 2048);
            const float mo = mx * SC;
            const float e0 = ex2(fmaf(sa.x, SC, -mo)), e1 = ex2(fmaf(sa.y, SC, -mo)), e2 = ex2(fmaf(sa.z, SC, -mo)), e3 = ex2(fmaf(sa.w, SC, -mo));
            float o0[4] = {0.f, 0.f, 0.f, 0.f}, o1[4] = {0.f, 0.f, 0.f, 0.f}, o2[4] = {0.f, 0.f, 0.f, 0.f};
            const uint32_t one = 0x3f803f80u, one4[4] = {one, one, one, one};
            { const uint32_t p0 = pack2(e0, e1), p1 = pack2(e2, e3); mma16(o0, va[0][0], p0, p1); mma16(o1, va[1][0], p0, p1); mma16(o2, one4, p0, p1); }
            const float e4 = ex2(fmaf(sbb.x, SC, -mo)), e5 = ex2(fmaf(sbb.y, SC, -mo)), e6 = ex2(fmaf(sbb.z, SC, -mo)), e7 = ex2(fmaf(sbb.w, SC, -mo));
            { const uint32_t p0 = pack2(e4, e5), p1 = pack2(e6, e7); mma16(o0, va[0][1], p0, p1); mma16(o1, va[1][1], p0, p1); mma16(o2, one4, p0, p1); }
            const float e8 = ex2(fmaf(sm2.x, SC, -mo)), e9 = ex2(fmaf(sm2.y, SC, -mo));
            { const uint32_t p0 = pack2(e8, e9); mma8(o0, vb[0], vb[1], p0); mma8(o1, vb[2], vb[3], p0); mma8(o2, one, one, p0); }
            {
                const uint32_t oa = sb + SM_OB + wq * 512 + (L16 >> 2);
                sts32(oa, pack2(o0[0], o0[1])); sts32(oa + 128, pack2(o0[2], o0[3]));
                sts32(oa + 256, pack2(o1[0], o1[1])); sts32(oa + 384, pack2(o1[2], o1[3]));
            }
            bar_sync(4, 128);
            uint32_t ob[4][4];
#pragma unroll
            for (int j = 0; j < 4; j++) ldsm4t(ob[j], sb + SM_OB + L16 + 512 * j);
            const float fs = __int_as_float((127 + ex) << 23);
            const float i0 = rcp_fast(o2[0]) * fs, i1 = rcp_fast(o2[1]) * fs;
            float v[12];
            {
                float r[6][4];
#pragma unroll
                for (int i = 0; i < 6; i++) { r[i][0] = 0.f; r[i][1] = 0.f; r[i][2] = 0.f; r[i][3] = 0.f; }
#pragma unroll
                for (int k = WRES + WO_PRE2; k < WRES + WO_PRE3 && k < 8; k++) lds128(ws[k], wou + L16 + (16 + k) * 2048);
#pragma unroll
                for (int i = 0; i < 8; i++) {
                    mma16v(r[(i & 1) ? 3 : 0], wa[i], ob[i >> 1][(i & 1) * 2], ob[i >> 1][(i & 1) * 2 + 1]);
                    mma16v(r[(i & 1) ? 4 : 1], wb[i], ob[i >> 1][(i & 1) * 2], ob[i >> 1][(i & 1) * 2 + 1]);
                    mma16v(r[(i & 1) ? 5 : 2], i < WRES ? wc[i] : ws[i], ob[i >> 1][(i & 1) * 2], ob[i >> 1][(i & 1) * 2 + 1]);
                    if (i + WRES + WO_PRE3 < 8) lds128(ws[i + WRES + WO_PRE3], wou + L16 + (16 + i + WRES + WO_PRE3) * 2048);
                }
#pragma unroll
                for (int j = 0; j < 3; j++) {
                    { r[j][0] += r[3 + j][0]; r[j][1] += r[3 + j][1]; r[j][2] += r[3 + j][2]; r[j][3] += r[3 + j][3]; }
                    v[4 * j] = r[j][0] * i0; v[4 * j + 1] = r[j][2] * i0; v[4 * j + 2] = r[j][1] * i1; v[4 * j + 3] = r[j][3] * i1;
                }
                const float m8 = maxn(maxn(maxn(v[0], v[1]), maxn(v[2], v[3])), maxn(maxn(v[4], v[5]), maxn(v[6], v[7])));
                const float m = maxn(maxn(maxn(v[8], v[9]), maxn(v[10], v[11])), m8);
                const uint32_t tag = m < 1024.f ? (m >= 0.0625f ? 0x3c003c00u : 0x00003c00u) : 0x54003c00u;
                redh4(rl, v, tag);
                bar_arrive(5, 384);
                redh4(rl + 16 * 72, v + 6, tag);
            }
            const unsigned tred = clk32();
            if (wq == 3) bar_sync(7, 288);
            if (wt == 0) {
                if (s + 2 < NSEG) { mbar_expect(bS, 2560); mbar_expect(bV, (8 - nv) * 256); }
                if (s + 3 < NSEG) mbar_expect(bVX + 8 * st, (8 - nv) * 1024);
            }
            {
                const uint4* gl = rl - c * 32 * 72;
                uint32_t ma = sb + SM_MEM + wq * 32 + ((L16 >> 4) & 3) * (2 * MP) + (L16 >> 6) * 4;
                PINL(gl); PIN(ma);
                unsigned tl = tred + p.d0;
                spin_until(tl);
                uint4 u[2][3];
#pragma unroll
                for (int j = 0; j < 2; j++)
#pragma unroll
                    for (int cc = 0; cc < 3; cc++) u[j][cc] = ld_relaxed4u(gl + (cc * 32 + j * 16) * 72);
                const uint32_t rebias = (uint32_t)(112 - ex) * 0x00800080u;
                int it = 0;
                auto cvt = [&](uint32_t x) { return ((((x + 0x00030004u) & 0x7ff87ff8u) >> 3) + rebias) | (x & 0x80008000u); };
                auto put = [&](int j, int cc) {
                    sts32(ma + (cc * 192 + ((3 * j) >> 1) * 64) * 2 + ((3 * j) & 1) * MP, u[j][cc].x);
                    sts32(ma + (cc * 192 + ((3 * j + 1) >> 1) * 64) * 2 + ((3 * j + 1) & 1) * MP, u[j][cc].y);
                    sts32(ma + (cc * 192 + ((3 * j + 2) >> 1) * 64) * 2 + ((3 * j + 2) & 1) * MP, u[j][cc].z);
                };
#pragma unroll
                for (int j = 0; j < 2; j++)
#pragma unroll
                    for (int cc = 0; cc < 3; cc++) {
                        u[j][cc].x = cvt(u[j][cc].x); u[j][cc].y = cvt(u[j][cc].y); u[j][cc].z = cvt(u[j][cc].z);
                        put(j, cc);
                    }
                {
                    const uint32_t bad = ((u[0][0].w ^ 0x5000u) | (u[0][1].w ^ 0x5000u) | (u[0][2].w ^ 0x5000u)) |
                                         ((u[1][0].w ^ 0x5000u) | (u[1][1].w ^ 0x5000u) | (u[1][2].w ^ 0x5000u));
                    const uint32_t tg = max(max(max(u[0][0].w, u[0][1].w), u[0][2].w), max(max(u[1][0].w, u[1][1].w), u[1][2].w));
                    const bool clean = __all_sync(0xffffffffu, (bad & 0xffffu) == 0 && tg < 0x54000000u);
                    const bool big = __any_sync(0xffffffffu, tg >= 0x3c000000u);
                    if (__builtin_expect(!(clean && big), 0)) {
                        while (true) {
                            bool ok = true;
#pragma unroll
                            for (int j = 0; j < 2; j++)
#pragma unroll
                                for (int cc = 0; cc < 3; cc++) ok = ok && (u[j][cc].w & 0xffffu) == 0x5000u;
                            if (__all_sync(0xffffffffu, ok)) break;
                            if (++it > (1 << 20)) __trap();
                            uint32_t redo = 0;
#pragma unroll
                            for (int j = 0; j < 2; j++)
#pragma unroll
                                for (int cc = 0; cc < 3; cc++) {
                                    if ((u[j][cc].w & 0xffffu) != 0x5000u) redo |= 1u << (j * 3 + cc);
                                    reld_relaxed4u(u[j][cc], gl + (cc * 32 + j * 16) * 72);
                                }
#pragma unroll
                            for (int j = 0; j < 2; j++)
#pragma unroll
                                for (int cc = 0; cc < 3; cc++) {
                                    const bool rd = (redo >> (j * 3 + cc)) & 1;
                                    u[j][cc].x = rd ? cvt(u[j][cc].x) : u[j][cc].x; u[j][cc].y = rd ? cvt(u[j][cc].y) : u[j][cc].y;
                                    u[j][cc].z = rd ? cvt(u[j][cc].z) : u[j][cc].z;
                                    put(j, cc);
                                }
                        }
                        const uint32_t t2 = max(max(max(u[0][0].w, u[0][1].w), u[0][2].w), max(max(u[1][0].w, u[1][1].w), u[1][2].w));
                        if (__any_sync(0xffffffffu, t2 >= 0x54000000u) || !__any_sync(0xffffffffu, t2 >= 0x3c000000u)) {
                            const float isc = __int_as_float((127 - ex) << 23);
                            float* fl = red_line(s, c * 64 + wq * 4 + (L16 >> 7)) + ((L16 >> 2) & 28);
#pragma unroll
                            for (int i = 0; i < 4; i++) red4(fl + i * 16 * 256, v[3 * i], v[3 * i + 1], v[3 * i + 2], 1.0f);
                            const float* fg = fl - c * 64 * 256;
#pragma unroll
                            for (int j = 0; j < 2; j++)
#pragma unroll
                                for (int cc = 0; cc < 3; cc++) {
                                    float4 a, b;
                                    while (true) {
                                        a = ld_relaxed4(fg + (cc * 64 + j * 32) * 256); b = ld_relaxed4(fg + (cc * 64 + j * 32 + 16) * 256);
                                        if (__all_sync(0xffffffffu, a.w == 32.f && b.w == 32.f)) break;
                                        if (++it > (1 << 20)) __trap();
                                    }
                                    u[j][cc].x = pack2(a.x * isc, a.y * isc); u[j][cc].y = pack2(a.z * isc, b.x * isc); u[j][cc].z = pack2(b.y * isc, b.z * isc);
                                    put(j, cc);
                                }
                        }
                    }
                }
                bar_arrive(1, 384);
                uint32_t am = max(max(u[0][0].x << 1, u[0][1].y << 1), max(u[1][1].x << 1, u[1][2].y << 1));
                am = __reduce_max_sync(0xffffffffu, am >> 24);
                if (am) ex = min(max(4 - ((int)am - 127), -60), 60);
                s3 = s3 == 2 ? 0 : s3 + 1;
            }
        }
        if (wt == 96) publish(NSEG - 1, 0);
        __syncwarp();
        if (wq < 3) bar_sync(8, nq * 64 + 96);
        bar_arrive(5, 384);
        if (wt == 96) publish(NSEG, 1);
        __syncwarp();
        if (wq == 3) bar_sync(7, 288);
    }
    cluster_sync();
}

constexpr int H_STAGES = 4, H_STAGE = 57344;
constexpr int HELP_SMEM = H_STAGES * H_STAGE + 1024 + 256;
constexpr int NBLK = 11;
enum { T_EXIT = 0, T_G0, T_F, T_AB, T_AA, T_FS };
enum { C_HG = 0, C_HB = 32, C_GATE = 33, C_G0 = 48, C_AB = 64, C_HF = 96, C_AA = 128, C_HAA = 160, C_F = 256 };
constexpr int NG0 = NBLK * 9;
constexpr int NB_UNITS = NG0 + 16 * 11;
__host__ __device__ constexpr int aa_units(int seg) { return seg < 36 ? 3 : 6; }
constexpr unsigned AA_CTAS = 4, AA_CTAS2 = 8, AA_CTAS3 = 18;
constexpr int AA_B3 = 9, AA_LATE = 61;
constexpr int NFB = 13;
__host__ __device__ constexpr int f_row0(int m) { return m < 10 ? m * 192 : 1856 + (m - 10) * 64; }
__host__ __device__ constexpr int f_rows(int m) { return m < 9 ? 192 : (m < 10 ? 128 : 64); }
__host__ __device__ constexpr int f_blk(int seg) { return seg < 54 ? seg / 6 : (seg < 58 ? 9 : 10 + (seg - 58) / 2); }
__host__ __device__ constexpr int f_ntiles(int m) { return m < 10 ? 3 : 9; }

__device__ __forceinline__ void signal(unsigned* q, int lane, unsigned n = 1) {
    __syncwarp();
    if (lane == 0) asm volatile("red.release.gpu.global.add.u32 [%0],%1;" ::"l"(q), "r"(n) : "memory");
}

__device__ __forceinline__ int pos_q(int d) { return (d / 3) * 8 + d % 3; }
__device__ __forceinline__ int pos_k(int d) { return (d / 3) * 8 + d % 3 + (d < 6 ? 3 : 2); }
__device__ __forceinline__ int mpos_k(int d) { return (d / 3) * 5 + d % 3; }
__device__ __forceinline__ int mpos_v(int d) { return d < 2 ? 3 + d : (d < 4 ? 6 + d : 8 + d); }
__device__ __forceinline__ int pos_v(int d) { return d < 2 ? 6 + d : (d < 4 ? 12 + d : 16 + d); }

__device__ __forceinline__ uint4 quad_tr(const uint32_t* v, int t) {
    uint32_t a0 = (t & 1) ? v[0] : v[1], a1 = (t & 1) ? v[2] : v[3];
    a0 = __shfl_xor_sync(0xffffffffu, a0, 1); a1 = __shfl_xor_sync(0xffffffffu, a1, 1);
    const uint32_t b0 = (t & 1) ? a0 : v[0], b1 = (t & 1) ? v[1] : a0, b2 = (t & 1) ? a1 : v[2], b3 = (t & 1) ? v[3] : a1;
    uint32_t c0 = (t & 2) ? b0 : b2, c1 = (t & 2) ? b1 : b3;
    c0 = __shfl_xor_sync(0xffffffffu, c0, 2); c1 = __shfl_xor_sync(0xffffffffu, c1, 2);
    uint4 o;
    o.x = (t & 2) ? c0 : b0; o.y = (t & 2) ? c1 : b1; o.z = (t & 2) ? b2 : c0; o.w = (t & 2) ? b3 : c1;
    return o;
}
template <int BN>
__device__ __forceinline__ void store_tile(const float* acc, bf16* q, int pitch, int t) {
#pragma unroll
    for (int j = 0; j < BN / 32; j++) {
        uint32_t lo[4], hi[4];
#pragma unroll
        for (int i = 0; i < 4; i++) {
            lo[i] = pack2(acc[16 * j + 4 * i], acc[16 * j + 4 * i + 1]); hi[i] = pack2(acc[16 * j + 4 * i + 2], acc[16 * j + 4 * i + 3]);
        }
        *reinterpret_cast<uint4*>(q + j * 32 + t * 8) = quad_tr(lo, t);
        *reinterpret_cast<uint4*>(q + (size_t)8 * pitch + j * 32 + t * 8) = quad_tr(hi, t);
    }
}

template <int MT>
__device__ __forceinline__ void attnA_unit(uint32_t xr, uint32_t mr, int s, int h, int lane, uint32_t rel) {
    const int g = lane >> 2, t = lane & 3, l7 = lane & 7, l3 = lane >> 3;
    const float SC = 0.08838834764831845f * 1.4426950408889634f;
    constexpr int NT = MT ? 5 : 3;
    const uint32_t offA = (l7 + (l3 & 1) * 8) * 32 + (((l3 >> 1) ^ (l7 >> 2)) << 4);
    const uint32_t offB = (l7 + (l3 >> 1) * 8) * 32 + (((l3 & 1) ^ (l7 >> 2)) << 4);
    float sa[NT][4];
#pragma unroll
    for (int n = 0; n < NT; n++)
#pragma unroll
        for (int i = 0; i < 4; i++) sa[n][i] = 0.f;
#pragma unroll
    for (int hf = 0; hf < 2; hf++) {
        uint32_t qf[4][4], k0[4][4], k1[4][4], km[4][2];
#pragma unroll
        for (int i = 0; i < 4; i++) {
            const int d = hf * 4 + i;
            ldsm4(qf[i], xr + pos_q(d) * 1024 + MT * 512 + offA);
            ldsm2(km[i], mr + mpos_k(d) * 256 + (offB & 255));
            ldsm4(k0[i], xr + pos_k(d) * 1024 + offB);
            if (MT) ldsm4(k1[i], xr + pos_k(d) * 1024 + 512 + offB);
        }
#pragma unroll
        for (int i = 0; i < 4; i++) {
            mma16(sa[0], qf[i], km[i][0], km[i][1]);
            mma16(sa[1], qf[i], k0[i][0], k0[i][1]); mma16(sa[2], qf[i], k0[i][2], k0[i][3]);
            if (MT) { mma16(sa[NT - 2], qf[i], k1[i][0], k1[i][1]); mma16(sa[NT - 1], qf[i], k1[i][2], k1[i][3]); }
        }
    }
    if (2 * t > g) sa[NT - 2][0] = -INFINITY;
    if (2 * t + 1 > g) sa[NT - 2][1] = -INFINITY;
    sa[NT - 1][0] = -INFINITY; sa[NT - 1][1] = -INFINITY;
    if (2 * t > g) sa[NT - 1][2] = -INFINITY;
    if (2 * t + 1 > g) sa[NT - 1][3] = -INFINITY;
    float m0 = fmaxf(sa[0][0], sa[0][1]), m1 = fmaxf(sa[0][2], sa[0][3]);
#pragma unroll
    for (int n = 1; n < NT; n++) { m0 = fmaxf(m0, fmaxf(sa[n][0], sa[n][1])); m1 = fmaxf(m1, fmaxf(sa[n][2], sa[n][3])); }
    m0 = fmaxf(m0, __shfl_xor_sync(0xffffffffu, m0, 1)); m1 = fmaxf(m1, __shfl_xor_sync(0xffffffffu, m1, 1));
    m0 = fmaxf(m0, __shfl_xor_sync(0xffffffffu, m0, 2)); m1 = fmaxf(m1, __shfl_xor_sync(0xffffffffu, m1, 2));
    m0 *= SC; m1 *= SC;
    float s0 = 0.f, s1 = 0.f;
#pragma unroll
    for (int n = 0; n < NT; n++) {
        sa[n][0] = ex2(fmaf(sa[n][0], SC, -m0)); sa[n][1] = ex2(fmaf(sa[n][1], SC, -m0));
        sa[n][2] = ex2(fmaf(sa[n][2], SC, -m1)); sa[n][3] = ex2(fmaf(sa[n][3], SC, -m1));
        s0 += sa[n][0] + sa[n][1]; s1 += sa[n][2] + sa[n][3];
    }
    s0 += __shfl_xor_sync(0xffffffffu, s0, 1); s1 += __shfl_xor_sync(0xffffffffu, s1, 1);
    s0 += __shfl_xor_sync(0xffffffffu, s0, 2); s1 += __shfl_xor_sync(0xffffffffu, s1, 2);
    s0 = rcp_fast(s0); s1 = rcp_fast(s1);
    uint32_t pa[NT][2];
#pragma unroll
    for (int n = 0; n < NT; n++) { pa[n][0] = pack2(sa[n][0] * s0, sa[n][1] * s0); pa[n][1] = pack2(sa[n][2] * s1, sa[n][3] * s1); }
    const uint32_t p0[4] = {pa[1][0], pa[1][1], pa[2][0], pa[2][1]}, p1[4] = {pa[NT - 2][0], pa[NT - 2][1], pa[NT - 1][0], pa[NT - 1][1]};
    bf16* op = g_O + (size_t)(s * 32 + MT * 16 + g) * OK + h * DH + t * 8;
#pragma unroll
    for (int dh = 0; dh < 2; dh++) {
        uint32_t f0[4][4], f1[4][4], f2[4][2];
#pragma unroll
        for (int n2 = 0; n2 < 4; n2++) {
            const int d = dh * 4 + n2;
            ldsm4t(f0[n2], xr + pos_v(d) * 1024 + offA);
            if (MT) ldsm4t(f1[n2], xr + pos_v(d) * 1024 + 512 + offA);
            ldsm2t(f2[n2], mr + mpos_v(d) * 256 + (offB & 255));
        }
        uint32_t lo[8], hi[8];
#pragma unroll
        for (int n2 = 0; n2 < 4; n2++) {
            float oa0[4] = {0.f, 0.f, 0.f, 0.f}, oa1[4] = {0.f, 0.f, 0.f, 0.f};
            mma16(oa0, p0, f0[n2][0], f0[n2][1]); mma16(oa1, p0, f0[n2][2], f0[n2][3]);
            if (MT) { mma16(oa0, p1, f1[n2][0], f1[n2][1]); mma16(oa1, p1, f1[n2][2], f1[n2][3]); }
            mma8(oa0, pa[0][0], pa[0][1], f2[n2][0]); mma8(oa1, pa[0][0], pa[0][1], f2[n2][1]);
            lo[2 * n2] = pack2(oa0[0], oa0[1]); hi[2 * n2] = pack2(oa0[2], oa0[3]);
            lo[2 * n2 + 1] = pack2(oa1[0], oa1[1]); hi[2 * n2 + 1] = pack2(oa1[2], oa1[3]);
        }
        if (dh == 1) { __syncwarp(); if (lane == 0) mbar_arrive(rel); }
#pragma unroll
        for (int q = 0; q < 2; q++) {
            *reinterpret_cast<uint4*>(op + dh * 64 + q * 32) = quad_tr(lo + 4 * q, t);
            *reinterpret_cast<uint4*>(op + (size_t)8 * OK + dh * 64 + q * 32) = quad_tr(hi + 4 * q, t);
        }
    }
}

__device__ __forceinline__ void attnB_unit(uint32_t sQ, int q0, int hh, int wq, int lane, uint32_t rel) {
    const int g = lane >> 2, t = lane & 3, l7 = lane & 7, l3 = lane >> 3;
    const uint32_t sK = sQ + 128 * 48, sV = sK + 384 * 48;
    const int sh = (hh & 3) * 2;
    uint32_t qa[2][4], qb[2][2];
#pragma unroll
    for (int m = 0; m < 2; m++) {
        ldsm4(qa[m], sQ + (wq * 32 + m * 16 + l7 + (l3 & 1) * 8) * 48 + (l3 >> 1) * 16);
        ldsm2(qb[m], sQ + (wq * 32 + m * 16 + l7 + (l3 & 1) * 8) * 48 + 32);
        if (2 * t < sh) { qa[m][0] = 0u; qa[m][1] = 0u; }
        if (16 + 2 * t >= sh + 18) { qb[m][0] = 0u; qb[m][1] = 0u; }
    }
    const bool one0 = (sh == 6 && g == 0), one2 = (sh != 6 && g == 7);
    float gt[2][2];
#pragma unroll
    for (int m = 0; m < 2; m++) { gt[m][0] = __ldcg(g_gate + q0 + wq * 32 + m * 16 + g); gt[m][1] = __ldcg(g_gate + q0 + wq * 32 + m * 16 + g + 8); }
    const float SC = 0.23570226039551584f * 1.4426950408889634f;
    float o[2][3][4];
    float mx[2][2];
#pragma unroll
    for (int m = 0; m < 2; m++) {
        mx[m][0] = -INFINITY; mx[m][1] = -INFINITY;
#pragma unroll
        for (int n = 0; n < 3; n++)
#pragma unroll
            for (int i = 0; i < 4; i++) o[m][n][i] = 0.f;
    }
    const int tfirst = max(0, (256 - q0) / 16 - 2 * wq);
    const uint32_t kb0 = sK + (wq * 32 + l7 + (l3 >> 1) * 8) * 48 + (l3 & 1) * 16;
    const uint32_t kb1 = sK + (wq * 32 + l7 + (l3 & 1) * 8) * 48 + 32;
    const uint32_t vb0 = sV + (wq * 32 + l7 + (l3 & 1) * 8) * 48 + (l3 >> 1) * 16;
    const uint32_t vb1 = sV + (wq * 32 + l7 + (l3 & 1) * 8) * 48 + 32;
    constexpr int CH = 3;
#pragma unroll 1
    for (int c0 = 18 - CH; c0 >= 0; c0 -= CH) {
        if (c0 + CH <= tfirst) break;
        float sc[2][CH][2][4];
#pragma unroll
        for (int u = 0; u < CH; u++) {
            uint32_t kf[4], kg[2];
            const int ti = max(c0 + u, tfirst);
            ldsm4(kf, kb0 + ti * 768); ldsm2(kg, kb1 + ti * 768);
#pragma unroll
            for (int m = 0; m < 2; m++) {
#pragma unroll
                for (int n = 0; n < 2; n++) {
#pragma unroll
                    for (int i = 0; i < 4; i++) sc[m][u][n][i] = 0.f;
                    mma16(sc[m][u][n], qa[m], kf[2 * n], kf[2 * n + 1]);
                    mma8(sc[m][u][n], qb[m][0], qb[m][1], kg[n]);
                }
            }
        }
        if (c0 == 18 - CH || c0 == 0 || c0 < tfirst) {
#pragma unroll
            for (int m = 0; m < 2; m++)
#pragma unroll
                for (int u = 0; u < CH; u++)
#pragma unroll
                    for (int n = 0; n < 2; n++)
#pragma unroll
                        for (int i = 0; i < 4; i++) {
                            const int d = 256 + m * 16 + g + (i >> 1) * 8 - ((c0 + u) * 16 + n * 8 + 2 * t + (i & 1));
                            if (d < 0 || d >= 256 || c0 + u < tfirst) sc[m][u][n][i] = -INFINITY;
                        }
        }
        float bs[2][2];
#pragma unroll
        for (int m = 0; m < 2; m++) {
            float n0 = mx[m][0], n1 = mx[m][1];
#pragma unroll
            for (int u = 0; u < CH; u++)
#pragma unroll
                for (int n = 0; n < 2; n++) {
                    n0 = fmaxf(n0, fmaxf(sc[m][u][n][0], sc[m][u][n][1])); n1 = fmaxf(n1, fmaxf(sc[m][u][n][2], sc[m][u][n][3]));
                }
            n0 = fmaxf(n0, __shfl_xor_sync(0xffffffffu, n0, 1)); n1 = fmaxf(n1, __shfl_xor_sync(0xffffffffu, n1, 1));
            n0 = fmaxf(n0, __shfl_xor_sync(0xffffffffu, n0, 2)); n1 = fmaxf(n1, __shfl_xor_sync(0xffffffffu, n1, 2));
            const float f0 = ex2((mx[m][0] - n0) * SC), f1 = ex2((mx[m][1] - n1) * SC);
            mx[m][0] = n0; mx[m][1] = n1;
            bs[m][0] = n0 * SC; bs[m][1] = n1 * SC;
#pragma unroll
            for (int n = 0; n < 3; n++) { o[m][n][0] *= f0; o[m][n][1] *= f0; o[m][n][2] *= f1; o[m][n][3] *= f1; }
        }
#pragma unroll
        for (int u = 0; u < CH; u++) {
            uint32_t vf[4], vg[2];
            const int ti = max(c0 + u, tfirst);
            ldsm4t(vf, vb0 + ti * 768); ldsm2t(vg, vb1 + ti * 768);
            if (one0) { vf[0] = 0x3f803f80u; vf[1] = 0x3f803f80u; }
            if (one2) { vg[0] = 0x3f803f80u; vg[1] = 0x3f803f80u; }
#pragma unroll
            for (int m = 0; m < 2; m++) {
                if ((m == 0 && u == CH - 1 && c0 == 18 - CH) || (m == 1 && u == 0 && c0 == 0)) continue;
                uint32_t pa[4];
#pragma unroll
                for (int n = 0; n < 2; n++) {
                    pa[2 * n] = pack2(ex2(fmaf(sc[m][u][n][0], SC, -bs[m][0])), ex2(fmaf(sc[m][u][n][1], SC, -bs[m][0])));
                    pa[2 * n + 1] = pack2(ex2(fmaf(sc[m][u][n][2], SC, -bs[m][1])), ex2(fmaf(sc[m][u][n][3], SC, -bs[m][1])));
                }
                mma16(o[m][0], pa, vf[0], vf[1]); mma16(o[m][1], pa, vf[2], vf[3]); mma16(o[m][2], pa, vg[0], vg[1]);
            }
        }
    }
    __syncwarp();
    if (lane == 0) mbar_arrive(rel);
#pragma unroll
    for (int m = 0; m < 2; m++) {
        const int src = sh == 6 ? (lane & ~3) : (lane | 3);
        const float s0 = __shfl_sync(0xffffffffu, sh == 6 ? o[m][0][0] : o[m][2][1], src);
        const float s1 = __shfl_sync(0xffffffffu, sh == 6 ? o[m][0][2] : o[m][2][3], src);
        const int r = q0 + wq * 32 + m * 16 + g;
        const float i0 = (1.f - gt[m][0]) * rcp_fast(s0), i1 = (1.f - gt[m][1]) * rcp_fast(s1);
        bf16* op = g_O + (size_t)r * OK + HD + hh * BD + 2 * t - sh;
#pragma unroll
        for (int n = 0; n < 3; n++) {
            const int col = n * 8 + 2 * t;
            if (col >= sh && col < sh + 18) {
                *reinterpret_cast<uint32_t*>(op + n * 8) = pack2(o[m][n][0] * i0, o[m][n][1] * i0);
                *reinterpret_cast<uint32_t*>(op + n * 8 + 8 * OK) = pack2(o[m][n][2] * i1, o[m][n][3] * i1);
            }
        }
    }
}

template <int BN>
__device__ __forceinline__ void gemm_unit(int ty, const uint32_t* d, uint32_t sb, uint32_t bF, uint32_t bE, int& sg, int& ph,
                                          int warp, int lane, bf16* __restrict__ out) {
    const int wg = warp >> 2, wq = warp & 3, g = lane >> 2, t = lane & 3;
    auto release = [&](int q) { __syncwarp(); if (lane == 0) mbar_arrive(bE + 8 * q); };
    const int n0 = d[2] * BN, kb0 = d[3] & 255, kb1 = d[3] >> 8;
    const int rb = (ty == T_G0 ? d[1] * 192 : f_row0(d[1])) + (BN == 64 ? wq : warp) * 16, r0 = rb + g;
    float g0 = 1.f, g1 = 1.f;
    if (ty != T_G0) { g0 = __ldcg(g_gate + r0); g1 = __ldcg(g_gate + r0 + 8); }
    if (ty != T_G0 && f_split(d[1]) > 1) {
        const float* pa = g_acc + (size_t)rb * DM + n0 * 16 + lane * 32;
#pragma unroll
        for (int i = 0; i < BN / 64; i++) asm volatile("prefetch.global.L2 [%0];" ::"l"(pa + i * 1024));
    }
    float acc[BN / 2];
#pragma unroll
    for (int i = 0; i < BN / 2; i++) acc[i] = 0.f;
    int prev = -1;
    constexpr int KPS = BN == 64 ? 3 : 1;
    for (int kb = kb0; kb < kb1;) {
        if (kb > kb0) mbar_wait(bF + 8 * sg, ph);
        for (int j = 0; j < KPS && kb < kb1; j++, kb++) {
            const uint32_t a = sb + sg * H_STAGE + (BN == 64 ? j * 16384 : wg * 8192), b = BN == 64 ? a + 8192 : sb + sg * H_STAGE + 24576;
            if (kb == 64 && kb0 < 64) {
                wg_wait<0>();
#pragma unroll
                for (int i = 0; i < BN / 8; i++) { acc[4 * i] *= g0; acc[4 * i + 1] *= g0; acc[4 * i + 2] *= g1; acc[4 * i + 3] *= g1; }
            }
            const uint64_t da = desc_sw128(a, 16, 1024), db = desc_sw128(b, 8192, 1024);
            wg_fence();
#pragma unroll
            for (int k = 0; k < 4; k++) {
                if (BN == 192) wgmma_ss_n192(acc, da + (uint64_t)(k * 2), db + (uint64_t)(k * 128), 1);
                else wgmma_ss_n64(acc, da + (uint64_t)(k * 2), db + (uint64_t)(k * 128));
            }
            wg_commit();
            wg_wait<1>();
            if (j == 0 && prev >= 0) release(prev);
        }
        prev = sg;
        if (++sg == H_STAGES) { sg = 0; ph ^= 1; }
    }
    wg_wait<0>();
    if (ty == T_G0) {
        release(prev);
        store_tile<BN>(acc, g_qkvB + (size_t)r0 * (3 * DM) + n0, 3 * DM, t);
        signal(g_ctr + C_G0 + d[1], lane);
        return;
    }
    if (kb1 <= 64) {
#pragma unroll
        for (int i = 0; i < BN / 8; i++) { acc[4 * i] *= g0; acc[4 * i + 1] *= g0; acc[4 * i + 2] *= g1; acc[4 * i + 3] *= g1; }
    }
    const int ks = f_split(d[1]);
    bool fin = true;
    if (ks == 1) release(prev);
    if (ks > 1) {
        float4* ga = reinterpret_cast<float4*>(g_acc + (size_t)rb * DM + n0 * 16) + lane;
#pragma unroll
        for (int i = 0; i < BN / 8; i++) red4(reinterpret_cast<float*>(ga + i * 32), acc[4 * i], acc[4 * i + 1], acc[4 * i + 2], acc[4 * i + 3]);
        release(prev);
        unsigned old = 0;
        if (lane == 0) asm volatile("atom.acq_rel.gpu.global.add.u32 %0,[%1],1;" : "=r"(old) : "l"(g_ctr + C_F + (d[1] * 9 + d[2]) * 12 + warp) : "memory");
        old = __shfl_sync(0xffffffffu, old, 0);
        fin = (old == (unsigned)ks - 1);
        if (fin) {
#pragma unroll
            for (int i = 0; i < BN / 8; i++) {
                const float4 u = __ldcg(ga + i * 32);
                acc[4 * i] = u.x; acc[4 * i + 1] = u.y; acc[4 * i + 2] = u.z; acc[4 * i + 3] = u.w;
            }
        }
    }
    if (fin) store_tile<BN>(acc, out + (size_t)r0 * DM + n0, DM, t);
}

struct HelpMaps { CUtensorMap x, wqkv, O, O64, Wo, wo, qkv; };

__global__ void __launch_bounds__(512, 1) k_help(const __grid_constant__ HelpMaps tm, const bf16* __restrict__ x,
                                                  const bf16* __restrict__ gw, bf16* __restrict__ out) {
    extern __shared__ uint8_t smem_raw[];
    const uint32_t sb = (s2u(smem_raw) + 1023) & ~1023u;
    const uint32_t bF = sb + H_STAGES * H_STAGE, bE = bF + 8 * H_STAGES, dsc = bF + 128;
    const int tid = threadIdx.x, warp = __shfl_sync(0xffffffffu, tid >> 5, 0), lane = tid & 31;
    if (tid == 0) {
        for (int i = 0; i < H_STAGES; i++) { mbar_init(bF + 8 * i, 1); mbar_init(bE + 8 * i, 12); }
        asm volatile("fence.mbarrier_init.release.cluster;" ::: "memory");
    }
    __syncthreads();
    if (warp >= 12) {
        asm volatile("setmaxnreg.dec.sync.aligned.u32 56;");
        if (warp != 12) {
            while (true) {
                unsigned u = 0;
                if (lane == 0) u = atomicAdd(g_ctr + C_HG, 1);
                u = __shfl_sync(0xffffffffu, u, 0);
                if (u >= SEQ / 16) return;
#pragma unroll 1
                for (int r0 = u * 16; r0 < u * 16 + 16; r0 += 2) {
                    float a0 = 0.f, a1 = 0.f;
                    const __nv_bfloat162* xr = reinterpret_cast<const __nv_bfloat162*>(x + (size_t)r0 * DM);
#pragma unroll
                    for (int i = 0; i < 9; i++) {
                        const float2 b = __bfloat1622float2(reinterpret_cast<const __nv_bfloat162*>(gw)[lane + 32 * i]);
                        const float2 y = __bfloat1622float2(xr[lane + 32 * i]), z = __bfloat1622float2(xr[DM / 2 + lane + 32 * i]);
                        a0 += y.x * b.x + y.y * b.y; a1 += z.x * b.x + z.y * b.y;
                    }
#pragma unroll
                    for (int o = 16; o; o >>= 1) { a0 += __shfl_xor_sync(0xffffffffu, a0, o); a1 += __shfl_xor_sync(0xffffffffu, a1, o); }
                    if (lane < 2) g_gate[r0 + lane] = 1.f / (1.f + __expf(-(lane ? a1 : a0)));
                }
                signal(g_ctr + C_GATE, lane);
            }
        }
        int sg = 0, ph = 1;
        auto next = [&](int ty, int a, int b, int c2) {
            mbar_wait(bE + 8 * sg, ph);
            if (lane == 0) asm volatile("st.shared.v4.u32 [%0],{%1,%2,%3,%4};" ::"r"(dsc + 16 * sg), "r"(ty), "r"(a), "r"(b), "r"(c2) : "memory");
        };
        auto adv = [&]() { __syncwarp(); if (++sg == H_STAGES) { sg = 0; ph ^= 1; } };
        auto acquire = [&]() { asm volatile("fence.acq_rel.gpu; fence.proxy.async.global;" ::: "memory"); };
        auto ticket = [&](unsigned* q) { unsigned u = 0; if (lane == 0) u = atomicAdd(q, 1); return __shfl_sync(0xffffffffu, u, 0); };
        auto gemm = [&](int ty, int m, int n, int kb0, int kb1) {
            for (int kb = kb0; kb < kb1; kb++) {
                next(ty, m, n, kb0 | (kb1 << 8));
                if (lane == 0) {
                    const uint32_t a = sb + sg * H_STAGE, b = a + 24576, bar = bF + 8 * sg;
                    mbar_expect(bar, 49152);
                    tma2d(a, ty == T_G0 ? &tm.x : &tm.O, kb * 64, m * 192, bar);
                    const CUtensorMap* mb = ty == T_G0 ? &tm.wqkv : (kb >= 64 ? &tm.wo : &tm.Wo);
                    const int kr = (kb >= 64 ? kb - 64 : kb) * 64;
                    for (int j = 0; j < 3; j++) tma2d(b + j * 8192, mb, n * 192 + j * 64, kr, bar);
                }
                adv();
            }
        };
        bool bdone = false;
        int idle = 0, rr = 0;
        const int fl = min(lane, 9);
        constexpr int NLATE = (NSEG - AA_LATE) * 6, N10 = 9 * f_split(10), N11 = N10 + 9 * f_split(11), NSMALL = N11 + 9 * f_split(12);
        auto attn_a = [&](int as, int u) {
            const int per = (15 + aa_units(as)) / aa_units(as), ns = min(per, 16 - u * per), h0 = u * per * 2;
            for (int i = 0; i < ns; i++) {
                next(T_AA, as, h0 + 2 * i, rr | (i + 3 >= ns ? 4 : 0)); rr = rr == 2 ? 0 : rr + 1;
                if (lane == 0) {
                    const uint32_t a = sb + sg * H_STAGE, bar = bF + 8 * sg;
                    mbar_expect(bar, 57344);
                    bulk_load(a, reinterpret_cast<uint8_t*>(g_xr) + (size_t)(as * 32 + h0 + 2 * i) * 24576, 49152, bar);
                    bulk_load(a + 49152, reinterpret_cast<uint8_t*>(g_mr) + (size_t)(as * 32 + h0 + 2 * i) * 4096, 8192, bar);
                }
                adv();
            }
        };
        auto spin_ge = [&](const unsigned* q, unsigned target) {
            int it = 0;
            while (ld_relaxed1(q) < target) { __nanosleep(20); if (++it > (1 << 22)) __trap(); }
            acquire();
        };
        auto drain = [&]() {
            const int ls = sg == 0 ? H_STAGES - 1 : sg - 1;
            mbar_wait(bE + 8 * ls, sg == 0 ? ph : ph ^ 1);
        };
        while (true) {
            const unsigned tk0 = ld_relaxed1(g_ctr + C_HAA + lane), tk1 = ld_relaxed1(g_ctr + C_HAA + 32 + lane);
            const unsigned f0 = ld_relaxed1(g_flagA + lane), f1 = ld_relaxed1(g_flagA + 32 + lane);
            const unsigned tkf = ld_relaxed1(g_ctr + C_HF + min(lane, 11)), ca = ld_relaxed1(g_ctr + C_AA + fl);
            const unsigned cb0 = ld_relaxed1(g_ctr + C_AB + (lane > 9 ? 14 : f_row0(fl) / 128));
            const unsigned cb1 = ld_relaxed1(g_ctr + C_AB + (lane > 9 ? 15 : (f_row0(fl) + f_rows(fl) - 1) / 128));
            const bool e0 = tk0 < (unsigned)aa_units(lane), e1 = 32 + lane < AA_LATE && tk1 < (unsigned)aa_units(32 + lane);
            const unsigned a0 = __ballot_sync(0xffffffffu, e0 && f0 >= 192), a1 = __ballot_sync(0xffffffffu, e1 && f1 >= 192);
            const bool early_left = __any_sync(0xffffffffu, e0 || e1);
            const unsigned tl = __shfl_sync(0xffffffffu, tkf, 10), ts = __shfl_sync(0xffffffffu, tkf, 11);
            const bool fleft = lane < 10 && tkf < (unsigned)(3 * f_split(fl));
            const unsigned fl_m = __ballot_sync(0xffffffffu, fleft);
            const bool may = blockIdx.x >= (fl >= AA_B3 ? AA_CTAS3 : (fl >= 6 ? AA_CTAS2 : AA_CTAS)) || tl >= NLATE;
            const unsigned fr = __ballot_sync(0xffffffffu, fleft && ca >= (unsigned)(2 * f_rows(fl)) && cb0 >= 128 && cb1 >= 128 && may);
            if (a0 | a1) {
                const int as = a0 ? __ffs(a0) - 1 : 31 + __ffs(a1);
                const unsigned u = ticket(g_ctr + C_HAA + as);
                if (u < (unsigned)aa_units(as)) { acquire(); attn_a(as, u); continue; }
            }
            if (tl < NLATE && !early_left) {
                const bool ready = __shfl_sync(0xffffffffu, f1, (AA_LATE - 32 + tl / 6) & 31) >= 192;
                if (ready || (blockIdx.x < AA_CTAS3 && bdone)) {
                    drain();
                    const unsigned u = ticket(g_ctr + C_HF + 10);
                    if (u < NLATE) { spin_ge(g_flagA + AA_LATE + u / 6, 192); attn_a(AA_LATE + u / 6, u % 6); continue; }
                }
            }
            if (fr) {
                const int fm = __ffs(fr) - 1;
                const unsigned u = ticket(g_ctr + C_HF + fm);
                const int ks = f_split(fm);
                if (u < (unsigned)(3 * ks)) {
                    const int kp = u / 3;
                    acquire();
                    gemm(T_F, fm, u % 3, kp * 73 / ks, (kp + 1) * 73 / ks);
                    drain();
                    continue;
                }
            }
            if (ts < NSMALL && tl >= NLATE && fl_m == fr && __shfl_sync(0xffffffffu, cb0 >= 128 && cb1 >= 128, 10)) {
                const unsigned u = ticket(g_ctr + C_HF + 11);
                if (u < NSMALL) {
                    const int fm = u < N10 ? 10 : (u < N11 ? 11 : 12), v = u - (u < N10 ? 0 : (u < N11 ? N10 : N11));
                    const int nn = v % 9, kp = v / 9, kb0 = kp * 73 / f_split(fm), kb1 = (kp + 1) * 73 / f_split(fm);
                    for (int k0 = kb0; k0 < kb1; k0 += 3 * H_STAGES) {
                        const int sg0 = sg, k1 = min(kb1, k0 + 3 * H_STAGES);
                        for (int kb = k0; kb < k1; kb += 3) {
                            next(T_FS, fm, nn, kb0 | (kb1 << 8));
                            const int kk = kb + lane;
                            if (lane == 0) mbar_expect(bF + 8 * sg, min(3, k1 - kb) * 16384);
                            __syncwarp();
                            if (lane < 3 && kk < k1) {
                                tma2d(sb + sg * H_STAGE + lane * 16384 + 8192, kk >= 64 ? &tm.wo : &tm.Wo, nn * 64, (kk >= 64 ? kk - 64 : kk) * 64, bF + 8 * sg);
                                if (k0 > kb0) tma2d(sb + sg * H_STAGE + lane * 16384, &tm.O64, kk * 64, f_row0(fm), bF + 8 * sg);
                            }
                            adv();
                        }
                        if (k0 == kb0) {
                            spin_ge(g_ctr + C_AA + fm, 128);
                            if (k0 + lane < k1) {
                                const int q = (sg0 + lane / 3) % H_STAGES;
                                tma2d(sb + q * H_STAGE + (lane % 3) * 16384, &tm.O64, (k0 + lane) * 64, f_row0(fm), bF + 8 * q);
                            }
                            __syncwarp();
                        }
                    }
                    drain();
                    continue;
                }
            }
            if (a0 | a1 | fr) continue;
            if (!bdone) {
                const unsigned u = ticket(g_ctr + C_HB);
                if (u < NG0) {
                    gemm(T_G0, u / 9, u % 9, 0, 9);
                } else if (u < NB_UNITS) {
                    const int m = (u - NG0) / 11, h0 = ((u - NG0) % 11) * 3;
                    const int mm = min(max(0, m * 128 - 256) / 192 + lane, (m * 128 + 127) / 192);
                    const unsigned* q = lane == 31 ? g_ctr + C_GATE : g_ctr + C_G0 + mm;
                    int it = 0;
                    while (!__all_sync(0xffffffffu, ld_relaxed1(q) >= (lane == 31 ? 128u : 108u))) { __nanosleep(100); if (++it > (1 << 22)) __trap(); }
                    acquire();
                    for (int hh = h0; hh < min(h0 + 3, BH); hh++) {
                        next(T_AB, m, hh, rr); rr = rr == 2 ? 0 : rr + 1;
                        if (lane == 0) {
                            const uint32_t a = sb + sg * H_STAGE, bar = bF + 8 * sg;
                            const int col = (hh >> 2) * 72 + (hh & 3) * 16;
                            mbar_expect(bar, 7 * 6144);
                            tma2d(a, &tm.qkv, col, m * 128, bar);
                            for (int j = 0; j < 3; j++) {
                                tma2d(a + (1 + j) * 6144, &tm.qkv, DM + col, (m - 2 + j) * 128, bar);
                                tma2d(a + (4 + j) * 6144, &tm.qkv, 2 * DM + col, (m - 2 + j) * 128, bar);
                            }
                        }
                        adv();
                    }
                } else bdone = true;
                continue;
            }
            if (fl_m == 0 && ts >= NSMALL) break;
            __nanosleep(150);
            if (++idle > (1 << 22)) __trap();
        }
        next(T_EXIT, 0, 0, 0);
        if (lane == 0) mbar_arrive(bF + 8 * sg);
    } else {
        asm volatile("setmaxnreg.inc.sync.aligned.u32 152;");
        const int wg = warp >> 2, wq = warp & 3;
        int sg = 0, ph = 0, skip = 0;
        unsigned pend = 0;
        auto release = [&](int q) { __syncwarp(); if (lane == 0) mbar_arrive(bE + 8 * q); };
        auto adv = [&]() { if (++sg == H_STAGES) { sg = 0; ph ^= 1; } };
        while (true) {
            mbar_wait(bF + 8 * sg, ph);
            uint32_t d[4];
            lds128(d, dsc + 16 * sg);
            const int ty = d[0];
            if (ty == T_EXIT) break;
            if ((ty == T_G0 && wg == 2 && d[1] == NBLK - 1) || (ty == T_F && wg == 2 && d[1] == 9) || (ty == T_FS && wg != 0)) {
                release(sg); adv();
                if (ty == T_G0 && ++skip == 9) { skip = 0; signal(g_ctr + C_G0 + d[1], lane); }
            } else if (ty == T_G0 || ty == T_F) {
                gemm_unit<192>(ty, d, sb, bF, bE, sg, ph, warp, lane, out);
            } else if (ty == T_FS) {
                gemm_unit<64>(ty, d, sb, bF, bE, sg, ph, warp, lane, out);
                if (tid == 0 && d[1] == NFB - 1) g_sync[0] = 0;
            } else {
                if ((int)(d[3] & 3) == wg) {
                    if (ty == T_AA) {
                        const uint32_t xr = sb + sg * H_STAGE + (wq >> 1) * 24576, mr = sb + sg * H_STAGE + 49152 + (wq >> 1) * 4096;
                        if ((wq + wg) & 1) attnA_unit<1>(xr, mr, d[1], d[2] + (wq >> 1), lane, bE + 8 * sg);
                        else attnA_unit<0>(xr, mr, d[1], d[2] + (wq >> 1), lane, bE + 8 * sg);
                        pend++;
                        if (d[3] & 4) { signal(g_ctr + C_AA + f_blk(d[1]), lane, pend); pend = 0; }
                    } else {
                        attnB_unit(sb + sg * H_STAGE, d[1] * 128, d[2], wq, lane, bE + 8 * sg);
                        signal(g_ctr + C_AB + d[1], lane);
                    }
                } else {
                    release(sg);
                }
                adv();
            }
        }
    }
}

__device__ float g_fmem[(NSEG + 1) * 8 * DM];
__device__ bf16 g_fq[8 * HD];
__device__ __forceinline__ int tile_off(int row, int e) { return row * 16 + ((((e >> 3) ^ (row >> 2)) & 1) << 3) + (e & 7); }

__global__ void fb_init(const bf16* __restrict__ mem0) {
    const int i = blockIdx.x * blockDim.x + threadIdx.x;
    if (i < (NSEG + 1) * 8 * DM) g_fmem[i] = i < 8 * DM ? __bfloat162float(mem0[i]) : 0.f;
    if (i < SEQ * DM) g_acc[i] = 0.f;
    if (i < 1920) g_ctr[i] = 0;
    if (i < NSEG) g_flagA[i] = 192;
}
__global__ void fb_proj(const bf16* __restrict__ x, const bf16* __restrict__ Wq, const bf16* __restrict__ Wk, const bf16* __restrict__ Wv, int seg) {
    __shared__ float in[8][DM];
    for (int i = threadIdx.x; i < 8 * DM; i += blockDim.x)
        in[i / DM][i % DM] = seg >= 0 ? __bfloat162float(__float2bfloat16(g_fmem[seg * 8 * DM + i])) : __bfloat162float(x[(size_t)blockIdx.y * 8 * DM + i]);
    __syncthreads();
    const int col = blockIdx.x * blockDim.x + threadIdx.x, ty = col / HD, hc = col % HD, h = hc / DH, d = (hc % DH) >> 4, e = hc & 15;
    const bf16* W = (ty == 0 ? Wq : (ty == 1 ? Wk : Wv)) + hc;
    float a[8] = {0.f, 0.f, 0.f, 0.f, 0.f, 0.f, 0.f, 0.f};
    for (int k = 0; k < DM; k++) {
        const float w = __bfloat162float(W[(size_t)k * HD]);
#pragma unroll
        for (int r = 0; r < 8; r++) a[r] += in[r][k] * w;
    }
    for (int r = 0; r < 8; r++) {
        const bf16 v = __float2bfloat16(a[r]);
        if (seg < 0) {
            const int pos = ty == 0 ? pos_q(d) : (ty == 1 ? pos_k(d) : pos_v(d));
            reinterpret_cast<bf16*>(g_xr)[((size_t)((blockIdx.y >> 2) * 32 + h) * 24 + pos) * 512 + tile_off((blockIdx.y & 3) * 8 + r, e)] = v;
        } else if (ty == 0) g_fq[r * HD + hc] = v;
        else reinterpret_cast<bf16*>(g_mr)[((size_t)(seg * 32 + h) * 16 + (ty == 1 ? mpos_k(d) : mpos_v(d))) * 128 + tile_off(r, e)] = v;
    }
}
__global__ void fb_attn(const bf16* __restrict__ Wo, int seg) {
    __shared__ float sc[8][40], o[8][DH];
    const int h = blockIdx.x, tid = threadIdx.x;
    const bf16* xr = reinterpret_cast<const bf16*>(g_xr) + (size_t)(seg * 32 + h) * 24 * 512;
    const bf16* mr = reinterpret_cast<const bf16*>(g_mr) + (size_t)(seg * 32 + h) * 16 * 128;
    {
        const int r = tid / 40, j = tid % 40;
        float a = 0.f;
        for (int c = 0; c < DH; c++) {
            const bf16 kv = j < 8 ? mr[mpos_k(c >> 4) * 128 + tile_off(j, c & 15)] : xr[pos_k(c >> 4) * 512 + tile_off(j - 8, c & 15)];
            a += __bfloat162float(g_fq[r * HD + h * DH + c]) * __bfloat162float(kv);
        }
        sc[r][j] = a * 0.08838834764831845f;
    }
    __syncthreads();
    if (tid < 8) {
        float m = sc[tid][0], z = 0.f;
        for (int j = 1; j < 40; j++) m = fmaxf(m, sc[tid][j]);
        for (int j = 0; j < 40; j++) { sc[tid][j] = __expf(sc[tid][j] - m); z += sc[tid][j]; }
        for (int j = 0; j < 40; j++) sc[tid][j] /= z;
    }
    __syncthreads();
    for (int i = tid; i < 8 * DH; i += 320) {
        const int r = i / DH, c = i % DH;
        float a = 0.f;
        for (int j = 0; j < 40; j++)
            a += sc[r][j] * __bfloat162float(j < 8 ? mr[mpos_v(c >> 4) * 128 + tile_off(j, c & 15)] : xr[pos_v(c >> 4) * 512 + tile_off(j - 8, c & 15)]);
        o[r][c] = __bfloat162float(__float2bfloat16(a));
    }
    __syncthreads();
    for (int n = tid; n < DM; n += 320) {
        float a[8] = {0.f, 0.f, 0.f, 0.f, 0.f, 0.f, 0.f, 0.f};
        for (int c = 0; c < DH; c++) {
            const float w = __bfloat162float(Wo[(size_t)(h * DH + c) * DM + n]);
#pragma unroll
            for (int r = 0; r < 8; r++) a[r] += o[r][c] * w;
        }
        for (int r = 0; r < 8; r++) atomicAdd(g_fmem + ((seg + 1) * 8 + r) * DM + n, a[r]);
    }
}

typedef CUresult (*EncodeFn)(CUtensorMap*, CUtensorMapDataType, cuuint32_t, void*, const cuuint64_t*, const cuuint64_t*,
                             const cuuint32_t*, const cuuint32_t*, CUtensorMapInterleave, CUtensorMapSwizzle,
                             CUtensorMapL2promotion, CUtensorMapFloatOOBfill);

static void make_map(EncodeFn fn, CUtensorMap* m, const void* ptr, uint64_t cols, uint64_t rows, uint32_t bc, uint32_t br,
                     CUtensorMapSwizzle sw = CU_TENSOR_MAP_SWIZZLE_128B) {
    cuuint64_t dims[2] = {cols, rows};
    cuuint64_t strides[1] = {cols * 2};
    cuuint32_t box[2] = {bc, br};
    cuuint32_t es[2] = {1, 1};
    fn(m, CU_TENSOR_MAP_DATA_TYPE_BFLOAT16, 2, const_cast<void*>(ptr), dims, strides, box, es, CU_TENSOR_MAP_INTERLEAVE_NONE,
       sw, sw == CU_TENSOR_MAP_SWIZZLE_NONE ? CU_TENSOR_MAP_L2_PROMOTION_NONE : CU_TENSOR_MAP_L2_PROMOTION_L2_256B, CU_TENSOR_MAP_FLOAT_OOB_FILL_NONE);
}

extern "C" void kernel_launch(void* const* d_in, const int* in_sizes, int n_in, void* d_out, int out_size) {
    const bf16* x = (const bf16*)d_in[0];
    const bf16* mem0 = (const bf16*)d_in[1];
    const bf16* Wq = (const bf16*)d_in[2];
    const bf16* Wk = (const bf16*)d_in[3];
    const bf16* Wv = (const bf16*)d_in[4];
    const bf16* Wo = (const bf16*)d_in[5];
    const bf16* wqkv = (const bf16*)d_in[8];
    const bf16* wo = (const bf16*)d_in[9];
    const bf16* gw = (const bf16*)d_in[10];
    bf16* out = (bf16*)d_out;

    void* fp = nullptr;
    cudaDriverEntryPointQueryResult qr;
    cudaGetDriverEntryPoint("cuTensorMapEncodeTiled", &fp, cudaEnableDefault, &qr);
    EncodeFn enc = (EncodeFn)fp;
    void* pO = nullptr;
    cudaGetSymbolAddress(&pO, g_O);
    CUtensorMap tx32;
    HelpMaps hm;
    make_map(enc, &tx32, x, DM, SEQ, 64, 32);
    make_map(enc, &hm.x, x, DM, SEQ, 64, 192);
    make_map(enc, &hm.wqkv, wqkv, 3 * DM, DM, 64, 64);
    make_map(enc, &hm.O, pO, OK, SEQ, 64, 192);
    make_map(enc, &hm.O64, pO, OK, SEQ, 64, 64);
    make_map(enc, &hm.Wo, Wo, DM, HD, 64, 64);
    make_map(enc, &hm.wo, wo, DM, DM, 64, 64);
    void* pQ = nullptr;
    cudaGetSymbolAddress(&pQ, g_qkvB);
    make_map(enc, &hm.qkv, pQ, 3 * DM, SEQ, 24, 128, CU_TENSOR_MAP_SWIZZLE_NONE);
    cudaFuncSetAttribute(k_rec, cudaFuncAttributeMaxDynamicSharedMemorySize, REC_SMEM);
    cudaFuncSetAttribute(k_help, cudaFuncAttributeMaxDynamicSharedMemorySize, HELP_SMEM);

    cudaStream_t st = cudaStreamPerThread;
    bool fast;
    int nsm = 132;
    cudaDeviceGetAttribute(&nsm, cudaDevAttrMultiProcessorCount, 0);
    {
        RecParams p{mem0, Wq, Wk, Wv, Wo, x, wqkv, 830, 230};
        cudaLaunchConfig_t cfg = {};
        cfg.gridDim = dim3(96); cfg.blockDim = dim3(384); cfg.dynamicSmemBytes = REC_SMEM; cfg.stream = st;
        cudaLaunchAttribute at[1];
        at[0].id = cudaLaunchAttributeClusterDimension;
        at[0].val.clusterDim.x = 3; at[0].val.clusterDim.y = 1; at[0].val.clusterDim.z = 1;
        cfg.attrs = at; cfg.numAttrs = 1;
        int ncl = 0;
        fast = cudaOccupancyMaxActiveClusters(&ncl, k_rec, &cfg) == cudaSuccess && ncl >= NH;
        if (fast) {
            cudaLaunchKernelEx(&cfg, k_rec, tx32, p);
        } else {
            fb_init<<<SEQ * DM / 256, 256, 0, st>>>(mem0);
            fb_proj<<<dim3(3 * HD / 256, SEQ / 8), 256, 0, st>>>(x, Wq, Wk, Wv, -1);
            for (int s = 0; s < NSEG; s++) {
                fb_proj<<<dim3(3 * HD / 128, 1), 128, 0, st>>>(x, Wq, Wk, Wv, s);
                if (s + 1 < NSEG) fb_attn<<<NH, 320, 0, st>>>(Wo, s);
            }
        }
    }
    {
        cudaLaunchConfig_t cfg = {};
        cfg.gridDim = dim3(nsm); cfg.blockDim = dim3(512); cfg.dynamicSmemBytes = HELP_SMEM; cfg.stream = st;
        cudaLaunchAttribute at[1];
        at[0].id = cudaLaunchAttributeProgrammaticStreamSerialization;
        at[0].val.programmaticStreamSerializationAllowed = 1;
        cfg.attrs = at; cfg.numAttrs = fast ? 1 : 0;
        cudaLaunchKernelEx(&cfg, k_help, hm, x, gw, out);
    }
}
```

```cpp
#include <cuda_runtime.h>
#include <cuda_bf16.h>
#include <cuda_fp16.h>
#include <cuda.h>
#include <stdint.h>

typedef __nv_bfloat16 bf16;

constexpr int SEQ = 2048, DM = 576, NH = 32, DH = 128, NSEG = 64;
constexpr int HD = NH * DH;
constexpr int OK = HD + DM;
constexpr int BH = 32, BD = 18;

__device__ bf16 g_O[SEQ * OK];
__device__ bf16 g_qkvB[SEQ * 3 * DM];
__device__ float g_acc[SEQ * DM];
__device__ float g_gate[SEQ];
__device__ float g_red[8 * 192 * 256];
__device__ uint4 g_redh[8 * 96 * 72];
__device__ unsigned g_sync[32];
__device__ unsigned g_ctr[1920];

__device__ __forceinline__ uint32_t s2u(const void* p) { return (uint32_t)__cvta_generic_to_shared(p); }
__device__ __forceinline__ uint32_t mapa(uint32_t a, uint32_t r) {
    uint32_t o; asm volatile("mapa.shared::cluster.u32 %0,%1,%2;" : "=r"(o) : "r"(a), "r"(r)); return o;
}
__device__ __forceinline__ void mbar_init(uint32_t a, int c) {
    asm volatile("mbarrier.init.shared::cta.b64 [%0],%1;" ::"r"(a), "r"(c) : "memory");
}
__device__ __forceinline__ void mbar_expect(uint32_t a, int bytes) {
    asm volatile("mbarrier.arrive.expect_tx.shared::cta.b64 _,[%0],%1;" ::"r"(a), "r"(bytes) : "memory");
}
__device__ __forceinline__ void mbar_arrive(uint32_t a) {
    asm volatile("mbarrier.arrive.shared::cta.b64 _,[%0];" ::"r"(a) : "memory");
}
__device__ __forceinline__ void mbar_wait(uint32_t a, int ph) {
    asm volatile("{.reg .pred p; .reg .u32 n; mov.u32 n,0;\n"
                 "WL%=: mbarrier.try_wait.parity.shared::cta.b64 p,[%0],%1; @p bra.uni WD%=;\n"
                 "add.u32 n,n,1; setp.lt.u32 p,n,4194304; @p bra.uni WL%=; trap;\n"
                 "WD%=: }" ::"r"(a), "r"(ph) : "memory");
}
__device__ __forceinline__ void bar_sync(int id, int n) { asm volatile("bar.sync %0,%1;" ::"r"(id), "r"(n) : "memory"); }
__device__ __forceinline__ void bar_arrive(int id, int n) { asm volatile("bar.arrive %0,%1;" ::"r"(id), "r"(n) : "memory"); }
__device__ __forceinline__ void cluster_sync() {
    asm volatile("barrier.cluster.arrive.release.aligned; barrier.cluster.wait.acquire.aligned;" ::: "memory");
}
__device__ __forceinline__ void fence_async() { asm volatile("fence.proxy.async.shared::cta;" ::: "memory"); }
__device__ __forceinline__ void ldsm4(uint32_t* r, uint32_t a) {
    asm volatile("ldmatrix.sync.aligned.m8n8.x4.shared.b16 {%0,%1,%2,%3},[%4];"
                 : "=r"(r[0]), "=r"(r[1]), "=r"(r[2]), "=r"(r[3]) : "r"(a) : "memory");
}
__device__ __forceinline__ void ldsm4t(uint32_t* r, uint32_t a) {
    asm volatile("ldmatrix.sync.aligned.m8n8.x4.trans.shared.b16 {%0,%1,%2,%3},[%4];"
                 : "=r"(r[0]), "=r"(r[1]), "=r"(r[2]), "=r"(r[3]) : "r"(a) : "memory");
}
__device__ __forceinline__ void ldsm2(uint32_t* r, uint32_t a) {
    asm volatile("ldmatrix.sync.aligned.m8n8.x2.shared.b16 {%0,%1},[%2];" : "=r"(r[0]), "=r"(r[1]) : "r"(a) : "memory");
}
__device__ __forceinline__ void ldsm2t(uint32_t* r, uint32_t a) {
    asm volatile("ldmatrix.sync.aligned.m8n8.x2.trans.shared.b16 {%0,%1},[%2];" : "=r"(r[0]), "=r"(r[1]) : "r"(a) : "memory");
}
__device__ __forceinline__ void mma16(float* c, const uint32_t* a, uint32_t b0, uint32_t b1) {
    asm("mma.sync.aligned.m16n8k16.row.col.f32.bf16.bf16.f32 {%0,%1,%2,%3},{%4,%5,%6,%7},{%8,%9},{%0,%1,%2,%3};"
                 : "+f"(c[0]), "+f"(c[1]), "+f"(c[2]), "+f"(c[3])
                 : "r"(a[0]), "r"(a[1]), "r"(a[2]), "r"(a[3]), "r"(b0), "r"(b1));
}
__device__ __forceinline__ void mma16v(float* c, const uint32_t* a, uint32_t b0, uint32_t b1) {
    asm volatile("mma.sync.aligned.m16n8k16.row.col.f32.bf16.bf16.f32 {%0,%1,%2,%3},{%4,%5,%6,%7},{%8,%9},{%0,%1,%2,%3};"
                 : "+f"(c[0]), "+f"(c[1]), "+f"(c[2]), "+f"(c[3])
                 : "r"(a[0]), "r"(a[1]), "r"(a[2]), "r"(a[3]), "r"(b0), "r"(b1));
}
__device__ __forceinline__ void mma8(float* c, uint32_t a0, uint32_t a1, uint32_t b0) {
    asm("mma.sync.aligned.m16n8k8.row.col.f32.bf16.bf16.f32 {%0,%1,%2,%3},{%4,%5},{%6},{%0,%1,%2,%3};"
                 : "+f"(c[0]), "+f"(c[1]), "+f"(c[2]), "+f"(c[3]) : "r"(a0), "r"(a1), "r"(b0));
}
__device__ __forceinline__ uint32_t pack2(float lo, float hi) {
    uint32_t r; asm("cvt.rn.bf16x2.f32 %0,%1,%2;" : "=r"(r) : "f"(hi), "f"(lo)); return r;
}
__device__ __forceinline__ float ex2(float x) { float y; asm("ex2.approx.ftz.f32 %0,%1;" : "=f"(y) : "f"(x)); return y; }
__device__ __forceinline__ void sts32(uint32_t a, uint32_t v) { asm volatile("st.shared.u32 [%0],%1;" ::"r"(a), "r"(v) : "memory"); }
__device__ __forceinline__ void sts128(uint32_t a, const uint32_t* v) {
    asm volatile("st.shared.v4.u32 [%0],{%1,%2,%3,%4};" ::"r"(a), "r"(v[0]), "r"(v[1]), "r"(v[2]), "r"(v[3]) : "memory");
}
__device__ __forceinline__ void lds128(uint32_t* v, uint32_t a) {
    asm volatile("ld.shared.v4.u32 {%0,%1,%2,%3},[%4];" : "=r"(v[0]), "=r"(v[1]), "=r"(v[2]), "=r"(v[3]) : "r"(a) : "memory");
}
__device__ __forceinline__ float2 lds64f(uint32_t a) {
    float2 v; asm volatile("ld.shared.v2.f32 {%0,%1},[%2];" : "=f"(v.x), "=f"(v.y) : "r"(a) : "memory"); return v;
}
__device__ __forceinline__ void tma2d(uint32_t dst, const CUtensorMap* m, int c0, int c1, uint32_t bar) {
    asm volatile("cp.async.bulk.tensor.2d.shared::cluster.global.mbarrier::complete_tx::bytes [%0],[%1,{%3,%4}],[%2];"
                 ::"r"(dst), "l"(m), "r"(bar), "r"(c0), "r"(c1) : "memory");
}
__device__ __forceinline__ void tma2d_mc(uint32_t dst, const CUtensorMap* m, int c0, int c1, uint32_t bar, uint16_t mask) {
    asm volatile("cp.async.bulk.tensor.2d.shared::cluster.global.mbarrier::complete_tx::bytes.multicast::cluster [%0],[%1,{%3,%4}],[%2],%5;"
                 ::"r"(dst), "l"(m), "r"(bar), "r"(c0), "r"(c1), "h"(mask) : "memory");
}
__device__ __forceinline__ uint64_t desc_sw128(uint32_t addr, uint32_t lbo, uint32_t sbo) {
    return (uint64_t)((addr & 0x3FFFF) >> 4) | ((uint64_t)(lbo >> 4) << 16) | ((uint64_t)(sbo >> 4) << 32) | (1ull << 62);
}
__device__ __forceinline__ void wg_fence() { asm volatile("wgmma.fence.sync.aligned;" ::: "memory"); }
__device__ __forceinline__ void wg_commit() { asm volatile("wgmma.commit_group.sync.aligned;" ::: "memory"); }
template <int N> __device__ __forceinline__ void wg_wait() { asm volatile("wgmma.wait_group.sync.aligned %0;" ::"n"(N) : "memory"); }

__device__ __forceinline__ void wgmma_rs_n32(float* d, const uint32_t* a, uint32_t dlo, int acc) {
    asm volatile("{.reg .pred p; .reg .b64 dd; setp.ne.b32 p,%21,0; mov.b64 dd,{%20,0x40000040};\n"
                 "wgmma.mma_async.sync.aligned.m64n32k16.f32.bf16.bf16 "
                 "{%0,%1,%2,%3,%4,%5,%6,%7,%8,%9,%10,%11,%12,%13,%14,%15},{%16,%17,%18,%19},dd,p,1,1,0;}"
                 : "+f"(d[0]), "+f"(d[1]), "+f"(d[2]), "+f"(d[3]), "+f"(d[4]), "+f"(d[5]), "+f"(d[6]), "+f"(d[7]),
                   "+f"(d[8]), "+f"(d[9]), "+f"(d[10]), "+f"(d[11]), "+f"(d[12]), "+f"(d[13]), "+f"(d[14]), "+f"(d[15])
                 : "r"(a[0]), "r"(a[1]), "r"(a[2]), "r"(a[3]), "r"(dlo), "r"(acc));
}

__device__ __forceinline__ void wgmma_ss_n32(float* d, uint32_t alo, uint32_t dlo, int acc) {
    asm volatile("{.reg .pred p; .reg .b64 da,dd; setp.ne.b32 p,%18,0; mov.b64 da,{%16,0x00000008}; mov.b64 dd,{%17,0x40000040};\n"
                 "wgmma.mma_async.sync.aligned.m64n32k16.f32.bf16.bf16 "
                 "{%0,%1,%2,%3,%4,%5,%6,%7,%8,%9,%10,%11,%12,%13,%14,%15},da,dd,p,1,1,0,0;}"
                 : "+f"(d[0]), "+f"(d[1]), "+f"(d[2]), "+f"(d[3]), "+f"(d[4]), "+f"(d[5]), "+f"(d[6]), "+f"(d[7]),
                   "+f"(d[8]), "+f"(d[9]), "+f"(d[10]), "+f"(d[11]), "+f"(d[12]), "+f"(d[13]), "+f"(d[14]), "+f"(d[15])
                 : "r"(alo), "r"(dlo), "r"(acc));
}

#define R8(b) "+f"(d[b]), "+f"(d[b + 1]), "+f"(d[b + 2]), "+f"(d[b + 3]), "+f"(d[b + 4]), "+f"(d[b + 5]), "+f"(d[b + 6]), "+f"(d[b + 7])
__device__ __forceinline__ void wgmma_ss_n192(float* d, uint64_t da, uint64_t db, int acc) {
    asm volatile("{.reg .pred p; setp.ne.b32 p,%98,0;\n"
                 "wgmma.mma_async.sync.aligned.m64n192k16.f32.bf16.bf16 "
                 "{%0,%1,%2,%3,%4,%5,%6,%7,%8,%9,%10,%11,%12,%13,%14,%15,%16,%17,%18,%19,%20,%21,%22,%23,"
                 "%24,%25,%26,%27,%28,%29,%30,%31,%32,%33,%34,%35,%36,%37,%38,%39,%40,%41,%42,%43,%44,%45,%46,%47,"
                 "%48,%49,%50,%51,%52,%53,%54,%55,%56,%57,%58,%59,%60,%61,%62,%63,%64,%65,%66,%67,%68,%69,%70,%71,"
                 "%72,%73,%74,%75,%76,%77,%78,%79,%80,%81,%82,%83,%84,%85,%86,%87,%88,%89,%90,%91,%92,%93,%94,%95},"
                 "%96,%97,p,1,1,0,1;}"
                 : R8(0), R8(8), R8(16), R8(24), R8(32), R8(40), R8(48), R8(56), R8(64), R8(72), R8(80), R8(88)
                 : "l"(da), "l"(db), "r"(acc));
}

__device__ __forceinline__ void wgmma_ss_n96(float* d, uint64_t da, uint64_t db) {
    asm volatile("wgmma.mma_async.sync.aligned.m64n96k16.f32.bf16.bf16 "
                 "{%0,%1,%2,%3,%4,%5,%6,%7,%8,%9,%10,%11,%12,%13,%14,%15,%16,%17,%18,%19,%20,%21,%22,%23,"
                 "%24,%25,%26,%27,%28,%29,%30,%31,%32,%33,%34,%35,%36,%37,%38,%39,%40,%41,%42,%43,%44,%45,%46,%47},%48,%49,1,1,1,0,1;"
                 : R8(0), R8(8), R8(16), R8(24), R8(32), R8(40) : "l"(da), "l"(db));
}
__device__ __forceinline__ void wgmma_ss_n64(float* d, uint64_t da, uint64_t db) {
    asm volatile("wgmma.mma_async.sync.aligned.m64n64k16.f32.bf16.bf16 "
                 "{%0,%1,%2,%3,%4,%5,%6,%7,%8,%9,%10,%11,%12,%13,%14,%15,%16,%17,%18,%19,%20,%21,%22,%23,"
                 "%24,%25,%26,%27,%28,%29,%30,%31},%32,%33,1,1,1,0,1;"
                 : R8(0), R8(8), R8(16), R8(24) : "l"(da), "l"(db));
}

constexpr int NSS = 1;
constexpr int QCH = 4, QD = 4;
constexpr int WRES = 2, WO_PRE2 = 3, WO_PRE3 = 4;
constexpr int MP = 1168;
constexpr int XT = 36864;
constexpr int XR_STAGE = 14 * 1024;
constexpr int MR_STAGE = 14 * 256;
constexpr int SM_X = 0;
constexpr int SM_XR = 2 * XT;
constexpr int SM_MR = SM_XR + 3 * XR_STAGE;
constexpr int SM_MEM = SM_MR + 3 * MR_STAGE;
constexpr int SM_SC = SM_MEM + 8 * MP;
constexpr int SM_OB = SM_SC + 3 * 1536;
constexpr int SM_ZERO = SM_OB + 2048;
constexpr int SM_WO = SM_ZERO + 512;
constexpr int SM_WS = SM_WO + 49152;
constexpr int SM_BAR = SM_WS + NSS * 4096;
constexpr int REC_SMEM = SM_BAR + 128 + 1024;

__device__ uint4 g_xr[NSEG * NH * 24 * 64];
__device__ uint4 g_mr[NSEG * NH * 16 * 16];
__device__ unsigned g_flagA[NSEG];

constexpr unsigned long long FSP = 0x111123564ull;
__host__ __device__ constexpr int f_split(int m) { return m < 3 ? 1 : (int)((FSP >> (4 * (11 - m))) & 15); }
constexpr int F_FIRST_SPLIT = f_split(3) > 1 ? 3 : (f_split(4) > 1 ? 4 : (f_split(5) > 1 ? 5 : (f_split(6) > 1 ? 6 : 7)));
struct RecParams {
    const bf16* mem0; const bf16* Wq; const bf16* Wk; const bf16* Wv; const bf16* Wo; const bf16* x; const bf16* wqkv;
    int d0, dv;
};

__device__ __forceinline__ float* red_line(int s, int line) { return g_red + ((s >> 3) * 192 + line) * 256 + (s & 7) * 32; }

#define PIN(x) asm volatile("" : "+r"(x))
#define PINL(x) asm volatile("" : "+l"(x))
__device__ __forceinline__ float4 ld_relaxed4(const float* q) {
    float4 v;
    asm volatile("ld.relaxed.gpu.global.v4.f32 {%0,%1,%2,%3},[%4];" : "=f"(v.x), "=f"(v.y), "=f"(v.z), "=f"(v.w) : "l"(q) : "memory");
    return v;
}
__device__ __forceinline__ unsigned ld_acq(const unsigned* q) {
    unsigned v; asm volatile("ld.acquire.gpu.global.u32 %0,[%1];" : "=r"(v) : "l"(q) : "memory"); return v;
}
__device__ __forceinline__ unsigned ld_relaxed1(const unsigned* q) {
    unsigned v; asm volatile("ld.relaxed.gpu.global.u32 %0,[%1];" : "=r"(v) : "l"(q) : "memory"); return v;
}
__device__ __forceinline__ uint4 ld_relaxed4u(const uint4* q) {
    uint4 v;
    asm volatile("ld.relaxed.gpu.global.v4.u32 {%0,%1,%2,%3},[%4];" : "=r"(v.x), "=r"(v.y), "=r"(v.z), "=r"(v.w) : "l"(q) : "memory");
    return v;
}
__device__ __forceinline__ void reld_relaxed4u(uint4& v, const uint4* q) {
    asm volatile("{.reg .pred p; .reg .b32 q; and.b32 q,%3,0xffff; setp.ne.u32 p,q,0x5000;\n"
                 "@p ld.relaxed.gpu.global.v4.u32 {%0,%1,%2,%3},[%4];}"
                 : "+r"(v.x), "+r"(v.y), "+r"(v.z), "+r"(v.w) : "l"(q) : "memory");
}
__device__ __forceinline__ uint32_t packh2(float lo, float hi) {
    uint32_t r; asm("cvt.rn.f16x2.f32 %0,%1,%2;" : "=r"(r) : "f"(hi), "f"(lo)); return r;
}
__device__ __forceinline__ float maxn(float a, float b) {
    float r; asm("max.NaN.f32 %0,%1,%2;" : "=f"(r) : "f"(fabsf(a)), "f"(fabsf(b))); return r;
}
__device__ __forceinline__ void redh4(uint4* q, const float* v, uint32_t tag) {
    asm volatile("red.relaxed.gpu.global.add.noftz.v4.f16x2 [%0],{%1,%2,%3,%4};"
                 ::"l"(q), "r"(packh2(v[0], v[1])), "r"(packh2(v[2], v[3])), "r"(packh2(v[4], v[5])), "r"(tag) : "memory");
}
__device__ __forceinline__ void red4(float* q, float a, float b, float c2, float d) {
    asm volatile("red.relaxed.gpu.global.add.v4.f32 [%0],{%1,%2,%3,%4};" ::"l"(q), "f"(a), "f"(b), "f"(c2), "f"(d) : "memory");
}
__device__ __forceinline__ unsigned clk32() { return (unsigned)clock64(); }
__device__ __forceinline__ void spin_until(unsigned tl) {
    asm volatile("{.reg .pred p; .reg .u64 c; .reg .u32 lo,hi; .reg .s32 d;\n"
                 "SP%=: mov.u64 c,%%clock64; mov.b64 {lo,hi},c; sub.s32 d,lo,%0; setp.lt.s32 p,d,0; @p bra.uni SP%=;}" ::"r"(tl) : "memory");
}
__device__ __forceinline__ float rcp_fast(float x) { float y; asm("rcp.approx.ftz.f32 %0,%1;" : "=f"(y) : "f"(x)); return y; }
__device__ __forceinline__ void bulk_store(void* gdst, uint32_t src, int bytes) {
    asm volatile("cp.async.bulk.global.shared::cta.bulk_group [%0],[%1],%2;" ::"l"(gdst), "r"(src), "r"(bytes) : "memory");
}
__device__ __forceinline__ void bulk_load(uint32_t dst, const void* gsrc, int bytes, uint32_t bar) {
    asm volatile("cp.async.bulk.shared::cluster.global.mbarrier::complete_tx::bytes [%0],[%1],%2,[%3];"
                 ::"r"(dst), "l"(gsrc), "r"(bytes), "r"(bar) : "memory");
}
__device__ __forceinline__ void bulk_s2s(uint32_t rdst, uint32_t src, int bytes, uint32_t rbar) {
    asm volatile("cp.async.bulk.shared::cluster.shared::cta.mbarrier::complete_tx::bytes [%0],[%1],%2,[%3];"
                 ::"r"(rdst), "r"(src), "r"(bytes), "r"(rbar) : "memory");
}
__device__ __forceinline__ void stas4(uint32_t rdst, uint32_t a, uint32_t b, uint32_t c2, uint32_t d, uint32_t rbar) {
    asm volatile("st.async.weak.shared::cluster.mbarrier::complete_tx::bytes.v4.b32 [%0],{%1,%2,%3,%4},[%5];"
                 ::"r"(rdst), "r"(a), "r"(b), "r"(c2), "r"(d), "r"(rbar) : "memory");
}
__device__ __forceinline__ void stas2(uint32_t rdst, uint32_t a, uint32_t b, uint32_t rbar) {
    asm volatile("st.async.weak.shared::cluster.mbarrier::complete_tx::bytes.v2.b32 [%0],{%1,%2},[%3];"
                 ::"r"(rdst), "r"(a), "r"(b), "r"(rbar) : "memory");
}
__device__ __forceinline__ float4 lds128f(uint32_t a) {
    float4 v; asm volatile("ld.shared.v4.f32 {%0,%1,%2,%3},[%4];" : "=f"(v.x), "=f"(v.y), "=f"(v.z), "=f"(v.w) : "r"(a) : "memory"); return v;
}

__device__ __forceinline__ void flag_seg(int seg) {
    asm volatile("cp.async.bulk.wait_group 0;" ::: "memory");
    asm volatile("red.relaxed.gpu.global.add.u32 [%0],1;" ::"l"(g_flagA + seg) : "memory");
}

__global__ void __launch_bounds__(384, 1) k_rec(const __grid_constant__ CUtensorMap tmx, const RecParams p) {
    extern __shared__ uint8_t smem_raw[];
    const uint32_t sb = (s2u(smem_raw) + 1023) & ~1023u;
    const int tid = threadIdx.x, warp = __shfl_sync(0xffffffffu, tid >> 5, 0), lane = tid & 31, g = lane >> 2, t = lane & 3;
    const int l7 = lane & 7, l3 = lane >> 3;
    const int c = blockIdx.x % 3, h = blockIdx.x / 3;
    const int nq = c < 2 ? 3 : 2, nv = 8 - 2 * nq, v0 = 2 * c;
    const uint32_t bXF = sb + SM_BAR, bVX = bXF + 16, bS = bVX + 16, bV = bS + 8;
    const uint32_t peer1 = (c + 1) % 3, peer2 = (c + 2) % 3;
    auto vslot = [](int r, int d) { return (r < 2 ? 6 : 4) + ((d - 2 * r) & 7); };

    if (tid == 1) asm volatile("cp.async.bulk.prefetch.L2.global [%0],20736;" ::"l"(reinterpret_cast<const uint8_t*>(p.wqkv) + (size_t)blockIdx.x * 20736) : "memory");
    if (tid == 33) asm volatile("cp.async.bulk.prefetch.L2.global [%0],9216;" ::"l"(reinterpret_cast<const uint8_t*>(p.x) + (size_t)blockIdx.x * 9216) : "memory");
    __syncthreads();
    if (lane == 0) {
        const int wsel = warp / 3;
        const bf16* W = wsel == 0 ? p.Wq : (wsel == 1 ? p.Wk : (wsel == 2 ? p.Wv : p.Wo));
        asm volatile("cp.async.bulk.prefetch.L2.global [%0],16384;" ::"l"(reinterpret_cast<const uint8_t*>(W) + (size_t)((warp % 3) * 96 + blockIdx.x) * 16384) : "memory");
    }
    if (tid == 0) {
        for (int i = 0; i < 2; i++) { mbar_init(bXF + 8 * i, 1); mbar_init(bVX + 8 * i, 1); }
        mbar_init(bS, 4); mbar_init(bV, nv + 1);
        asm volatile("fence.mbarrier_init.release.cluster;" ::: "memory");
        for (int i = 0; i < 2; i++) { mbar_expect(bXF + 8 * i, XT); mbar_expect(bVX + 8 * i, (8 - nv) * 1024); }
        mbar_expect(bS, 2560); mbar_expect(bV, (8 - nv) * 256);
    }
    if (blockIdx.x == 0) {
        for (int i = tid; i < 1920; i += 384) g_ctr[i] = 0;
        if (tid < NSEG) g_flagA[tid] = 0;
        __threadfence();
    }
    __syncthreads();
    asm volatile("griddepcontrol.launch_dependents;" ::: "memory");
    cluster_sync();

    if (warp < 8) {
        asm volatile("setmaxnreg.inc.sync.aligned.u32 %0;" ::"n"(184));
        if (tid == 0) {
            for (int sl = 0; sl < 2; sl++)
                for (int j = 0; j < 3; j++)
                    tma2d_mc(sb + SM_X + sl * XT + (c * 3 + j) * 4096, &tmx, (c * 3 + j) * 64, sl * 32, bXF + 8 * sl, 7);
        }
        const bool isv = warp >= 2 * nq;
        const int slot = warp;
        uint32_t w[36][4];
        {
            const int dt = isv ? v0 + warp - 2 * nq : 3 * c + (warp >= nq ? warp - nq : warp);
            const bf16* W = (isv ? p.Wv : (warp >= nq ? p.Wk : p.Wq)) + h * DH + dt * 16 + 2 * g + (size_t)(2 * t) * HD;
#pragma unroll
            for (int k = 0; k < 36; k++) {
                const uint32_t* q = reinterpret_cast<const uint32_t*>(W + (size_t)k * 16 * HD);
                w[k][0] = __ldg(q); w[k][1] = __ldg(q + HD / 2); w[k][2] = __ldg(q + 4 * HD); w[k][3] = __ldg(q + 4 * HD + HD / 2);
            }
#pragma unroll
            for (int k = 0; k < 36; k++) {
                uint32_t a = w[k][0], b = w[k][1], d = w[k][2], e = w[k][3];
                w[k][0] = __byte_perm(a, b, 0x5410); w[k][1] = __byte_perm(a, b, 0x7632);
                w[k][2] = __byte_perm(d, e, 0x5410); w[k][3] = __byte_perm(d, e, 0x7632);
            }
#pragma unroll
            for (int k = 0; k < NSS; k++) {
                const uint32_t a = sb + SM_WS + k * 4096 + (warp >> 2) * 2048 + (warp & 3) * 256 + lane * 4;
                sts32(a, w[36 - NSS + k][0]); sts32(a + 128, w[36 - NSS + k][1]);
                sts32(a + 1024, w[36 - NSS + k][2]); sts32(a + 1152, w[36 - NSS + k][3]);
            }
            fence_async();
            bar_sync(9, 256);
        }
        const uint32_t wsd = (((sb + SM_WS + (warp >> 2) * 2048) & 0x3FFFF) >> 4) | (64u << 16);
        const uint32_t woff = 2 * t * 32 + (((g >> 2) ^ (t >> 1)) << 4) + (g & 3) * 4;

        float d[16];
        auto xdesc = [&](int sl) { return __shfl_sync(0xffffffffu, (((sb + SM_X + sl * XT) & 0x3FFFF) >> 4) | 0x10000u, 0); };
        auto filler = [&](uint32_t xd, int stg) {
            wg_fence();
#pragma unroll
            for (int k = 36 - NSS; k < 36; k++) wgmma_ss_n32(d, wsd + (k - 36 + NSS) * 256, xd + ((k >> 2) * 256 + (k & 3) * 2), k > 36 - NSS);
#pragma unroll
            for (int k = 0; k < 36 - NSS; k++) wgmma_rs_n32(d, w[k], xd + ((k >> 2) * 256 + (k & 3) * 2), 1);
            wg_commit();
            wg_wait<0>();
            const uint32_t dst = sb + SM_XR + stg * XR_STAGE + slot * 1024 + woff;
#pragma unroll
            for (int j = 0; j < 4; j++) {
                sts32(dst + j * 256, pack2(d[4 * j], d[4 * j + 2]));
                sts32(dst + j * 256 + 32, pack2(d[4 * j + 1], d[4 * j + 3]));
            }
        };
        auto fwd_v = [&](int sl, int stg) {
            const uint32_t base = sb + SM_XR + stg * XR_STAGE;
            bulk_s2s(mapa(base + vslot(peer1, v0) * 1024, peer1), base + 2 * nq * 1024, nv * 1024, mapa(bVX + 8 * sl, peer1));
            bulk_s2s(mapa(base + vslot(peer2, v0) * 1024, peer2), base + 2 * nq * 1024, nv * 1024, mapa(bVX + 8 * sl, peer2));
        };

        mbar_wait(bXF, 0);
        filler(xdesc(0), 0);
        fence_async();
        bar_sync(9, 256);
        if (tid == 32) fwd_v(0, 0);
        __syncwarp();
        mbar_wait(bXF + 8, 0);
        filler(xdesc(1), 1);
        bar_sync(9, 256);
        if (tid == 0) { mbar_expect(bXF, XT); mbar_expect(bXF + 8, XT); }
        cluster_sync();
        if (tid == 0) {
            for (int sl = 0; sl < 2; sl++)
                for (int j = 0; j < 3; j++)
                    tma2d_mc(sb + SM_X + sl * XT + (c * 3 + j) * 4096, &tmx, (c * 3 + j) * 64, (2 + sl) * 32, bXF + 8 * sl, 7);
        }
        __syncwarp();
        uint32_t mema = sb + SM_MEM + l7 * MP + l3 * 16;
        const uint32_t xpeer = (g & 2) ? peer2 : peer1;
        const uint32_t rdst0 = mapa(sb + SM_MR + vslot(xpeer, v0 + warp - 2 * nq) * 256 + (2 * t + (g & 1)) * 32 + (((g >> 2) ^ (t >> 1)) << 4), xpeer);
        uint32_t rbar = mapa(bV, xpeer);
        int s3 = 0;
        for (int s = 0; s < NSEG; s++) {
            const int st = s & 1, s3n = s3 == 2 ? 0 : s3 + 1, s3p = s3 == 0 ? 2 : s3 - 1;
            uint32_t rdst = rdst0 + s3 * MR_STAGE;
            uint32_t ldst = sb + SM_MR + s3 * MR_STAGE + slot * 256 + woff;
            PIN(rdst); PIN(rbar); PIN(ldst); PIN(mema);
            float a[QCH][4];
#pragma unroll
            for (int i = 0; i < QCH; i++) { a[i][0] = 0.f; a[i][1] = 0.f; a[i][2] = 0.f; a[i][3] = 0.f; }
            uint32_t wx[NSS][4];
#pragma unroll
            for (int k = 0; k < NSS; k++)
                ldsm4(wx[k], sb + SM_WS + k * 4096 + (warp >> 2) * 2048 + (warp & 3) * 256 + (l3 >> 1) * 1024 + (l3 & 1) * 128 + l7 * 16);
            bar_sync(1, 384);
            if (isv) spin_until(clk32() + p.dv);
            uint32_t bf[18][4];
#pragma unroll
            for (int ii = 0; ii < QD; ii++) ldsm4(bf[17 - ii], mema + (17 - ii) * 64);
#pragma unroll
            for (int ii = 0; ii < 18; ii++) {
                const int i = 17 - ii;
                mma16v(a[(2 * i) % QCH], 2 * i >= 36 - NSS ? wx[2 * i - 36 + NSS] : w[2 * i], bf[i][0], bf[i][1]);
                mma16v(a[(2 * i + 1) % QCH], 2 * i + 1 >= 36 - NSS ? wx[2 * i + 1 - 36 + NSS] : w[2 * i + 1], bf[i][2], bf[i][3]);
                if (i - QD >= 0) ldsm4(bf[i - QD], mema + (i - QD) * 64);
            }
#pragma unroll
            for (int i = 0; i < 4; i++) {
                a[0][i] = (a[2][i] + a[3][i]) + (a[0][i] + a[1][i]);
            }
            const uint32_t w0 = pack2(a[0][0], a[0][2]), w1 = pack2(a[0][1], a[0][3]);
            sts32(ldst, w0); sts32(ldst + 32, w1);
            if (!isv) bar_arrive(8, nq * 64 + 96);
            if (isv && s + 1 < NSEG) {
                uint32_t snd = (g & 1) ? w0 : w1, keep = (g & 1) ? w1 : w0;
                uint32_t rcv = __shfl_xor_sync(0xffffffffu, snd, 4);
                uint32_t lo = (g & 1) ? rcv : keep, hi = (g & 1) ? keep : rcv;
                uint32_t olo = __shfl_xor_sync(0xffffffffu, lo, 8), ohi = __shfl_xor_sync(0xffffffffu, hi, 8);
                stas4(rdst, (g & 2) ? olo : lo, (g & 2) ? ohi : hi, (g & 2) ? lo : olo, (g & 2) ? hi : ohi, rbar);
                __syncwarp();
                if (lane == 0) mbar_arrive(bV);
            }
            const uint32_t xd = xdesc(st);
            if (s + 2 < NSEG) {
                mbar_wait(bXF + 8 * st, ((s + 2) >> 1) & 1);
            }
            fence_async();
            bar_arrive(7, 288);
            if (warp == 1) bar_sync(6, 256); else bar_arrive(6, 256);
            if (warp < 2) {
                if (s + 1 < NSEG) { mbar_wait(bS, st); mbar_wait(bV, st); }
                if (lane == 0) {
                    if (warp == 0) {
                        if (s >= 1 && s + 3 < NSEG) {
                            mbar_expect(bXF + 8 * (st ^ 1), XT);
                            for (int j = 0; j < 3; j++)
                                tma2d_mc(sb + SM_X + (st ^ 1) * XT + (c * 3 + j) * 4096, &tmx, (c * 3 + j) * 64, (s + 3) * 32, bXF + 8 * (st ^ 1), 7);
                        }
                    } else {
                        if (s >= 1) flag_seg(s - 1);
                        bulk_store(reinterpret_cast<uint8_t*>(g_mr) + (size_t)(s * 32 + h) * 4096 + c * 1280,
                                   sb + SM_MR + s3 * MR_STAGE + nq * 256, (8 - nq) * 256);
                        asm volatile("cp.async.bulk.commit_group;" ::: "memory");
                        if (s + 2 < NSEG) fwd_v(st ^ 1, s3n);
                    }
                }
                __syncwarp();
            }
            if (s + 2 < NSEG) {
                bar_sync(5, 384);
                filler(xd, s3p);
            } else {
                bar_sync(5, 384);
            }
            s3 = s3n;
        }
        if (tid == 32) flag_seg(NSEG - 1);
    } else {
        asm volatile("setmaxnreg.dec.sync.aligned.u32 %0;" ::"n"(136));
        const int wq = warp - 8, wt = tid - 256;
        uint32_t woa = sb + SM_WO + wt * 16;
        uint32_t am0 = 0;
        {
            for (int i = wt; i < 576; i += 128) g_redh[blockIdx.x * 576 + i] = make_uint4(0u, 0u, 0u, 0u);
            float4* z = reinterpret_cast<float4*>(g_red) + blockIdx.x * 1024;
            for (int i = wt; i < 1024; i += 128) z[i] = make_float4(0.f, 0.f, 0.f, 0.f);
            constexpr int ZN = (SEQ - F_FIRST_SPLIT * 192) * (DM / 4) / 96;
            float4* za = reinterpret_cast<float4*>(g_acc + F_FIRST_SPLIT * 192 * DM) + blockIdx.x * ZN;
            for (int i = wt; i < ZN; i += 128) za[i] = make_float4(0.f, 0.f, 0.f, 0.f);
            __threadfence();
            bar_sync(4, 128);
            if (wt == 0) asm volatile("red.relaxed.gpu.global.add.u32 [%0],1;" ::"l"(g_sync) : "memory");
        }
        {
            const bf16* W = p.Wo + (size_t)(h * DH + 2 * t) * DM + c * 192 + wq * 16 + 2 * g;
            uint32_t wo[24][4];
#pragma unroll
            for (int k = 0; k < 24; k++) {
                const uint32_t* q = reinterpret_cast<const uint32_t*>(W + (k & 7) * 16 * DM + (k >> 3) * 64);
                wo[k][0] = __ldg(q); wo[k][1] = __ldg(q + DM / 2);
                wo[k][2] = __ldg(q + 4 * DM); wo[k][3] = __ldg(q + 4 * DM + DM / 2);
            }
#pragma unroll
            for (int k = 0; k < 24; k++) {
                uint32_t a = wo[k][0], b = wo[k][1], d = wo[k][2], e = wo[k][3];
                wo[k][0] = __byte_perm(a, b, 0x5410); wo[k][1] = __byte_perm(a, b, 0x7632);
                wo[k][2] = __byte_perm(d, e, 0x5410); wo[k][3] = __byte_perm(d, e, 0x7632);
                sts128(woa + k * 2048, wo[k]);
            }
            sts32(sb + SM_ZERO + wt * 4, 0u);
            for (int i = wt; i < 8 * 72; i += 128) {
                const int r = i / 72, cc = i % 72;
                uint4 v = __ldg(reinterpret_cast<const uint4*>(p.mem0 + r * DM) + cc);
                am0 = __vmaxu2(__vmaxu2(am0, __vmaxu2(v.x & 0x7fff7fffu, v.y & 0x7fff7fffu)), __vmaxu2(v.z & 0x7fff7fffu, v.w & 0x7fff7fffu));
                asm volatile("st.shared.v4.u32 [%0],{%1,%2,%3,%4};" ::"r"(sb + SM_MEM + r * MP + cc * 16), "r"(v.x), "r"(v.y), "r"(v.z), "r"(v.w) : "memory");
            }
        }
        cluster_sync();
        bar_arrive(1, 384);
        uint32_t wa[8][4], wb[8][4], wc[WRES + 1][4];
#pragma unroll
        for (int k = 0; k < 8; k++) lds128(wa[k], woa + k * 2048);
#pragma unroll
        for (int k = 0; k < 8; k++) lds128(wb[k], woa + (8 + k) * 2048);
#pragma unroll
        for (int k = 0; k < WRES; k++) lds128(wc[k], woa + (16 + k) * 2048);

        int ex;
        {
            const uint32_t m = __reduce_max_sync(0xffffffffu, max(am0 & 0xffffu, am0 >> 16));
            ex = m ? min(max(4 - ((int)(m >> 7) - 127), -60), 60) : 0;
        }
        const float SC = 0.08838834764831845f * 1.4426950408889634f;
        uint32_t L16 = lane * 16;
        uint32_t AB = (l3 >> 1) * 256 + l7 * 32 + (((l3 & 1) ^ (l7 >> 2)) << 4);
        uint32_t AA = (l3 & 1) * 256 + l7 * 32 + (((l3 >> 1) ^ (l7 >> 2)) << 4);
        const uint32_t scu = sb + SM_SC + c * 1536 + (wq == 0 ? 1024 : (wq - 1) * 512);
        const uint32_t sc1 = mapa(scu, peer1), sc2 = mapa(scu, peer2), sb1 = mapa(bS, peer1), sb2 = mapa(bS, peer2);
        const uint32_t wou = sb + SM_WO + wq * 512;
        const int vs = vslot(c, 2 * wq);
        auto publish = [&](int xs, int stg) {
            if (xs >= 1) flag_seg(xs - 1);
            if (xs < NSEG) {
                bulk_store(reinterpret_cast<uint8_t*>(g_xr) + (size_t)(xs * 96 + blockIdx.x) * 8192, sb + SM_XR + stg * XR_STAGE, 8192);
                asm volatile("cp.async.bulk.commit_group;" ::: "memory");
            }
        };
        int s3 = 0;
        for (int s = 0; s + 1 < NSEG; s++) {
            const int st = s & 1;
            const uint32_t xr = sb + SM_XR + s3 * XR_STAGE, mr = sb + SM_MR + s3 * MR_STAGE;
            PIN(L16); PIN(AB); PIN(AA);
            if (wq < 3) {
                uint32_t kf[3][4], q0[4], q1[4];
                float ca[4] = {0.f, 0.f, 0.f, 0.f}, cb[4] = {0.f, 0.f, 0.f, 0.f}, cc[4] = {0.f, 0.f, 0.f, 0.f};
                if (wq) {
                    const uint32_t ka = xr + nq * 1024 + (wq - 1) * 512 + AB;
                    ldsm4(kf[0], ka); ldsm4(kf[1], ka + 1024); ldsm4(kf[2], nq == 3 ? ka + 2048 : sb + SM_ZERO + AB);
                    uint32_t da1 = sc1 + L16, da2 = sc2 + L16, qa = mr + AA;
                    PIN(da1); PIN(da2); PIN(qa);
                    bar_sync(8, nq * 64 + 96);
                    ldsm4(q0, qa); ldsm4(q1, qa + 512);
                    float da[4] = {0.f, 0.f, 0.f, 0.f}, db[4] = {0.f, 0.f, 0.f, 0.f}, dc[4] = {0.f, 0.f, 0.f, 0.f};
                    mma16(ca, q0, kf[0][0], kf[0][1]); mma16(da, q0, kf[0][2], kf[0][3]);
                    mma16(cb, q0, kf[1][0], kf[1][1]); mma16(db, q0, kf[1][2], kf[1][3]);
                    mma16(cc, q1, kf[2][0], kf[2][1]); mma16(dc, q1, kf[2][2], kf[2][3]);
                    const uint32_t rr[4] = {__float_as_uint((ca[0] + cb[2]) + cc[0]), __float_as_uint((ca[1] + cb[3]) + cc[1]),
                                            __float_as_uint((da[0] + db[2]) + dc[0]), __float_as_uint((da[1] + db[3]) + dc[1])};
                    stas4(da1, rr[0], rr[1], rr[2], rr[3], sb1); stas4(da2, rr[0], rr[1], rr[2], rr[3], sb2);
                    sts128(scu + L16, rr);
                } else {
                    uint32_t da1 = sc1 + (L16 >> 1), da2 = sc2 + (L16 >> 1), qa = mr + AA, ka = mr + nq * 256 + AB;
                    uint32_t kb = nq == 3 ? ka + 512 : sb + SM_ZERO + AB;
                    PIN(da1); PIN(da2); PIN(qa); PIN(ka); PIN(kb);
                    bar_sync(8, nq * 64 + 96);
                    ldsm4(q0, qa); ldsm4(kf[0], ka); ldsm4(q1, qa + 512); ldsm2(kf[1], kb);
                    mma16(ca, q0, kf[0][0], kf[0][1]); mma16(cb, q0, kf[0][2], kf[0][3]); mma16(cc, q1, kf[1][0], kf[1][1]);
                    const uint32_t r0 = __float_as_uint((ca[0] + cb[2]) + cc[0]), r1 = __float_as_uint((ca[1] + cb[3]) + cc[1]);
                    stas2(da1, r0, r1, sb1); stas2(da2, r0, r1, sb2);
                    asm volatile("st.shared.v2.u32 [%0],{%1,%2};" ::"r"(scu + (L16 >> 1)), "r"(r0), "r"(r1) : "memory");
                }
                __syncwarp();
                if (L16 == 0) mbar_arrive(bS);
            } else {
                if (lane == 0) {
                    if (s >= 1 && s + 4 < NSEG)
                        asm volatile("prefetch.global.L2 [%0];" ::"l"(g_redh + (((s + 3) >> 3) * 96 + blockIdx.x) * 72 + ((s + 3) & 7) * 8));
                    publish(s, s3);
                    if (s == 0) {
                        int it = 0;
                        while (ld_acq(g_sync) < 96) { if (++it > (1 << 22)) __trap(); }
                    }
                }
                __syncwarp();
            }
            uint32_t va[2][2][4], vb[4];
            mbar_wait(bVX + 8 * st, (s >> 1) & 1);
            const uint32_t v0a = xr + vs * 1024 + AB;
            ldsm4t(va[0][0], v0a); ldsm4t(va[1][0], v0a + 1024);
            uint4* rl = g_redh + (((s >> 3) * 96 + c * 32 + wq * 4) * 9 + (s & 7)) * 8 + (L16 >> 7) * 72 + ((L16 >> 4) & 7);
            PINL(rl);
            mbar_wait(bS, s & 1);
            float4 sa, sbb; float2 sm2;
            {
                const uint32_t scl = sb + SM_SC + L16;
                const float4 a0 = lds128f(scl), a1 = lds128f(scl + 1536), a2 = lds128f(scl + 3072);
                const float4 b0 = lds128f(scl + 512), b1 = lds128f(scl + 2048), b2 = lds128f(scl + 3584);
                const uint32_t scm = sb + SM_SC + 1024 + (L16 >> 1);
                const float2 m0 = lds64f(scm), m1 = lds64f(scm + 1536), m2 = lds64f(scm + 3072);
                sa.x = a0.x + a1.x + a2.x; sa.y = a0.y + a1.y + a2.y; sa.z = a0.z + a1.z + a2.z; sa.w = a0.w + a1.w + a2.w;
                sbb.x = b0.x + b1.x + b2.x; sbb.y = b0.y + b1.y + b2.y; sbb.z = b0.z + b1.z + b2.z; sbb.w = b0.w + b1.w + b2.w;
                sm2.x = m0.x + m1.x + m2.x; sm2.y = m0.y + m1.y + m2.y;
            }
            float mx = fmaxf(fmaxf(fmaxf(sa.x, sa.y), fmaxf(sa.z, sa.w)), fmaxf(fmaxf(sbb.x, sbb.y), fmaxf(sbb.z, sbb.w)));
            mx = fmaxf(mx, fmaxf(sm2.x, sm2.y));
            {
                const float x1 = __shfl_xor_sync(0xffffffffu, mx, 1), x2 = __shfl_xor_sync(0xffffffffu, mx, 2), x3 = __shfl_xor_sync(0xffffffffu, mx, 3);
                ldsm4t(va[0][1], v0a + 512); ldsm4t(va[1][1], v0a + 1024 + 512);
                mbar_wait(bV, s & 1);
                ldsm4t(vb, mr + vs * 256 + AB);
                mx = fmaxf(fmaxf(mx, x1), fmaxf(x2, x3));
            }
            uint32_t ws[8][4];
#pragma unroll
            for (int k = WRES; k < WRES + WO_PRE2 && k < 8; k++) lds128(ws[k], wou + L16 + (16 + k) * 2048);
            const float mo = mx * SC;
            const float e0 = ex2(fmaf(sa.x, SC, -mo)), e1 = ex2(fmaf(sa.y, SC, -mo)), e2 = ex2(fmaf(sa.z, SC, -mo)), e3 = ex2(fmaf(sa.w, SC, -mo));
            float o0[4] = {0.f, 0.f, 0.f, 0.f}, o1[4] = {0.f, 0.f, 0.f, 0.f}, o2[4] = {0.f, 0.f, 0.f, 0.f};
            const uint32_t one = 0x3f803f80u, one4[4] = {one, one, one, one};
            { const uint32_t p0 = pack2(e0, e1), p1 = pack2(e2, e3); mma16(o0, va[0][0], p0, p1); mma16(o1, va[1][0], p0, p1); mma16(o2, one4, p0, p1); }
            const float e4 = ex2(fmaf(sbb.x, SC, -mo)), e5 = ex2(fmaf(sbb.y, SC, -mo)), e6 = ex2(fmaf(sbb.z, SC, -mo)), e7 = ex2(fmaf(sbb.w, SC, -mo));
            { const uint32_t p0 = pack2(e4, e5), p1 = pack2(e6, e7); mma16(o0, va[0][1], p0, p1); mma16(o1, va[1][1], p0, p1); mma16(o2, one4, p0, p1); }
            const float e8 = ex2(fmaf(sm2.x, SC, -mo)), e9 = ex2(fmaf(sm2.y, SC, -mo));
            { const uint32_t p0 = pack2(e8, e9); mma8(o0, vb[0], vb[1], p0); mma8(o1, vb[2], vb[3], p0); mma8(o2, one, one, p0); }
            {
                const uint32_t oa = sb + SM_OB + wq * 512 + (L16 >> 2);
                sts32(oa, pack2(o0[0], o0[1])); sts32(oa + 128, pack2(o0[2], o0[3]));
                sts32(oa + 256, pack2(o1[0], o1[1])); sts32(oa + 384, pack2(o1[2], o1[3]));
            }
            bar_sync(4, 128);
            uint32_t ob[4][4];
#pragma unroll
            for (int j = 0; j < 4; j++) ldsm4t(ob[j], sb + SM_OB + L16 + 512 * j);
            const float fs = __int_as_float((127 + ex) << 23);
            const float i0 = rcp_fast(o2[0]) * fs, i1 = rcp_fast(o2[1]) * fs;
            float v[12];
            {
                float r[6][4];
#pragma unroll
                for (int i = 0; i < 6; i++) { r[i][0] = 0.f; r[i][1] = 0.f; r[i][2] = 0.f; r[i][3] = 0.f; }
#pragma unroll
                for (int k = WRES + WO_PRE2; k < WRES + WO_PRE3 && k < 8; k++) lds128(ws[k], wou + L16 + (16 + k) * 2048);
#pragma unroll
                for (int i = 0; i < 8; i++) {
                    mma16v(r[(i & 1) ? 3 : 0], wa[i], ob[i >> 1][(i & 1) * 2], ob[i >> 1][(i & 1) * 2 + 1]);
                    mma16v(r[(i & 1) ? 4 : 1], wb[i], ob[i >> 1][(i & 1) * 2], ob[i >> 1][(i & 1) * 2 + 1]);
                    mma16v(r[(i & 1) ? 5 : 2], i < WRES ? wc[i] : ws[i], ob[i >> 1][(i & 1) * 2], ob[i >> 1][(i & 1) * 2 + 1]);
                    if (i + WRES + WO_PRE3 < 8) lds128(ws[i + WRES + WO_PRE3], wou + L16 + (16 + i + WRES + WO_PRE3) * 2048);
                }
#pragma unroll
                for (int j = 0; j < 3; j++) {
                    { r[j][0] += r[3 + j][0]; r[j][1] += r[3 + j][1]; r[j][2] += r[3 + j][2]; r[j][3] += r[3 + j][3]; }
                    v[4 * j] = r[j][0] * i0; v[4 * j + 1] = r[j][2] * i0; v[4 * j + 2] = r[j][1] * i1; v[4 * j + 3] = r[j][3] * i1;
                }
                const float m8 = maxn(maxn(maxn(v[0], v[1]), maxn(v[2], v[3])), maxn(maxn(v[4], v[5]), maxn(v[6], v[7])));
                const float m = maxn(maxn(maxn(v[8], v[9]), maxn(v[10], v[11])), m8);
                const uint32_t tag = m < 1024.f ? (m >= 0.0625f ? 0x3c003c00u : 0x00003c00u) : 0x54003c00u;
                redh4(rl, v, tag);
                bar_arrive(5, 384);
                redh4(rl + 16 * 72, v + 6, tag);
            }
            const unsigned tred = clk32();
            if (wq == 3) bar_sync(7, 288);
            if (wt == 0) {
                if (s + 2 < NSEG) { mbar_expect(bS, 2560); mbar_expect(bV, (8 - nv) * 256); }
                if (s + 3 < NSEG) mbar_expect(bVX + 8 * st, (8 - nv) * 1024);
            }
            {
                const uint4* gl = rl - c * 32 * 72;
                uint32_t ma = sb + SM_MEM + wq * 32 + ((L16 >> 4) & 3) * (2 * MP) + (L16 >> 6) * 4;
                PINL(gl); PIN(ma);
                unsigned tl = tred + p.d0;
                spin_until(tl);
                uint4 u[2][3];
#pragma unroll
                for (int j = 0; j < 2; j++)
#pragma unroll
                    for (int cc = 0; cc < 3; cc++) u[j][cc] = ld_relaxed4u(gl + (cc * 32 + j * 16) * 72);
                const uint32_t rebias = (uint32_t)(112 - ex) * 0x00800080u;
                int it = 0;
                auto cvt = [&](uint32_t x) { return ((((x + 0x00030004u) & 0x7ff87ff8u) >> 3) + rebias) | (x & 0x80008000u); };
                auto put = [&](int j, int cc) {
                    sts32(ma + (cc * 192 + ((3 * j) >> 1) * 64) * 2 + ((3 * j) & 1) * MP, u[j][cc].x);
                    sts32(ma + (cc * 192 + ((3 * j + 1) >> 1) * 64) * 2 + ((3 * j + 1) & 1) * MP, u[j][cc].y);
                    sts32(ma + (cc * 192 + ((3 * j + 2) >> 1) * 64) * 2 + ((3 * j + 2) & 1) * MP, u[j][cc].z);
                };
#pragma unroll
                for (int j = 0; j < 2; j++)
#pragma unroll
                    for (int cc = 0; cc < 3; cc++) {
                        u[j][cc].x = cvt(u[j][cc].x); u[j][cc].y = cvt(u[j][cc].y); u[j][cc].z = cvt(u[j][cc].z);
                        put(j, cc);
                    }
                {
                    const uint32_t bad = ((u[0][0].w ^ 0x5000u) | (u[0][1].w ^ 0x5000u) | (u[0][2].w ^ 0x5000u)) |
                                         ((u[1][0].w ^ 0x5000u) | (u[1][1].w ^ 0x5000u) | (u[1][2].w ^ 0x5000u));
                    const uint32_t tg = max(max(max(u[0][0].w, u[0][1].w), u[0][2].w), max(max(u[1][0].w, u[1][1].w), u[1][2].w));
                    const bool clean = __all_sync(0xffffffffu, (bad & 0xffffu) == 0 && tg < 0x54000000u);
                    const bool big = __any_sync(0xffffffffu, tg >= 0x3c000000u);
                    if (__builtin_expect(!(clean && big), 0)) {
                        while (true) {
                            bool ok = true;
#pragma unroll
                            for (int j = 0; j < 2; j++)
#pragma unroll
                                for (int cc = 0; cc < 3; cc++) ok = ok && (u[j][cc].w & 0xffffu) == 0x5000u;
                            if (__all_sync(0xffffffffu, ok)) break;
                            if (++it > (1 << 20)) __trap();
                            uint32_t redo = 0;
#pragma unroll
                            for (int j = 0; j < 2; j++)
#pragma unroll
                                for (int cc = 0; cc < 3; cc++) {
                                    if ((u[j][cc].w & 0xffffu) != 0x5000u) redo |= 1u << (j * 3 + cc);
                                    reld_relaxed4u(u[j][cc], gl + (cc * 32 + j * 16) * 72);
                                }
#pragma unroll
                            for (int j = 0; j < 2; j++)
#pragma unroll
                                for (int cc = 0; cc < 3; cc++) {
                                    const bool rd = (redo >> (j * 3 + cc)) & 1;
                                    u[j][cc].x = rd ? cvt(u[j][cc].x) : u[j][cc].x; u[j][cc].y = rd ? cvt(u[j][cc].y) : u[j][cc].y;
                                    u[j][cc].z = rd ? cvt(u[j][cc].z) : u[j][cc].z;
                                    put(j, cc);
                                }
                        }
                        const uint32_t t2 = max(max(max(u[0][0].w, u[0][1].w), u[0][2].w), max(max(u[1][0].w, u[1][1].w), u[1][2].w));
                        if (__any_sync(0xffffffffu, t2 >= 0x54000000u) || !__any_sync(0xffffffffu, t2 >= 0x3c000000u)) {
                            const float isc = __int_as_float((127 - ex) << 23);
                            float* fl = red_line(s, c * 64 + wq * 4 + (L16 >> 7)) + ((L16 >> 2) & 28);
#pragma unroll
                            for (int i = 0; i < 4; i++) red4(fl + i * 16 * 256, v[3 * i], v[3 * i + 1], v[3 * i + 2], 1.0f);
                            const float* fg = fl - c * 64 * 256;
#pragma unroll
                            for (int j = 0; j < 2; j++)
#pragma unroll
                                for (int cc = 0; cc < 3; cc++) {
                                    float4 a, b;
                                    while (true) {
                                        a = ld_relaxed4(fg + (cc * 64 + j * 32) * 256); b = ld_relaxed4(fg + (cc * 64 + j * 32 + 16) * 256);
                                        if (__all_sync(0xffffffffu, a.w == 32.f && b.w == 32.f)) break;
                                        if (++it > (1 << 20)) __trap();
                                    }
                                    u[j][cc].x = pack2(a.x * isc, a.y * isc); u[j][cc].y = pack2(a.z * isc, b.x * isc); u[j][cc].z = pack2(b.y * isc, b.z * isc);
                                    put(j, cc);
                                }
                        }
                    }
                }
                bar_arrive(1, 384);
                uint32_t am = max(max(u[0][0].x << 1, u[0][1].y << 1), max(u[1][1].x << 1, u[1][2].y << 1));
                am = __reduce_max_sync(0xffffffffu, am >> 24);
                if (am) ex = min(max(4 - ((int)am - 127), -60), 60);
                s3 = s3 == 2 ? 0 : s3 + 1;
            }
        }
        if (wt == 96) publish(NSEG - 1, 0);
        __syncwarp();
        if (wq < 3) bar_sync(8, nq * 64 + 96);
        bar_arrive(5, 384);
        if (wt == 96) publish(NSEG, 1);
        __syncwarp();
        if (wq == 3) bar_sync(7, 288);
    }
    cluster_sync();
}

constexpr int H_STAGES = 4, H_STAGE = 57344;
constexpr int HELP_SMEM = H_STAGES * H_STAGE + 1024 + 256;
constexpr int NBLK = 11;
enum { T_EXIT = 0, T_G0, T_F, T_AB, T_AA, T_FS, T_FN };
enum { C_HG = 0, C_HB = 32, C_GATE = 33, C_G0 = 48, C_AB = 64, C_HF = 96, C_AA = 128, C_HAA = 160, C_F = 256 };
constexpr int NG0 = NBLK * 9;
constexpr int ABH = 6;
constexpr int ABT = (BH + ABH - 1) / ABH;
constexpr int NB_UNITS = NG0 + 16 * ABT;
__host__ __device__ constexpr int aa_units(int seg) { return seg < 36 ? 3 : 6; }
constexpr unsigned AA_CTAS = 4;
constexpr unsigned AA_CTAS2 = 8;
constexpr unsigned AA_CTAS3 = 18;
constexpr int AA_B3 = 9;
constexpr int AA_LATE = 61;
constexpr int NFB = 12;
__host__ __device__ constexpr int f_row0(int m) { return m < 10 ? m * 192 : 1856 + (m - 10) * 128; }
__host__ __device__ constexpr int f_rows(int m) { return m < 9 ? 192 : (m < 11 ? 128 : 64); }
__host__ __device__ constexpr int f_blk(int seg) { return seg < 54 ? seg / 6 : 9 + (seg - 54) / 4; }
constexpr int DRAIN_B = 5;
constexpr int SPIN_NS = 20;
constexpr int FNM = 0x7f0;
__host__ __device__ constexpr int f_ntiles(int m) { return m < 11 ? (((FNM >> m) & 1) ? 6 : 3) : 9; }

__device__ __forceinline__ void signal(unsigned* q, int lane, unsigned n = 1) {
    asm volatile("fence.proxy.async.global;" ::: "memory");
    __syncwarp();
    if (lane == 0) asm volatile("red.release.gpu.global.add.u32 [%0],%1;" ::"l"(q), "r"(n) : "memory");
}

__device__ __forceinline__ int pos_q(int d) { return (d / 3) * 8 + d % 3; }
__device__ __forceinline__ int pos_k(int d) { return (d / 3) * 8 + d % 3 + (d < 6 ? 3 : 2); }
__device__ __forceinline__ int mpos_k(int d) { return (d / 3) * 5 + d % 3; }
__device__ __forceinline__ int mpos_v(int d) { return d < 2 ? 3 + d : (d < 4 ? 6 + d : 8 + d); }
__device__ __forceinline__ int pos_v(int d) { return d < 2 ? 6 + d : (d < 4 ? 12 + d : 16 + d); }

__device__ __forceinline__ uint4 quad_tr(const uint32_t* v, int t) {
    uint32_t a0 = (t & 1) ? v[0] : v[1], a1 = (t & 1) ? v[2] : v[3];
    a0 = __shfl_xor_sync(0xffffffffu, a0, 1); a1 = __shfl_xor_sync(0xffffffffu, a1, 1);
    const uint32_t b0 = (t & 1) ? a0 : v[0], b1 = (t & 1) ? v[1] : a0, b2 = (t & 1) ? a1 : v[2], b3 = (t & 1) ? v[3] : a1;
    uint32_t c0 = (t & 2) ? b0 : b2, c1 = (t & 2) ? b1 : b3;
    c0 = __shfl_xor_sync(0xffffffffu, c0, 2); c1 = __shfl_xor_sync(0xffffffffu, c1, 2);
    uint4 o;
    o.x = (t & 2) ? c0 : b0; o.y = (t & 2) ? c1 : b1; o.z = (t & 2) ? b2 : c0; o.w = (t & 2) ? b3 : c1;
    return o;
}
template <int BN>
__device__ __forceinline__ void store_tile(const float* acc, bf16* q, int pitch, int t) {
#pragma unroll
    for (int j = 0; j < BN / 32; j++) {
        uint32_t lo[4], hi[4];
#pragma unroll
        for (int i = 0; i < 4; i++) {
            lo[i] = pack2(acc[16 * j + 4 * i], acc[16 * j + 4 * i + 1]); hi[i] = pack2(acc[16 * j + 4 * i + 2], acc[16 * j + 4 * i + 3]);
        }
        *reinterpret_cast<uint4*>(q + j * 32 + t * 8) = quad_tr(lo, t);
        *reinterpret_cast<uint4*>(q + (size_t)8 * pitch + j * 32 + t * 8) = quad_tr(hi, t);
    }
}

template <int MT>
__device__ __forceinline__ void attnA_unit(uint32_t xr, uint32_t mr, int s, int h, int lane, uint32_t rel) {
    const int g = lane >> 2, t = lane & 3, l7 = lane & 7, l3 = lane >> 3;
    const float SC = 0.08838834764831845f * 1.4426950408889634f;
    constexpr int NT = MT ? 5 : 3;
    const uint32_t offA = (l7 + (l3 & 1) * 8) * 32 + (((l3 >> 1) ^ (l7 >> 2)) << 4);
    const uint32_t offB = (l7 + (l3 >> 1) * 8) * 32 + (((l3 & 1) ^ (l7 >> 2)) << 4);
    float sa[NT][4];
#pragma unroll
    for (int n = 0; n < NT; n++)
#pragma unroll
        for (int i = 0; i < 4; i++) sa[n][i] = 0.f;
#pragma unroll
    for (int hf = 0; hf < 2; hf++) {
        uint32_t qf[4][4], k0[4][4], k1[4][4], km[4][2];
#pragma unroll
        for (int i = 0; i < 4; i++) {
            const int d = hf * 4 + i;
            ldsm4(qf[i], xr + pos_q(d) * 1024 + MT * 512 + offA);
            ldsm2(km[i], mr + mpos_k(d) * 256 + (offB & 255));
            ldsm4(k0[i], xr + pos_k(d) * 1024 + offB);
            if (MT) ldsm4(k1[i], xr + pos_k(d) * 1024 + 512 + offB);
        }
#pragma unroll
        for (int i = 0; i < 4; i++) {
            mma16(sa[0], qf[i], km[i][0], km[i][1]);
            mma16(sa[1], qf[i], k0[i][0], k0[i][1]); mma16(sa[2], qf[i], k0[i][2], k0[i][3]);
            if (MT) { mma16(sa[NT - 2], qf[i], k1[i][0], k1[i][1]); mma16(sa[NT - 1], qf[i], k1[i][2], k1[i][3]); }
        }
    }
    if (2 * t > g) sa[NT - 2][0] = -INFINITY;
    if (2 * t + 1 > g) sa[NT - 2][1] = -INFINITY;
    sa[NT - 1][0] = -INFINITY; sa[NT - 1][1] = -INFINITY;
    if (2 * t > g) sa[NT - 1][2] = -INFINITY;
    if (2 * t + 1 > g) sa[NT - 1][3] = -INFINITY;
    float m0 = fmaxf(sa[0][0], sa[0][1]), m1 = fmaxf(sa[0][2], sa[0][3]);
#pragma unroll
    for (int n = 1; n < NT; n++) { m0 = fmaxf(m0, fmaxf(sa[n][0], sa[n][1])); m1 = fmaxf(m1, fmaxf(sa[n][2], sa[n][3])); }
    m0 = fmaxf(m0, __shfl_xor_sync(0xffffffffu, m0, 1)); m1 = fmaxf(m1, __shfl_xor_sync(0xffffffffu, m1, 1));
    m0 = fmaxf(m0, __shfl_xor_sync(0xffffffffu, m0, 2)); m1 = fmaxf(m1, __shfl_xor_sync(0xffffffffu, m1, 2));
    m0 *= SC; m1 *= SC;
    float s0 = 0.f, s1 = 0.f;
#pragma unroll
    for (int n = 0; n < NT; n++) {
        sa[n][0] = ex2(fmaf(sa[n][0], SC, -m0)); sa[n][1] = ex2(fmaf(sa[n][1], SC, -m0));
        sa[n][2] = ex2(fmaf(sa[n][2], SC, -m1)); sa[n][3] = ex2(fmaf(sa[n][3], SC, -m1));
        s0 += sa[n][0] + sa[n][1]; s1 += sa[n][2] + sa[n][3];
    }
    s0 += __shfl_xor_sync(0xffffffffu, s0, 1); s1 += __shfl_xor_sync(0xffffffffu, s1, 1);
    s0 += __shfl_xor_sync(0xffffffffu, s0, 2); s1 += __shfl_xor_sync(0xffffffffu, s1, 2);
    s0 = rcp_fast(s0); s1 = rcp_fast(s1);
    uint32_t pa[NT][2];
#pragma unroll
    for (int n = 0; n < NT; n++) { pa[n][0] = pack2(sa[n][0] * s0, sa[n][1] * s0); pa[n][1] = pack2(sa[n][2] * s1, sa[n][3] * s1); }
    const uint32_t p0[4] = {pa[1][0], pa[1][1], pa[2][0], pa[2][1]}, p1[4] = {pa[NT - 2][0], pa[NT - 2][1], pa[NT - 1][0], pa[NT - 1][1]};
    bf16* op = g_O + (size_t)(s * 32 + MT * 16 + g) * OK + h * DH + t * 8;
#pragma unroll
    for (int dh = 0; dh < 2; dh++) {
        uint32_t f0[4][4], f1[4][4], f2[4][2];
#pragma unroll
        for (int n2 = 0; n2 < 4; n2++) {
            const int d = dh * 4 + n2;
            ldsm4t(f0[n2], xr + pos_v(d) * 1024 + offA);
            if (MT) ldsm4t(f1[n2], xr + pos_v(d) * 1024 + 512 + offA);
            ldsm2t(f2[n2], mr + mpos_v(d) * 256 + (offB & 255));
        }
        uint32_t lo[8], hi[8];
#pragma unroll
        for (int n2 = 0; n2 < 4; n2++) {
            float oa0[4] = {0.f, 0.f, 0.f, 0.f}, oa1[4] = {0.f, 0.f, 0.f, 0.f};
            mma16(oa0, p0, f0[n2][0], f0[n2][1]); mma16(oa1, p0, f0[n2][2], f0[n2][3]);
            if (MT) { mma16(oa0, p1, f1[n2][0], f1[n2][1]); mma16(oa1, p1, f1[n2][2], f1[n2][3]); }
            mma8(oa0, pa[0][0], pa[0][1], f2[n2][0]); mma8(oa1, pa[0][0], pa[0][1], f2[n2][1]);
            lo[2 * n2] = pack2(oa0[0], oa0[1]); hi[2 * n2] = pack2(oa0[2], oa0[3]);
            lo[2 * n2 + 1] = pack2(oa1[0], oa1[1]); hi[2 * n2 + 1] = pack2(oa1[2], oa1[3]);
        }
        if (dh == 1) { __syncwarp(); if (lane == 0) mbar_arrive(rel); }
#pragma unroll
        for (int q = 0; q < 2; q++) {
            *reinterpret_cast<uint4*>(op + dh * 64 + q * 32) = quad_tr(lo + 4 * q, t);
            *reinterpret_cast<uint4*>(op + (size_t)8 * OK + dh * 64 + q * 32) = quad_tr(hi + 4 * q, t);
        }
    }
}

template <int V> struct IC { static constexpr int value = V; };
__device__ __forceinline__ void attnB_unit(uint32_t sQ, int q0, int hh, int wq, int lane, uint32_t rel) {
    const int g = lane >> 2, t = lane & 3, l7 = lane & 7, l3 = lane >> 3;
    const uint32_t sK = sQ + 128 * 48, sV = sK + 384 * 48;
    const int sh = (hh & 3) * 2;
    uint32_t qa[2][4], qb[2][2];
#pragma unroll
    for (int m = 0; m < 2; m++) {
        ldsm4(qa[m], sQ + (wq * 32 + m * 16 + l7 + (l3 & 1) * 8) * 48 + (l3 >> 1) * 16);
        ldsm2(qb[m], sQ + (wq * 32 + m * 16 + l7 + (l3 & 1) * 8) * 48 + 32);
        if (2 * t < sh) { qa[m][0] = 0u; qa[m][1] = 0u; }
        if (16 + 2 * t >= sh + 18) { qb[m][0] = 0u; qb[m][1] = 0u; }
    }
    const bool one0 = (sh == 6 && g == 0), one2 = (sh != 6 && g == 7);
    float gt[2][2];
#pragma unroll
    for (int m = 0; m < 2; m++) { gt[m][0] = __ldcg(g_gate + q0 + wq * 32 + m * 16 + g); gt[m][1] = __ldcg(g_gate + q0 + wq * 32 + m * 16 + g + 8); }
    const float SC = 0.23570226039551584f * 1.4426950408889634f;
    float o[2][3][4];
    float mx[2][2];
#pragma unroll
    for (int m = 0; m < 2; m++) {
        mx[m][0] = -INFINITY; mx[m][1] = -INFINITY;
#pragma unroll
        for (int n = 0; n < 3; n++)
#pragma unroll
            for (int i = 0; i < 4; i++) o[m][n][i] = 0.f;
    }
    const int tfirst = max(0, (256 - q0) / 16 - 2 * wq);
    const uint32_t kb0 = sK + (wq * 32 + l7 + (l3 >> 1) * 8) * 48 + (l3 & 1) * 16;
    const uint32_t kb1 = sK + (wq * 32 + l7 + (l3 & 1) * 8) * 48 + 32;
    const uint32_t vb0 = sV + (wq * 32 + l7 + (l3 & 1) * 8) * 48 + (l3 >> 1) * 16;
    const uint32_t vb1 = sV + (wq * 32 + l7 + (l3 & 1) * 8) * 48 + 32;
    constexpr int CH = 3;
    auto chunk = [&](auto mode, int c0) {
        constexpr int MODE = decltype(mode)::value;
        auto dead = [](int m, int u) { return (MODE == 0 && m == 0 && u == 2) || (MODE == 2 && m == 1 && u == 0); };
        float sc[2][CH][2][4];
#pragma unroll
        for (int u = 0; u < CH; u++) {
            uint32_t kf[4], kg[2];
            const int ti = MODE == 3 ? max(c0 + u, tfirst) : c0 + u;
            ldsm4(kf, kb0 + ti * 768); ldsm2(kg, kb1 + ti * 768);
#pragma unroll
            for (int m = 0; m < 2; m++) {
                if (dead(m, u)) continue;
#pragma unroll
                for (int n = 0; n < 2; n++) {
#pragma unroll
                    for (int i = 0; i < 4; i++) sc[m][u][n][i] = 0.f;
                    mma16(sc[m][u][n], qa[m], kf[2 * n], kf[2 * n + 1]);
                    mma8(sc[m][u][n], qb[m][0], qb[m][1], kg[n]);
                }
            }
        }
#pragma unroll
        for (int m = 0; m < 2; m++)
#pragma unroll
            for (int u = 0; u < CH; u++)
#pragma unroll
                for (int n = 0; n < 2; n++)
#pragma unroll
                    for (int i = 0; i < 4; i++) {
                        const int dl = g + (i >> 1) * 8 - (n * 8 + 2 * t + (i & 1));
                        if (MODE == 0 && u == m + 1 && dl < 0) sc[m][u][n][i] = -INFINITY;
                        if (MODE == 2 && u == m && dl >= 0) sc[m][u][n][i] = -INFINITY;
                        if (MODE == 3) {
                            const int d = 256 + (m - c0 - u) * 16 + dl;
                            if (d < 0 || d >= 256 || c0 + u < tfirst) sc[m][u][n][i] = -INFINITY;
                        }
                    }
        float bs[2][2];
#pragma unroll
        for (int m = 0; m < 2; m++) {
            float n0 = mx[m][0], n1 = mx[m][1];
#pragma unroll
            for (int u = 0; u < CH; u++) {
                if (dead(m, u)) continue;
#pragma unroll
                for (int n = 0; n < 2; n++) {
                    n0 = fmaxf(n0, fmaxf(sc[m][u][n][0], sc[m][u][n][1])); n1 = fmaxf(n1, fmaxf(sc[m][u][n][2], sc[m][u][n][3]));
                }
            }
            n0 = fmaxf(n0, __shfl_xor_sync(0xffffffffu, n0, 1)); n1 = fmaxf(n1, __shfl_xor_sync(0xffffffffu, n1, 1));
            n0 = fmaxf(n0, __shfl_xor_sync(0xffffffffu, n0, 2)); n1 = fmaxf(n1, __shfl_xor_sync(0xffffffffu, n1, 2));
            if (MODE != 0) {
                const float f0 = ex2((mx[m][0] - n0) * SC), f1 = ex2((mx[m][1] - n1) * SC);
#pragma unroll
                for (int n = 0; n < 3; n++) { o[m][n][0] *= f0; o[m][n][1] *= f0; o[m][n][2] *= f1; o[m][n][3] *= f1; }
            }
            mx[m][0] = n0; mx[m][1] = n1;
            bs[m][0] = n0 * SC; bs[m][1] = n1 * SC;
        }
#pragma unroll
        for (int u = 0; u < CH; u++) {
            uint32_t vf[4], vg[2];
            const int ti = MODE == 3 ? max(c0 + u, tfirst) : c0 + u;
            ldsm4t(vf, vb0 + ti * 768); ldsm2t(vg, vb1 + ti * 768);
            if (one0) { vf[0] = 0x3f803f80u; vf[1] = 0x3f803f80u; }
            if (one2) { vg[0] = 0x3f803f80u; vg[1] = 0x3f803f80u; }
#pragma unroll
            for (int m = 0; m < 2; m++) {
                if (dead(m, u)) continue;
                uint32_t pa[4];
#pragma unroll
                for (int n = 0; n < 2; n++) {
                    pa[2 * n] = pack2(ex2(fmaf(sc[m][u][n][0], SC, -bs[m][0])), ex2(fmaf(sc[m][u][n][1], SC, -bs[m][0])));
                    pa[2 * n + 1] = pack2(ex2(fmaf(sc[m][u][n][2], SC, -bs[m][1])), ex2(fmaf(sc[m][u][n][3], SC, -bs[m][1])));
                }
                mma16(o[m][0], pa, vf[0], vf[1]); mma16(o[m][1], pa, vf[2], vf[3]); mma16(o[m][2], pa, vg[0], vg[1]);
            }
        }
    };
    if (tfirst == 0) {
        chunk(IC<0>{}, 15);
#pragma unroll 1
        for (int c0 = 12; c0 > 0; c0 -= CH) chunk(IC<1>{}, c0);
        chunk(IC<2>{}, 0);
    } else {
#pragma unroll 1
        for (int c0 = 15; c0 >= 0 && c0 + CH > tfirst; c0 -= CH) chunk(IC<3>{}, c0);
    }
    __syncwarp();
    if (lane == 0) mbar_arrive(rel);
#pragma unroll
    for (int m = 0; m < 2; m++) {
        const int src = sh == 6 ? (lane & ~3) : (lane | 3);
        const float s0 = __shfl_sync(0xffffffffu, sh == 6 ? o[m][0][0] : o[m][2][1], src);
        const float s1 = __shfl_sync(0xffffffffu, sh == 6 ? o[m][0][2] : o[m][2][3], src);
        const int r = q0 + wq * 32 + m * 16 + g;
        const float i0 = (1.f - gt[m][0]) * rcp_fast(s0), i1 = (1.f - gt[m][1]) * rcp_fast(s1);
        bf16* op = g_O + (size_t)r * OK + HD + hh * BD + 2 * t - sh;
#pragma unroll
        for (int n = 0; n < 3; n++) {
            const int col = n * 8 + 2 * t;
            if (col >= sh && col < sh + 18) {
                *reinterpret_cast<uint32_t*>(op + n * 8) = pack2(o[m][n][0] * i0, o[m][n][1] * i0);
                *reinterpret_cast<uint32_t*>(op + n * 8 + 8 * OK) = pack2(o[m][n][2] * i1, o[m][n][3] * i1);
            }
        }
    }
}

template <int BN>
__device__ __forceinline__ void gemm_unit(int ty, const uint32_t* d, uint32_t sb, uint32_t bF, uint32_t bE, int& sg, int& ph,
                                          int warp, int lane, bf16* __restrict__ out) {
    const int wg = warp >> 2, wq = warp & 3, g = lane >> 2, t = lane & 3;
    auto release = [&](int q) { __syncwarp(); if (lane == 0) mbar_arrive(bE + 8 * q); };
    const int n0 = d[2] * BN, kb0 = d[3] & 255, kb1 = d[3] >> 8;
    const int rb = (ty == T_G0 ? d[1] * 192 : f_row0(d[1])) + (BN == 64 ? wq : warp) * 16, r0 = rb + g;
    float g0 = 1.f, g1 = 1.f;
    if (ty != T_G0) { g0 = __ldcg(g_gate + r0); g1 = __ldcg(g_gate + r0 + 8); }
    if (ty != T_G0 && f_split(d[1]) > 1) {
        const float* pa = g_acc + (size_t)rb * DM + n0 * 16 + lane * 32;
#pragma unroll
        for (int i = 0; i < (BN + 63) / 64; i++) if (i * 64 + lane * 2 < BN) asm volatile("prefetch.global.L2 [%0];" ::"l"(pa + i * 1024));
    }
    float acc[BN / 2];
#pragma unroll
    for (int i = 0; i < BN / 2; i++) acc[i] = 0.f;
    int prev = -1;
    constexpr int KPS = BN == 64 ? 3 : 1;
    for (int kb = kb0; kb < kb1;) {
        if (kb > kb0) mbar_wait(bF + 8 * sg, ph);
        for (int j = 0; j < KPS && kb < kb1; j++, kb++) {
            const uint32_t a = sb + sg * H_STAGE + (BN == 64 ? j * 16384 : wg * 8192), b = BN == 64 ? a + 8192 : sb + sg * H_STAGE + 24576;
            if (kb == 64 && kb0 < 64) {
                wg_wait<0>();
#pragma unroll
                for (int i = 0; i < BN / 8; i++) { acc[4 * i] *= g0; acc[4 * i + 1] *= g0; acc[4 * i + 2] *= g1; acc[4 * i + 3] *= g1; }
            }
            const uint64_t da = desc_sw128(a, 16, 1024), db = desc_sw128(b, 8192, 1024);
            wg_fence();
#pragma unroll
            for (int k = 0; k < 4; k++) {
                if (BN == 192) wgmma_ss_n192(acc, da + (uint64_t)(k * 2), db + (uint64_t)(k * 128), 1);
                else if (BN == 96) wgmma_ss_n96(acc, da + (uint64_t)(k * 2), db + (uint64_t)(k * 128));
                else wgmma_ss_n64(acc, da + (uint64_t)(k * 2), db + (uint64_t)(k * 128));
            }
            wg_commit();
            wg_wait<1>();
            if (j == 0 && prev >= 0) release(prev);
        }
        prev = sg;
        if (++sg == H_STAGES) { sg = 0; ph ^= 1; }
    }
    wg_wait<0>();
    if (ty == T_G0) {
        release(prev);
        store_tile<BN>(acc, g_qkvB + (size_t)r0 * (3 * DM) + n0, 3 * DM, t);
        signal(g_ctr + C_G0 + d[1], lane);
        return;
    }
    if (kb1 <= 64) {
#pragma unroll
        for (int i = 0; i < BN / 8; i++) { acc[4 * i] *= g0; acc[4 * i + 1] *= g0; acc[4 * i + 2] *= g1; acc[4 * i + 3] *= g1; }
    }
    const int ks = f_split(d[1]);
    bool fin = true;
    if (ks == 1) release(prev);
    if (ks > 1) {
        float4* ga = reinterpret_cast<float4*>(g_acc + (size_t)rb * DM + n0 * 16) + lane;
#pragma unroll
        for (int i = 0; i < BN / 8; i++) red4(reinterpret_cast<float*>(ga + i * 32), acc[4 * i], acc[4 * i + 1], acc[4 * i + 2], acc[4 * i + 3]);
        release(prev);
        unsigned old = 0;
        if (lane == 0) asm volatile("atom.acq_rel.gpu.global.add.u32 %0,[%1],1;" : "=r"(old) : "l"(g_ctr + C_F + (d[1] * 9 + d[2]) * 12 + warp) : "memory");
        old = __shfl_sync(0xffffffffu, old, 0);
        fin = (old == (unsigned)ks - 1);
        if (fin) {
#pragma unroll
            for (int i = 0; i < BN / 8; i++) {
                const float4 u = __ldcg(ga + i * 32);
                acc[4 * i] = u.x; acc[4 * i + 1] = u.y; acc[4 * i + 2] = u.z; acc[4 * i + 3] = u.w;
            }
        }
    }
    if (fin) store_tile<BN>(acc, out + (size_t)r0 * DM + n0, DM, t);
}

struct HelpMaps { CUtensorMap x, wqkv, O, O128, O64, Wo, wo, qkv; };

__global__ void __launch_bounds__(512, 1) k_help(const __grid_constant__ HelpMaps tm, const bf16* __restrict__ x,
                                                  const bf16* __restrict__ gw, bf16* __restrict__ out) {
    extern __shared__ uint8_t smem_raw[];
    const uint32_t sb = (s2u(smem_raw) + 1023) & ~1023u;
    const uint32_t bF = sb + H_STAGES * H_STAGE, bE = bF + 8 * H_STAGES, dsc = bF + 128;
    const int tid = threadIdx.x, warp = __shfl_sync(0xffffffffu, tid >> 5, 0), lane = tid & 31;
    if (tid == 0) {
        for (int i = 0; i < H_STAGES; i++) { mbar_init(bF + 8 * i, 1); mbar_init(bE + 8 * i, 12); }
        asm volatile("fence.mbarrier_init.release.cluster;" ::: "memory");
    }
    __syncthreads();
    if (warp >= 12) {
        asm volatile("setmaxnreg.dec.sync.aligned.u32 56;");
        if (warp != 12) {
            while (true) {
                unsigned u = 0;
                if (lane == 0) u = atomicAdd(g_ctr + C_HG, 1);
                u = __shfl_sync(0xffffffffu, u, 0);
                if (u >= SEQ / 16) return;
#pragma unroll 1
                for (int r0 = u * 16; r0 < u * 16 + 16; r0 += 2) {
                    float a0 = 0.f, a1 = 0.f;
                    const __nv_bfloat162* xr = reinterpret_cast<const __nv_bfloat162*>(x + (size_t)r0 * DM);
#pragma unroll
                    for (int i = 0; i < 9; i++) {
                        const float2 b = __bfloat1622float2(reinterpret_cast<const __nv_bfloat162*>(gw)[lane + 32 * i]);
                        const float2 y = __bfloat1622float2(xr[lane + 32 * i]), z = __bfloat1622float2(xr[DM / 2 + lane + 32 * i]);
                        a0 += y.x * b.x + y.y * b.y; a1 += z.x * b.x + z.y * b.y;
                    }
#pragma unroll
                    for (int o = 16; o; o >>= 1) { a0 += __shfl_xor_sync(0xffffffffu, a0, o); a1 += __shfl_xor_sync(0xffffffffu, a1, o); }
                    if (lane < 2) g_gate[r0 + lane] = 1.f / (1.f + __expf(-(lane ? a1 : a0)));
                }
                signal(g_ctr + C_GATE, lane);
            }
        }
        int sg = 0, ph = 1;
        auto next = [&](int ty, int a, int b, int c2) {
            mbar_wait(bE + 8 * sg, ph);
            if (lane == 0) asm volatile("st.shared.v4.u32 [%0],{%1,%2,%3,%4};" ::"r"(dsc + 16 * sg), "r"(ty), "r"(a), "r"(b), "r"(c2) : "memory");
        };
        auto adv = [&]() { __syncwarp(); if (++sg == H_STAGES) { sg = 0; ph ^= 1; } };
        auto acquire = [&]() { asm volatile("fence.acq_rel.gpu;" ::: "memory"); };
        auto ticket = [&](unsigned* q) { unsigned u = 0; if (lane == 0) u = atomicAdd(q, 1); return __shfl_sync(0xffffffffu, u, 0); };
        auto gemm = [&](int ty, int m, int n, int kb0, int kb1) {
            for (int kb = kb0; kb < kb1; kb++) {
                next(ty, m, n, kb0 | (kb1 << 8));
                if (lane == 0) {
                    const uint32_t a = sb + sg * H_STAGE, b = a + 24576, bar = bF + 8 * sg;
                    const bool half = ty != T_G0 && m >= 9;
                    mbar_expect(bar, (ty == T_FN ? 40960 : 49152) - (half ? 8192 : 0));
                    tma2d(a, ty == T_G0 ? &tm.x : (half ? &tm.O128 : &tm.O), kb * 64, ty == T_G0 ? m * 192 : f_row0(m), bar);
                    const CUtensorMap* mb = ty == T_G0 ? &tm.wqkv : (kb >= 64 ? &tm.wo : &tm.Wo);
                    const int kr = (kb >= 64 ? kb - 64 : kb) * 64;
                    if (ty == T_FN) for (int j = 0; j < 2; j++) tma2d(b + j * 8192, mb, n * 96 + j * 64, kr, bar);
                    else for (int j = 0; j < 3; j++) tma2d(b + j * 8192, mb, n * 192 + j * 64, kr, bar);
                }
                adv();
            }
        };
        bool bdone = false;
        int idle = 0, rr = 0;
        const int fl = min(lane, 10);
        constexpr int NLATE = (NSEG - AA_LATE) * 6, NSMALL = 9 * f_split(11);
        auto attn_a = [&](int as, int u) {
            const int per = (15 + aa_units(as)) / aa_units(as), ns = min(per, 16 - u * per), h0 = u * per * 2;
            for (int i = 0; i < ns; i++) {
                next(T_AA, as, h0 + 2 * i, rr | (i + 3 >= ns ? 4 : 0)); rr = rr == 2 ? 0 : rr + 1;
                if (lane == 0) {
                    const uint32_t a = sb + sg * H_STAGE, bar = bF + 8 * sg;
                    mbar_expect(bar, 57344);
                    bulk_load(a, reinterpret_cast<uint8_t*>(g_xr) + (size_t)(as * 32 + h0 + 2 * i) * 24576, 49152, bar);
                    bulk_load(a + 49152, reinterpret_cast<uint8_t*>(g_mr) + (size_t)(as * 32 + h0 + 2 * i) * 4096, 8192, bar);
                }
                adv();
            }
        };
        auto spin_ge = [&](const unsigned* q, unsigned target) {
            int it = 0;
            while (ld_acq(q) < target) { __nanosleep(SPIN_NS); if (++it > (1 << 22)) __trap(); }
        };
        auto drain = [&]() {
            const int ls = sg == 0 ? H_STAGES - 1 : sg - 1;
            mbar_wait(bE + 8 * ls, sg == 0 ? ph : ph ^ 1);
        };
        while (true) {
            const unsigned tk0 = ld_relaxed1(g_ctr + C_HAA + lane), tk1 = ld_relaxed1(g_ctr + C_HAA + 32 + lane);
            const unsigned f0 = ld_relaxed1(g_flagA + lane), f1 = ld_relaxed1(g_flagA + 32 + lane);
            const unsigned tkf = ld_relaxed1(g_ctr + C_HF + min(lane, 12)), ca = ld_relaxed1(g_ctr + C_AA + fl);
            const unsigned cb0 = ld_relaxed1(g_ctr + C_AB + (lane > 10 ? 15 : f_row0(fl) / 128));
            const unsigned cb1 = ld_relaxed1(g_ctr + C_AB + (lane > 10 ? 15 : (f_row0(fl) + f_rows(fl) - 1) / 128));
            const bool e0 = tk0 < (unsigned)aa_units(lane), e1 = 32 + lane < AA_LATE && tk1 < (unsigned)aa_units(32 + lane);
            const unsigned a0 = __ballot_sync(0xffffffffu, e0 && f0 >= 192), a1 = __ballot_sync(0xffffffffu, e1 && f1 >= 192);
            const bool early_left = __any_sync(0xffffffffu, e0 || e1);
            const unsigned tl = __shfl_sync(0xffffffffu, tkf, 11), ts = __shfl_sync(0xffffffffu, tkf, 12);
            const bool fleft = lane < 11 && tkf < (unsigned)(f_ntiles(fl) * f_split(fl));
            const unsigned fl_m = __ballot_sync(0xffffffffu, fleft);
            const bool may = blockIdx.x >= (fl >= AA_B3 ? AA_CTAS3 : (fl >= 6 ? AA_CTAS2 : AA_CTAS)) || tl >= NLATE;
            const unsigned fr = __ballot_sync(0xffffffffu, fleft && ca >= (unsigned)(2 * f_rows(fl)) && cb0 >= 128 && cb1 >= 128 && may);
            if (a0 | a1) {
                const int as = a0 ? __ffs(a0) - 1 : 31 + __ffs(a1);
                const unsigned u = ticket(g_ctr + C_HAA + as);
                if (u < (unsigned)aa_units(as)) { acquire(); attn_a(as, u); continue; }
            }
            if (tl < NLATE && !early_left) {
                const bool ready = __shfl_sync(0xffffffffu, f1, (AA_LATE - 32 + tl / 6) & 31) >= 192;
                if (ready || (blockIdx.x < AA_CTAS3 && bdone)) {
                    drain();
                    const unsigned u = ticket(g_ctr + C_HF + 11);
                    if (u < NLATE) { spin_ge(g_flagA + AA_LATE + u / 6, 192); attn_a(AA_LATE + u / 6, u % 6); drain(); continue; }
                }
            }
            if (fr) {
                const int fm = __ffs(fr) - 1;
                const unsigned u = ticket(g_ctr + C_HF + fm);
                const int ks = f_split(fm), nt = f_ntiles(fm);
                if (u < (unsigned)(nt * ks)) {
                    const int kp = u / nt;
                    acquire();
                    gemm(nt == 3 ? T_F : T_FN, fm, u % nt, kp * 73 / ks, (kp + 1) * 73 / ks);
                    if (fm >= DRAIN_B) drain();
                    continue;
                }
            }
            if (ts < NSMALL && tl >= NLATE && __shfl_sync(0xffffffffu, cb0 >= 128, 11)) {
                const unsigned u = ticket(g_ctr + C_HF + 12);
                if (u < NSMALL) {
                    const int fm = 11, v = u;
                    const int nn = v % 9, kp = v / 9, kb0 = kp * 73 / f_split(fm), kb1 = (kp + 1) * 73 / f_split(fm);
                    for (int k0 = kb0; k0 < kb1; k0 += 3 * H_STAGES) {
                        const int sg0 = sg, k1 = min(kb1, k0 + 3 * H_STAGES);
                        for (int kb = k0; kb < k1; kb += 3) {
                            next(T_FS, fm, nn, kb0 | (kb1 << 8));
                            const int kk = kb + lane;
                            if (lane == 0) mbar_expect(bF + 8 * sg, min(3, k1 - kb) * 16384);
                            __syncwarp();
                            if (lane < 3 && kk < k1) {
                                tma2d(sb + sg * H_STAGE + lane * 16384 + 8192, kk >= 64 ? &tm.wo : &tm.Wo, nn * 64, (kk >= 64 ? kk - 64 : kk) * 64, bF + 8 * sg);
                                if (k0 > kb0) tma2d(sb + sg * H_STAGE + lane * 16384, &tm.O64, kk * 64, f_row0(fm), bF + 8 * sg);
                            }
                            adv();
                        }
                        if (k0 == kb0) {
                            spin_ge(g_ctr + C_AA + fm, 128);
                            if (k0 + lane < k1) {
                                const int q = (sg0 + lane / 3) % H_STAGES;
                                tma2d(sb + q * H_STAGE + (lane % 3) * 16384, &tm.O64, (k0 + lane) * 64, f_row0(fm), bF + 8 * q);
                            }
                            __syncwarp();
                        }
                    }
                    drain();
                    continue;
                }
            }
            if (a0 | a1 | fr) continue;
            if (!bdone) {
                const unsigned u = ticket(g_ctr + C_HB);
                if (u < NG0) {
                    gemm(T_G0, u / 9, u % 9, 0, 9);
                } else if (u < NB_UNITS) {
                    const int m = (u - NG0) / ABT, h0 = ((u - NG0) % ABT) * ABH, h1 = min(h0 + ABH, BH);
                    const int mm = min(max(0, m * 128 - 256) / 192 + lane, (m * 128 + 127) / 192);
                    const unsigned* q = lane == 31 ? g_ctr + C_GATE : g_ctr + C_G0 + mm;
                    int it = 0;
                    while (!__all_sync(0xffffffffu, ld_relaxed1(q) >= (lane == 31 ? 128u : 108u))) { __nanosleep(100); if (++it > (1 << 22)) __trap(); }
                    acquire();
                    for (int hh = h0; hh < h1; hh++) {
                        next(T_AB, m, hh, rr | (hh + 3 >= h1 ? 4 : 0)); rr = rr == 2 ? 0 : rr + 1;
                        if (lane == 0) {
                            const uint32_t a = sb + sg * H_STAGE, bar = bF + 8 * sg;
                            const int col = (hh >> 2) * 72 + (hh & 3) * 16;
                            mbar_expect(bar, 7 * 6144);
                            tma2d(a, &tm.qkv, col, m * 128, bar);
                            for (int j = 0; j < 3; j++) {
                                tma2d(a + (1 + j) * 6144, &tm.qkv, DM + col, (m - 2 + j) * 128, bar);
                                tma2d(a + (4 + j) * 6144, &tm.qkv, 2 * DM + col, (m - 2 + j) * 128, bar);
                            }
                        }
                        adv();
                    }
                } else bdone = true;
                continue;
            }
            if (fl_m == 0 && ts >= NSMALL) break;
            __nanosleep(150);
            if (++idle > (1 << 22)) __trap();
        }
        next(T_EXIT, 0, 0, 0);
        if (lane == 0) mbar_arrive(bF + 8 * sg);
    } else {
        asm volatile("setmaxnreg.inc.sync.aligned.u32 152;");
        const int wg = warp >> 2, wq = warp & 3;
        int sg = 0, ph = 0, skip = 0;
        unsigned pend = 0;
        auto release = [&](int q) { __syncwarp(); if (lane == 0) mbar_arrive(bE + 8 * q); };
        auto adv = [&]() { if (++sg == H_STAGES) { sg = 0; ph ^= 1; } };
        while (true) {
            mbar_wait(bF + 8 * sg, ph);
            uint32_t d[4];
            lds128(d, dsc + 16 * sg);
            const int ty = d[0];
            if (ty == T_EXIT) break;
            if ((ty == T_G0 && wg == 2 && d[1] == NBLK - 1) || ((ty == T_F || ty == T_FN) && wg == 2 && d[1] >= 9) || (ty == T_FS && wg != 0)) {
                release(sg); adv();
                if (ty == T_G0 && ++skip == 9) { skip = 0; signal(g_ctr + C_G0 + d[1], lane); }
            } else if (ty == T_G0 || ty == T_F) {
                gemm_unit<192>(ty, d, sb, bF, bE, sg, ph, warp, lane, out);
            } else if (ty == T_FN) {
                gemm_unit<96>(ty, d, sb, bF, bE, sg, ph, warp, lane, out);
            } else if (ty == T_FS) {
                gemm_unit<64>(ty, d, sb, bF, bE, sg, ph, warp, lane, out);
                if (tid == 0 && d[1] == NFB - 1) g_sync[0] = 0;
            } else {
                if ((int)(d[3] & 3) == wg) {
                    if (ty == T_AA) {
                        const uint32_t xr = sb + sg * H_STAGE + (wq >> 1) * 24576, mr = sb + sg * H_STAGE + 49152 + (wq >> 1) * 4096;
                        if ((wq + wg) & 1) attnA_unit<1>(xr, mr, d[1], d[2] + (wq >> 1), lane, bE + 8 * sg);
                        else attnA_unit<0>(xr, mr, d[1], d[2] + (wq >> 1), lane, bE + 8 * sg);
                        pend++;
                        if (d[3] & 4) { signal(g_ctr + C_AA + f_blk(d[1]), lane, pend); pend = 0; }
                    } else {
                        attnB_unit(sb + sg * H_STAGE, d[1] * 128, d[2], wq, lane, bE + 8 * sg);
                        pend++;
                        if (d[3] & 4) { signal(g_ctr + C_AB + d[1], lane, pend); pend = 0; }
                    }
                } else {
                    release(sg);
                }
                adv();
            }
        }
    }
}

__device__ float g_fmem[(NSEG + 1) * 8 * DM];
__device__ bf16 g_fq[8 * HD];
__device__ __forceinline__ int tile_off(int row, int e) { return row * 16 + ((((e >> 3) ^ (row >> 2)) & 1) << 3) + (e & 7); }

__global__ void fb_init(const bf16* __restrict__ mem0) {
    const int i = blockIdx.x * blockDim.x + threadIdx.x;
    if (i < (NSEG + 1) * 8 * DM) g_fmem[i] = i < 8 * DM ? __bfloat162float(mem0[i]) : 0.f;
    if (i < SEQ * DM) g_acc[i] = 0.f;
    if (i < 1920) g_ctr[i] = 0;
    if (i < NSEG) g_flagA[i] = 192;
}
__global__ void fb_proj(const bf16* __restrict__ x, const bf16* __restrict__ Wq, const bf16* __restrict__ Wk, const bf16* __restrict__ Wv, int seg) {
    __shared__ float in[8][DM];
    for (int i = threadIdx.x; i < 8 * DM; i += blockDim.x)
        in[i / DM][i % DM] = seg >= 0 ? __bfloat162float(__float2bfloat16(g_fmem[seg * 8 * DM + i])) : __bfloat162float(x[(size_t)blockIdx.y * 8 * DM + i]);
    __syncthreads();
    const int col = blockIdx.x * blockDim.x + threadIdx.x, ty = col / HD, hc = col % HD, h = hc / DH, d = (hc % DH) >> 4, e = hc & 15;
    const bf16* W = (ty == 0 ? Wq : (ty == 1 ? Wk : Wv)) + hc;
    float a[8] = {0.f, 0.f, 0.f, 0.f, 0.f, 0.f, 0.f, 0.f};
    for (int k = 0; k < DM; k++) {
        const float w = __bfloat162float(W[(size_t)k * HD]);
#pragma unroll
        for (int r = 0; r < 8; r++) a[r] += in[r][k] * w;
    }
    for (int r = 0; r < 8; r++) {
        const bf16 v = __float2bfloat16(a[r]);
        if (seg < 0) {
            const int pos = ty == 0 ? pos_q(d) : (ty == 1 ? pos_k(d) : pos_v(d));
            reinterpret_cast<bf16*>(g_xr)[((size_t)((blockIdx.y >> 2) * 32 + h) * 24 + pos) * 512 + tile_off((blockIdx.y & 3) * 8 + r, e)] = v;
        } else if (ty == 0) g_fq[r * HD + hc] = v;
        else reinterpret_cast<bf16*>(g_mr)[((size_t)(seg * 32 + h) * 16 + (ty == 1 ? mpos_k(d) : mpos_v(d))) * 128 + tile_off(r, e)] = v;
    }
}
__global__ void fb_attn(const bf16* __restrict__ Wo, int seg) {
    __shared__ float sc[8][40], o[8][DH];
    const int h = blockIdx.x, tid = threadIdx.x;
    const bf16* xr = reinterpret_cast<const bf16*>(g_xr) + (size_t)(seg * 32 + h) * 24 * 512;
    const bf16* mr = reinterpret_cast<const bf16*>(g_mr) + (size_t)(seg * 32 + h) * 16 * 128;
    {
        const int r = tid / 40, j = tid % 40;
        float a = 0.f;
        for (int c = 0; c < DH; c++) {
            const bf16 kv = j < 8 ? mr[mpos_k(c >> 4) * 128 + tile_off(j, c & 15)] : xr[pos_k(c >> 4) * 512 + tile_off(j - 8, c & 15)];
            a += __bfloat162float(g_fq[r * HD + h * DH + c]) * __bfloat162float(kv);
        }
        sc[r][j] = a * 0.08838834764831845f;
    }
    __syncthreads();
    if (tid < 8) {
        float m = sc[tid][0], z = 0.f;
        for (int j = 1; j < 40; j++) m = fmaxf(m, sc[tid][j]);
        for (int j = 0; j < 40; j++) { sc[tid][j] = __expf(sc[tid][j] - m); z += sc[tid][j]; }
        for (int j = 0; j < 40; j++) sc[tid][j] /= z;
    }
    __syncthreads();
    for (int i = tid; i < 8 * DH; i += 320) {
        const int r = i / DH, c = i % DH;
        float a = 0.f;
        for (int j = 0; j < 40; j++)
            a += sc[r][j] * __bfloat162float(j < 8 ? mr[mpos_v(c >> 4) * 128 + tile_off(j, c & 15)] : xr[pos_v(c >> 4) * 512 + tile_off(j - 8, c & 15)]);
        o[r][c] = __bfloat162float(__float2bfloat16(a));
    }
    __syncthreads();
    for (int n = tid; n < DM; n += 320) {
        float a[8] = {0.f, 0.f, 0.f, 0.f, 0.f, 0.f, 0.f, 0.f};
        for (int c = 0; c < DH; c++) {
            const float w = __bfloat162float(Wo[(size_t)(h * DH + c) * DM + n]);
#pragma unroll
            for (int r = 0; r < 8; r++) a[r] += o[r][c] * w;
        }
        for (int r = 0; r < 8; r++) atomicAdd(g_fmem + ((seg + 1) * 8 + r) * DM + n, a[r]);
    }
}

typedef CUresult (*EncodeFn)(CUtensorMap*, CUtensorMapDataType, cuuint32_t, void*, const cuuint64_t*, const cuuint64_t*,
                             const cuuint32_t*, const cuuint32_t*, CUtensorMapInterleave, CUtensorMapSwizzle,
                             CUtensorMapL2promotion, CUtensorMapFloatOOBfill);

static void make_map(EncodeFn fn, CUtensorMap* m, const void* ptr, uint64_t cols, uint64_t rows, uint32_t bc, uint32_t br,
                     CUtensorMapSwizzle sw = CU_TENSOR_MAP_SWIZZLE_128B) {
    cuuint64_t dims[2] = {cols, rows};
    cuuint64_t strides[1] = {cols * 2};
    cuuint32_t box[2] = {bc, br};
    cuuint32_t es[2] = {1, 1};
    fn(m, CU_TENSOR_MAP_DATA_TYPE_BFLOAT16, 2, const_cast<void*>(ptr), dims, strides, box, es, CU_TENSOR_MAP_INTERLEAVE_NONE,
       sw, sw == CU_TENSOR_MAP_SWIZZLE_NONE ? CU_TENSOR_MAP_L2_PROMOTION_NONE : CU_TENSOR_MAP_L2_PROMOTION_L2_256B, CU_TENSOR_MAP_FLOAT_OOB_FILL_NONE);
}

extern "C" void kernel_launch(void* const* d_in, const int* in_sizes, int n_in, void* d_out, int out_size) {
    const bf16* x = (const bf16*)d_in[0];
    const bf16* mem0 = (const bf16*)d_in[1];
    const bf16* Wq = (const bf16*)d_in[2];
    const bf16* Wk = (const bf16*)d_in[3];
    const bf16* Wv = (const bf16*)d_in[4];
    const bf16* Wo = (const bf16*)d_in[5];
    const bf16* wqkv = (const bf16*)d_in[8];
    const bf16* wo = (const bf16*)d_in[9];
    const bf16* gw = (const bf16*)d_in[10];
    bf16* out = (bf16*)d_out;

    void* fp = nullptr;
    cudaDriverEntryPointQueryResult qr;
    cudaGetDriverEntryPoint("cuTensorMapEncodeTiled", &fp, cudaEnableDefault, &qr);
    EncodeFn enc = (EncodeFn)fp;
    void* pO = nullptr;
    cudaGetSymbolAddress(&pO, g_O);
    CUtensorMap tx32;
    HelpMaps hm;
    make_map(enc, &tx32, x, DM, SEQ, 64, 32);
    make_map(enc, &hm.x, x, DM, SEQ, 64, 192);
    make_map(enc, &hm.wqkv, wqkv, 3 * DM, DM, 64, 64);
    make_map(enc, &hm.O, pO, OK, SEQ, 64, 192);
    make_map(enc, &hm.O128, pO, OK, SEQ, 64, 128);
    make_map(enc, &hm.O64, pO, OK, SEQ, 64, 64);
    make_map(enc, &hm.Wo, Wo, DM, HD, 64, 64);
    make_map(enc, &hm.wo, wo, DM, DM, 64, 64);
    void* pQ = nullptr;
    cudaGetSymbolAddress(&pQ, g_qkvB);
    make_map(enc, &hm.qkv, pQ, 3 * DM, SEQ, 24, 128, CU_TENSOR_MAP_SWIZZLE_NONE);
    cudaFuncSetAttribute(k_rec, cudaFuncAttributeMaxDynamicSharedMemorySize, REC_SMEM);
    cudaFuncSetAttribute(k_help, cudaFuncAttributeMaxDynamicSharedMemorySize, HELP_SMEM);

    cudaStream_t st = cudaStreamPerThread;
    bool fast;
    int nsm = 132;
    cudaDeviceGetAttribute(&nsm, cudaDevAttrMultiProcessorCount, 0);
    {
        RecParams p{mem0, Wq, Wk, Wv, Wo, x, wqkv, 830, 230};
        cudaLaunchConfig_t cfg = {};
        cfg.gridDim = dim3(96); cfg.blockDim = dim3(384); cfg.dynamicSmemBytes = REC_SMEM; cfg.stream = st;
        cudaLaunchAttribute at[1];
        at[0].id = cudaLaunchAttributeClusterDimension;
        at[0].val.clusterDim.x = 3; at[0].val.clusterDim.y = 1; at[0].val.clusterDim.z = 1;
        cfg.attrs = at; cfg.numAttrs = 1;
        int ncl = 0;
        fast = cudaOccupancyMaxActiveClusters(&ncl, k_rec, &cfg) == cudaSuccess && ncl >= NH;
        if (fast) {
            cudaLaunchKernelEx(&cfg, k_rec, tx32, p);
        } else {
            fb_init<<<SEQ * DM / 256, 256, 0, st>>>(mem0);
            fb_proj<<<dim3(3 * HD / 256, SEQ / 8), 256, 0, st>>>(x, Wq, Wk, Wv, -1);
            for (int s = 0; s < NSEG; s++) {
                fb_proj<<<dim3(3 * HD / 128, 1), 128, 0, st>>>(x, Wq, Wk, Wv, s);
                if (s + 1 < NSEG) fb_attn<<<NH, 320, 0, st>>>(Wo, s);
            }
        }
    }
    {
        cudaLaunchConfig_t cfg = {};
        cfg.gridDim = dim3(nsm); cfg.blockDim = dim3(512); cfg.dynamicSmemBytes = HELP_SMEM; cfg.stream = st;
        cudaLaunchAttribute at[1];
        at[0].id = cudaLaunchAttributeProgrammaticStreamSerialization;
        at[0].val.programmaticStreamSerializationAllowed = 1;
        cfg.attrs = at; cfg.numAttrs = fast ? 1 : 0;
        cudaLaunchKernelEx(&cfg, k_help, hm, x, gw, out);
    }
}
```

```cpp
#include <cuda_runtime.h>
#include <cuda_bf16.h>
#include <cuda_fp16.h>
#include <cuda.h>
#include <stdint.h>

typedef __nv_bfloat16 bf16;

constexpr int SEQ = 2048, DM = 576, NH = 32, DH = 128, NSEG = 64;
constexpr int HD = NH * DH;
constexpr int OK = HD + DM;
constexpr int BH = 32, BD = 18;

__device__ bf16 g_O[SEQ * OK];
__device__ bf16 g_qkvB[SEQ * 3 * DM];
__device__ float g_acc[SEQ * DM];
__device__ float g_gate[SEQ];
__device__ float g_red[8 * 192 * 256];
__device__ uint4 g_redh[8 * 96 * 72];
__device__ unsigned g_sync[32];
__device__ unsigned g_ctr[1920];

__device__ __forceinline__ uint32_t s2u(const void* p) { return (uint32_t)__cvta_generic_to_shared(p); }
__device__ __forceinline__ uint32_t mapa(uint32_t a, uint32_t r) {
    uint32_t o; asm volatile("mapa.shared::cluster.u32 %0,%1,%2;" : "=r"(o) : "r"(a), "r"(r)); return o;
}
__device__ __forceinline__ void mbar_init(uint32_t a, int c) {
    asm volatile("mbarrier.init.shared::cta.b64 [%0],%1;" ::"r"(a), "r"(c) : "memory");
}
__device__ __forceinline__ void mbar_expect(uint32_t a, int bytes) {
    asm volatile("mbarrier.arrive.expect_tx.shared::cta.b64 _,[%0],%1;" ::"r"(a), "r"(bytes) : "memory");
}
__device__ __forceinline__ void mbar_arrive(uint32_t a) {
    asm volatile("mbarrier.arrive.shared::cta.b64 _,[%0];" ::"r"(a) : "memory");
}
__device__ __forceinline__ void mbar_wait(uint32_t a, int ph) {
    asm volatile("{.reg .pred p; .reg .u32 n; mov.u32 n,0;\n"
                 "WL%=: mbarrier.try_wait.parity.shared::cta.b64 p,[%0],%1; @p bra.uni WD%=;\n"
                 "add.u32 n,n,1; setp.lt.u32 p,n,4194304; @p bra.uni WL%=; trap;\n"
                 "WD%=: }" ::"r"(a), "r"(ph) : "memory");
}
__device__ __forceinline__ void bar_sync(int id, int n) { asm volatile("bar.sync %0,%1;" ::"r"(id), "r"(n) : "memory"); }
__device__ __forceinline__ void bar_arrive(int id, int n) { asm volatile("bar.arrive %0,%1;" ::"r"(id), "r"(n) : "memory"); }
__device__ __forceinline__ void cluster_sync() {
    asm volatile("barrier.cluster.arrive.release.aligned; barrier.cluster.wait.acquire.aligned;" ::: "memory");
}
__device__ __forceinline__ void cluster_sync_relaxed() {
    asm volatile("barrier.cluster.arrive.relaxed.aligned; barrier.cluster.wait.aligned;" ::: "memory");
}
__device__ __forceinline__ uint32_t lds32(uint32_t a) { uint32_t v; asm volatile("ld.shared.u32 %0,[%1];" : "=r"(v) : "r"(a) : "memory"); return v; }
__device__ __forceinline__ void fence_async() { asm volatile("fence.proxy.async.shared::cta;" ::: "memory"); }
__device__ __forceinline__ void ldsm4(uint32_t* r, uint32_t a) {
    asm volatile("ldmatrix.sync.aligned.m8n8.x4.shared.b16 {%0,%1,%2,%3},[%4];"
                 : "=r"(r[0]), "=r"(r[1]), "=r"(r[2]), "=r"(r[3]) : "r"(a) : "memory");
}
__device__ __forceinline__ void ldsm4t(uint32_t* r, uint32_t a) {
    asm volatile("ldmatrix.sync.aligned.m8n8.x4.trans.shared.b16 {%0,%1,%2,%3},[%4];"
                 : "=r"(r[0]), "=r"(r[1]), "=r"(r[2]), "=r"(r[3]) : "r"(a) : "memory");
}
__device__ __forceinline__ void ldsm2(uint32_t* r, uint32_t a) {
    asm volatile("ldmatrix.sync.aligned.m8n8.x2.shared.b16 {%0,%1},[%2];" : "=r"(r[0]), "=r"(r[1]) : "r"(a) : "memory");
}
__device__ __forceinline__ void ldsm2t(uint32_t* r, uint32_t a) {
    asm volatile("ldmatrix.sync.aligned.m8n8.x2.trans.shared.b16 {%0,%1},[%2];" : "=r"(r[0]), "=r"(r[1]) : "r"(a) : "memory");
}
__device__ __forceinline__ void mma16(float* c, const uint32_t* a, uint32_t b0, uint32_t b1) {
    asm("mma.sync.aligned.m16n8k16.row.col.f32.bf16.bf16.f32 {%0,%1,%2,%3},{%4,%5,%6,%7},{%8,%9},{%0,%1,%2,%3};"
                 : "+f"(c[0]), "+f"(c[1]), "+f"(c[2]), "+f"(c[3])
                 : "r"(a[0]), "r"(a[1]), "r"(a[2]), "r"(a[3]), "r"(b0), "r"(b1));
}
__device__ __forceinline__ void mma16v(float* c, const uint32_t* a, uint32_t b0, uint32_t b1) {
    asm volatile("mma.sync.aligned.m16n8k16.row.col.f32.bf16.bf16.f32 {%0,%1,%2,%3},{%4,%5,%6,%7},{%8,%9},{%0,%1,%2,%3};"
                 : "+f"(c[0]), "+f"(c[1]), "+f"(c[2]), "+f"(c[3])
                 : "r"(a[0]), "r"(a[1]), "r"(a[2]), "r"(a[3]), "r"(b0), "r"(b1));
}
__device__ __forceinline__ void mma8(float* c, uint32_t a0, uint32_t a1, uint32_t b0) {
    asm("mma.sync.aligned.m16n8k8.row.col.f32.bf16.bf16.f32 {%0,%1,%2,%3},{%4,%5},{%6},{%0,%1,%2,%3};"
                 : "+f"(c[0]), "+f"(c[1]), "+f"(c[2]), "+f"(c[3]) : "r"(a0), "r"(a1), "r"(b0));
}
__device__ __forceinline__ uint32_t pack2(float lo, float hi) {
    uint32_t r; asm("cvt.rn.bf16x2.f32 %0,%1,%2;" : "=r"(r) : "f"(hi), "f"(lo)); return r;
}
__device__ __forceinline__ float ex2(float x) { float y; asm("ex2.approx.ftz.f32 %0,%1;" : "=f"(y) : "f"(x)); return y; }
__device__ __forceinline__ void sts32(uint32_t a, uint32_t v) { asm volatile("st.shared.u32 [%0],%1;" ::"r"(a), "r"(v) : "memory"); }
__device__ __forceinline__ void sts128(uint32_t a, const uint32_t* v) {
    asm volatile("st.shared.v4.u32 [%0],{%1,%2,%3,%4};" ::"r"(a), "r"(v[0]), "r"(v[1]), "r"(v[2]), "r"(v[3]) : "memory");
}
__device__ __forceinline__ void lds128(uint32_t* v, uint32_t a) {
    asm volatile("ld.shared.v4.u32 {%0,%1,%2,%3},[%4];" : "=r"(v[0]), "=r"(v[1]), "=r"(v[2]), "=r"(v[3]) : "r"(a) : "memory");
}
__device__ __forceinline__ float2 lds64f(uint32_t a) {
    float2 v; asm volatile("ld.shared.v2.f32 {%0,%1},[%2];" : "=f"(v.x), "=f"(v.y) : "r"(a) : "memory"); return v;
}
__device__ __forceinline__ void tma2d(uint32_t dst, const CUtensorMap* m, int c0, int c1, uint32_t bar) {
    asm volatile("cp.async.bulk.tensor.2d.shared::cluster.global.mbarrier::complete_tx::bytes [%0],[%1,{%3,%4}],[%2];"
                 ::"r"(dst), "l"(m), "r"(bar), "r"(c0), "r"(c1) : "memory");
}
__device__ __forceinline__ void tma2d_mc(uint32_t dst, const CUtensorMap* m, int c0, int c1, uint32_t bar, uint16_t mask) {
    asm volatile("cp.async.bulk.tensor.2d.shared::cluster.global.mbarrier::complete_tx::bytes.multicast::cluster [%0],[%1,{%3,%4}],[%2],%5;"
                 ::"r"(dst), "l"(m), "r"(bar), "r"(c0), "r"(c1), "h"(mask) : "memory");
}
__device__ __forceinline__ uint64_t desc_sw128(uint32_t addr, uint32_t lbo, uint32_t sbo) {
    return (uint64_t)((addr & 0x3FFFF) >> 4) | ((uint64_t)(lbo >> 4) << 16) | ((uint64_t)(sbo >> 4) << 32) | (1ull << 62);
}
__device__ __forceinline__ void wg_fence() { asm volatile("wgmma.fence.sync.aligned;" ::: "memory"); }
__device__ __forceinline__ void wg_commit() { asm volatile("wgmma.commit_group.sync.aligned;" ::: "memory"); }
template <int N> __device__ __forceinline__ void wg_wait() { asm volatile("wgmma.wait_group.sync.aligned %0;" ::"n"(N) : "memory"); }

__device__ __forceinline__ void wgmma_rs_n32(float* d, const uint32_t* a, uint32_t dlo, int acc) {
    asm volatile("{.reg .pred p; .reg .b64 dd; setp.ne.b32 p,%21,0; mov.b64 dd,{%20,0x40000040};\n"
                 "wgmma.mma_async.sync.aligned.m64n32k16.f32.bf16.bf16 "
                 "{%0,%1,%2,%3,%4,%5,%6,%7,%8,%9,%10,%11,%12,%13,%14,%15},{%16,%17,%18,%19},dd,p,1,1,0;}"
                 : "+f"(d[0]), "+f"(d[1]), "+f"(d[2]), "+f"(d[3]), "+f"(d[4]), "+f"(d[5]), "+f"(d[6]), "+f"(d[7]),
                   "+f"(d[8]), "+f"(d[9]), "+f"(d[10]), "+f"(d[11]), "+f"(d[12]), "+f"(d[13]), "+f"(d[14]), "+f"(d[15])
                 : "r"(a[0]), "r"(a[1]), "r"(a[2]), "r"(a[3]), "r"(dlo), "r"(acc));
}

__device__ __forceinline__ void wgmma_ss_n32(float* d, uint32_t alo, uint32_t dlo, int acc) {
    asm volatile("{.reg .pred p; .reg .b64 da,dd; setp.ne.b32 p,%18,0; mov.b64 da,{%16,0x00000008}; mov.b64 dd,{%17,0x40000040};\n"
                 "wgmma.mma_async.sync.aligned.m64n32k16.f32.bf16.bf16 "
                 "{%0,%1,%2,%3,%4,%5,%6,%7,%8,%9,%10,%11,%12,%13,%14,%15},da,dd,p,1,1,0,0;}"
                 : "+f"(d[0]), "+f"(d[1]), "+f"(d[2]), "+f"(d[3]), "+f"(d[4]), "+f"(d[5]), "+f"(d[6]), "+f"(d[7]),
                   "+f"(d[8]), "+f"(d[9]), "+f"(d[10]), "+f"(d[11]), "+f"(d[12]), "+f"(d[13]), "+f"(d[14]), "+f"(d[15])
                 : "r"(alo), "r"(dlo), "r"(acc));
}

#define R8(b) "+f"(d[b]), "+f"(d[b + 1]), "+f"(d[b + 2]), "+f"(d[b + 3]), "+f"(d[b + 4]), "+f"(d[b + 5]), "+f"(d[b + 6]), "+f"(d[b + 7])
__device__ __forceinline__ void wgmma_ss_n192(float* d, uint64_t da, uint64_t db, int acc) {
    asm volatile("{.reg .pred p; setp.ne.b32 p,%98,0;\n"
                 "wgmma.mma_async.sync.aligned.m64n192k16.f32.bf16.bf16 "
                 "{%0,%1,%2,%3,%4,%5,%6,%7,%8,%9,%10,%11,%12,%13,%14,%15,%16,%17,%18,%19,%20,%21,%22,%23,"
                 "%24,%25,%26,%27,%28,%29,%30,%31,%32,%33,%34,%35,%36,%37,%38,%39,%40,%41,%42,%43,%44,%45,%46,%47,"
                 "%48,%49,%50,%51,%52,%53,%54,%55,%56,%57,%58,%59,%60,%61,%62,%63,%64,%65,%66,%67,%68,%69,%70,%71,"
                 "%72,%73,%74,%75,%76,%77,%78,%79,%80,%81,%82,%83,%84,%85,%86,%87,%88,%89,%90,%91,%92,%93,%94,%95},"
                 "%96,%97,p,1,1,0,1;}"
                 : R8(0), R8(8), R8(16), R8(24), R8(32), R8(40), R8(48), R8(56), R8(64), R8(72), R8(80), R8(88)
                 : "l"(da), "l"(db), "r"(acc));
}

__device__ __forceinline__ void wgmma_ss_n96(float* d, uint64_t da, uint64_t db) {
    asm volatile("wgmma.mma_async.sync.aligned.m64n96k16.f32.bf16.bf16 "
                 "{%0,%1,%2,%3,%4,%5,%6,%7,%8,%9,%10,%11,%12,%13,%14,%15,%16,%17,%18,%19,%20,%21,%22,%23,"
                 "%24,%25,%26,%27,%28,%29,%30,%31,%32,%33,%34,%35,%36,%37,%38,%39,%40,%41,%42,%43,%44,%45,%46,%47},%48,%49,1,1,1,0,1;"
                 : R8(0), R8(8), R8(16), R8(24), R8(32), R8(40) : "l"(da), "l"(db));
}
__device__ __forceinline__ void wgmma_ss_n64(float* d, uint64_t da, uint64_t db) {
    asm volatile("wgmma.mma_async.sync.aligned.m64n64k16.f32.bf16.bf16 "
                 "{%0,%1,%2,%3,%4,%5,%6,%7,%8,%9,%10,%11,%12,%13,%14,%15,%16,%17,%18,%19,%20,%21,%22,%23,"
                 "%24,%25,%26,%27,%28,%29,%30,%31},%32,%33,1,1,1,0,1;"
                 : R8(0), R8(8), R8(16), R8(24) : "l"(da), "l"(db));
}

constexpr int NSS = 1;
constexpr int QCH = 4, QD = 4;
constexpr int WRES = 2, WO_PRE2 = 3, WO_PRE3 = 4;
constexpr int MP = 1168;
constexpr int XT = 36864;
constexpr int XR_STAGE = 14 * 1024;
constexpr int MR_STAGE = 14 * 256;
constexpr int SM_X = 0;
constexpr int SM_XR = 2 * XT;
constexpr int SM_MR = SM_XR + 3 * XR_STAGE;
constexpr int SM_MEM = SM_XR + 2 * XT;
constexpr int SM_SC = SM_MEM + 8 * MP;
constexpr int SM_OB = SM_SC + 3 * 1536;
constexpr int SM_ZERO = SM_OB + 2048;
constexpr int SM_WO = SM_ZERO + 512;
constexpr int SM_WS = SM_WO + 49152;
constexpr int SM_BAR = SM_WS + NSS * 4096;
constexpr int REC_SMEM = SM_BAR + 128 + 1024;

__device__ uint4 g_xr[NSEG * NH * 24 * 64];
__device__ uint4 g_mr[NSEG * NH * 16 * 16];
__device__ unsigned g_flagA[NSEG];

constexpr unsigned long long FSP = 0x111123564ull;
__host__ __device__ constexpr int f_split(int m) { return m < 3 ? 1 : (int)((FSP >> (4 * (11 - m))) & 15); }
constexpr int F_FIRST_SPLIT = f_split(3) > 1 ? 3 : (f_split(4) > 1 ? 4 : (f_split(5) > 1 ? 5 : (f_split(6) > 1 ? 6 : 7)));
struct RecMaps { CUtensorMap w[2][3], wo; };
struct RecParams {
    const bf16* mem0; const bf16* Wq; const bf16* Wk; const bf16* Wv;
    int d0, dv;
};

__device__ __forceinline__ float* red_line(int s, int line) { return g_red + ((s >> 3) * 192 + line) * 256 + (s & 7) * 32; }

#define PIN(x) asm volatile("" : "+r"(x))
#define PINL(x) asm volatile("" : "+l"(x))
__device__ __forceinline__ float4 ld_relaxed4(const float* q) {
    float4 v;
    asm volatile("ld.relaxed.gpu.global.v4.f32 {%0,%1,%2,%3},[%4];" : "=f"(v.x), "=f"(v.y), "=f"(v.z), "=f"(v.w) : "l"(q) : "memory");
    return v;
}
__device__ __forceinline__ unsigned ld_acq(const unsigned* q) {
    unsigned v; asm volatile("ld.acquire.gpu.global.u32 %0,[%1];" : "=r"(v) : "l"(q) : "memory"); return v;
}
__device__ __forceinline__ unsigned ld_relaxed1(const unsigned* q) {
    unsigned v; asm volatile("ld.relaxed.gpu.global.u32 %0,[%1];" : "=r"(v) : "l"(q) : "memory"); return v;
}
__device__ __forceinline__ uint4 ld_relaxed4u(const uint4* q) {
    uint4 v;
    asm volatile("ld.relaxed.gpu.global.v4.u32 {%0,%1,%2,%3},[%4];" : "=r"(v.x), "=r"(v.y), "=r"(v.z), "=r"(v.w) : "l"(q) : "memory");
    return v;
}
__device__ __forceinline__ void reld_relaxed4u(uint4& v, const uint4* q) {
    asm volatile("{.reg .pred p; .reg .b32 q; and.b32 q,%3,0xffff; setp.ne.u32 p,q,0x5000;\n"
                 "@p ld.relaxed.gpu.global.v4.u32 {%0,%1,%2,%3},[%4];}"
                 : "+r"(v.x), "+r"(v.y), "+r"(v.z), "+r"(v.w) : "l"(q) : "memory");
}
__device__ __forceinline__ uint32_t packh2(float lo, float hi) {
    uint32_t r; asm("cvt.rn.f16x2.f32 %0,%1,%2;" : "=r"(r) : "f"(hi), "f"(lo)); return r;
}
__device__ __forceinline__ float maxn(float a, float b) {
    float r; asm("max.NaN.f32 %0,%1,%2;" : "=f"(r) : "f"(fabsf(a)), "f"(fabsf(b))); return r;
}
__device__ __forceinline__ void redh4(uint4* q, const float* v, uint32_t tag) {
    asm volatile("red.relaxed.gpu.global.add.noftz.v4.f16x2 [%0],{%1,%2,%3,%4};"
                 ::"l"(q), "r"(packh2(v[0], v[1])), "r"(packh2(v[2], v[3])), "r"(packh2(v[4], v[5])), "r"(tag) : "memory");
}
__device__ __forceinline__ void red4(float* q, float a, float b, float c2, float d) {
    asm volatile("red.relaxed.gpu.global.add.v4.f32 [%0],{%1,%2,%3,%4};" ::"l"(q), "f"(a), "f"(b), "f"(c2), "f"(d) : "memory");
}
__device__ __forceinline__ unsigned clk32() { return (unsigned)clock64(); }
__device__ __forceinline__ void spin_until(unsigned tl) {
    asm volatile("{.reg .pred p; .reg .u64 c; .reg .u32 lo,hi; .reg .s32 d;\n"
                 "SP%=: mov.u64 c,%%clock64; mov.b64 {lo,hi},c; sub.s32 d,lo,%0; setp.lt.s32 p,d,0; @p bra.uni SP%=;}" ::"r"(tl) : "memory");
}
__device__ __forceinline__ float rcp_fast(float x) { float y; asm("rcp.approx.ftz.f32 %0,%1;" : "=f"(y) : "f"(x)); return y; }
__device__ __forceinline__ void bulk_store(void* gdst, uint32_t src, int bytes) {
    asm volatile("cp.async.bulk.global.shared::cta.bulk_group [%0],[%1],%2;" ::"l"(gdst), "r"(src), "r"(bytes) : "memory");
}
__device__ __forceinline__ void bulk_load(uint32_t dst, const void* gsrc, int bytes, uint32_t bar) {
    asm volatile("cp.async.bulk.shared::cluster.global.mbarrier::complete_tx::bytes [%0],[%1],%2,[%3];"
                 ::"r"(dst), "l"(gsrc), "r"(bytes), "r"(bar) : "memory");
}
__device__ __forceinline__ void bulk_s2s(uint32_t rdst, uint32_t src, int bytes, uint32_t rbar) {
    asm volatile("cp.async.bulk.shared::cluster.shared::cta.mbarrier::complete_tx::bytes [%0],[%1],%2,[%3];"
                 ::"r"(rdst), "r"(src), "r"(bytes), "r"(rbar) : "memory");
}
__device__ __forceinline__ void stas4(uint32_t rdst, uint32_t a, uint32_t b, uint32_t c2, uint32_t d, uint32_t rbar) {
    asm volatile("st.async.weak.shared::cluster.mbarrier::complete_tx::bytes.v4.b32 [%0],{%1,%2,%3,%4},[%5];"
                 ::"r"(rdst), "r"(a), "r"(b), "r"(c2), "r"(d), "r"(rbar) : "memory");
}
__device__ __forceinline__ void stas2(uint32_t rdst, uint32_t a, uint32_t b, uint32_t rbar) {
    asm volatile("st.async.weak.shared::cluster.mbarrier::complete_tx::bytes.v2.b32 [%0],{%1,%2},[%3];"
                 ::"r"(rdst), "r"(a), "r"(b), "r"(rbar) : "memory");
}
__device__ __forceinline__ float4 lds128f(uint32_t a) {
    float4 v; asm volatile("ld.shared.v4.f32 {%0,%1,%2,%3},[%4];" : "=f"(v.x), "=f"(v.y), "=f"(v.z), "=f"(v.w) : "r"(a) : "memory"); return v;
}

__device__ __forceinline__ void flag_seg(int seg) {
    asm volatile("cp.async.bulk.wait_group 0;" ::: "memory");
    asm volatile("red.relaxed.gpu.global.add.u32 [%0],1;" ::"l"(g_flagA + seg) : "memory");
}

__global__ void __launch_bounds__(384, 1) k_rec(const __grid_constant__ CUtensorMap tmx, const __grid_constant__ RecMaps rm, const RecParams p) {
    extern __shared__ uint8_t smem_raw[];
    const uint32_t sb = (s2u(smem_raw) + 1023) & ~1023u;
    const int tid = threadIdx.x, warp = __shfl_sync(0xffffffffu, tid >> 5, 0), lane = tid & 31, g = lane >> 2, t = lane & 3;
    const int l7 = lane & 7, l3 = lane >> 3;
    const int c = blockIdx.x % 3, h = blockIdx.x / 3;
    const int nq = c < 2 ? 3 : 2, nv = 8 - 2 * nq, v0 = 2 * c;
    const uint32_t bXF = sb + SM_BAR, bVX = bXF + 16, bS = bVX + 16, bV = bS + 8, bW = bV + 8;
    const uint32_t peer1 = (c + 1) % 3, peer2 = (c + 2) % 3;
    auto vslot = [](int r, int d) { return (r < 2 ? 6 : 4) + ((d - 2 * r) & 7); };

    if (blockIdx.x == 0) {
        for (int i = tid; i < 1920; i += 384) g_ctr[i] = 0;
        if (tid < NSEG) g_flagA[tid] = 0;
        __threadfence();
        __syncthreads();
    }
    asm volatile("griddepcontrol.launch_dependents;" ::: "memory");
    auto wbox = [&](int ch, int ty) {
        tma2d(sb + SM_XR + (ch & 1) * XT + ty * nq * 4608, &rm.w[c == 2][ty], h * DH + c * (ty == 2 ? 32 : 48), ch * 144, bW + 8 * (ch & 1));
    };
    if (lane == 0 && warp >= 1 && warp < 6)
        asm volatile("prefetch.tensormap [%0];" ::"l"(warp < 4 ? &rm.w[c == 2][warp - 1] : (warp == 4 ? &rm.wo : &tmx)) : "memory");
    if (tid == 0) {
        for (int i = 0; i < 2; i++) { mbar_init(bXF + 8 * i, 1); mbar_init(bVX + 8 * i, 1); mbar_init(bW + 8 * i, 1); }
        mbar_init(bS, 4); mbar_init(bV, nv + 1); mbar_init(bW + 16, 1);
        asm volatile("fence.mbarrier_init.release.cluster;" ::: "memory");
        for (int i = 0; i < 2; i++) { mbar_expect(bW + 8 * i, XT); mbar_expect(bXF + 8 * i, XT); mbar_expect(bVX + 8 * i, (8 - nv) * 1024); }
        mbar_expect(bW + 16, 49152); mbar_expect(bS, 2560); mbar_expect(bV, (8 - nv) * 256);
    }
    __syncthreads();
    if (lane == 0) {
        if (warp >= 1 && warp < 4) { wbox(0, warp - 1); wbox(1, warp - 1); }
        if (warp == 4) tma2d(sb + SM_WO, &rm.wo, c * 192, h * DH, bW + 16);
        if (warp >= 5 && warp < 8) {
            const bf16* W = warp == 5 ? p.Wq : (warp == 6 ? p.Wk : p.Wv);
            asm volatile("cp.async.bulk.prefetch.L2.global [%0],24576;" ::"l"(reinterpret_cast<const uint8_t*>(W) + (size_t)(96 + blockIdx.x) * 24576) : "memory");
        }
    }
    __syncwarp();
    cluster_sync_relaxed();

    if (warp < 8) {
        asm volatile("setmaxnreg.inc.sync.aligned.u32 %0;" ::"n"(184));
        const bool isv = warp >= 2 * nq;
        const int slot = warp;
        uint32_t w[36][4];
        {
            const uint32_t pitch = (isv ? nv : nq) * 32;
            const uint32_t src = sb + SM_XR + (isv ? nq * 9216 + (warp - 2 * nq) * 32 : (warp >= nq ? nq * 4608 + (warp - nq) * 32 : warp * 32)) + 2 * t * pitch + g * 4;
#pragma unroll
            for (int ch = 0; ch < 4; ch++) {
                mbar_wait(bW + 8 * (ch & 1), ch >> 1);
#pragma unroll
                for (int kk = 0; kk < 9; kk++) {
                    const uint32_t q = src + (ch & 1) * XT + kk * 16 * pitch;
                    const uint32_t a = lds32(q), b = lds32(q + pitch), d = lds32(q + 8 * pitch), e = lds32(q + 9 * pitch);
                    uint32_t* o = w[ch * 9 + kk];
                    o[0] = __byte_perm(a, b, 0x5410); o[1] = __byte_perm(a, b, 0x7632);
                    o[2] = __byte_perm(d, e, 0x5410); o[3] = __byte_perm(d, e, 0x7632);
                }
                if (ch < 2) {
                    bar_sync(9, 256);
                    if (tid == 0) mbar_expect(bW + 8 * ch, XT);
                    if (lane == 0 && warp >= 1 && warp < 4) wbox(ch + 2, warp - 1);
                    __syncwarp();
                }
            }
#pragma unroll
            for (int k = 0; k < NSS; k++) {
                const uint32_t a = sb + SM_WS + k * 4096 + (warp >> 2) * 2048 + (warp & 3) * 256 + lane * 4;
                sts32(a, w[36 - NSS + k][0]); sts32(a + 128, w[36 - NSS + k][1]);
                sts32(a + 1024, w[36 - NSS + k][2]); sts32(a + 1152, w[36 - NSS + k][3]);
            }
            fence_async();
            bar_sync(9, 256);
            asm volatile("barrier.cluster.arrive.relaxed.aligned;" ::: "memory");
        }
        const uint32_t wsd = (((sb + SM_WS + (warp >> 2) * 2048) & 0x3FFFF) >> 4) | (64u << 16);
        const uint32_t woff = 2 * t * 32 + (((g >> 2) ^ (t >> 1)) << 4) + (g & 3) * 4;

        float d[16];
        auto xdesc = [&](int sl) { return __shfl_sync(0xffffffffu, (((sb + SM_X + sl * XT) & 0x3FFFF) >> 4) | 0x10000u, 0); };
        auto filler = [&](uint32_t xd, int stg) {
            wg_fence();
#pragma unroll
            for (int k = 36 - NSS; k < 36; k++) wgmma_ss_n32(d, wsd + (k - 36 + NSS) * 256, xd + ((k >> 2) * 256 + (k & 3) * 2), k > 36 - NSS);
#pragma unroll
            for (int k = 0; k < 36 - NSS; k++) wgmma_rs_n32(d, w[k], xd + ((k >> 2) * 256 + (k & 3) * 2), 1);
            wg_commit();
            wg_wait<0>();
            const uint32_t dst = sb + SM_XR + stg * XR_STAGE + slot * 1024 + woff;
#pragma unroll
            for (int j = 0; j < 4; j++) {
                sts32(dst + j * 256, pack2(d[4 * j], d[4 * j + 2]));
                sts32(dst + j * 256 + 32, pack2(d[4 * j + 1], d[4 * j + 3]));
            }
        };
        auto fwd_v = [&](int sl, int stg) {
            const uint32_t base = sb + SM_XR + stg * XR_STAGE;
            bulk_s2s(mapa(base + vslot(peer1, v0) * 1024, peer1), base + 2 * nq * 1024, nv * 1024, mapa(bVX + 8 * sl, peer1));
            bulk_s2s(mapa(base + vslot(peer2, v0) * 1024, peer2), base + 2 * nq * 1024, nv * 1024, mapa(bVX + 8 * sl, peer2));
        };

        mbar_wait(bXF, 0);
        filler(xdesc(0), 0);
        fence_async();
        bar_arrive(7, 288);
        bar_sync(9, 256);
        asm volatile("barrier.cluster.wait.aligned;" ::: "memory");
        if (tid == 32) fwd_v(0, 0);
        __syncwarp();
        mbar_wait(bXF + 8, 0);
        filler(xdesc(1), 1);
        bar_sync(9, 256);
        if (tid == 0) { mbar_expect(bXF, XT); mbar_expect(bXF + 8, XT); }
        cluster_sync_relaxed();
        if (tid == 0) {
            for (int sl = 0; sl < 2; sl++)
                for (int j = 0; j < 3; j++)
                    tma2d_mc(sb + SM_X + sl * XT + (c * 3 + j) * 4096, &tmx, (c * 3 + j) * 64, (2 + sl) * 32, bXF + 8 * sl, 7);
        }
        __syncwarp();
        uint32_t mema = sb + SM_MEM + l7 * MP + l3 * 16;
        const uint32_t xpeer = (g & 2) ? peer2 : peer1;
        const uint32_t rdst0 = mapa(sb + SM_MR + vslot(xpeer, v0 + warp - 2 * nq) * 256 + (2 * t + (g & 1)) * 32 + (((g >> 2) ^ (t >> 1)) << 4), xpeer);
        uint32_t rbar = mapa(bV, xpeer);
        int s3 = 0;
        for (int s = 0; s < NSEG; s++) {
            const int st = s & 1, s3n = s3 == 2 ? 0 : s3 + 1, s3p = s3 == 0 ? 2 : s3 - 1;
            uint32_t rdst = rdst0 + s3 * MR_STAGE;
            uint32_t ldst = sb + SM_MR + s3 * MR_STAGE + slot * 256 + woff;
            PIN(rdst); PIN(rbar); PIN(ldst); PIN(mema);
            float a[QCH][4];
#pragma unroll
            for (int i = 0; i < QCH; i++) { a[i][0] = 0.f; a[i][1] = 0.f; a[i][2] = 0.f; a[i][3] = 0.f; }
            uint32_t wx[NSS][4];
#pragma unroll
            for (int k = 0; k < NSS; k++)
                ldsm4(wx[k], sb + SM_WS + k * 4096 + (warp >> 2) * 2048 + (warp & 3) * 256 + (l3 >> 1) * 1024 + (l3 & 1) * 128 + l7 * 16);
            bar_sync(1, 384);
            if (isv) spin_until(clk32() + p.dv);
            uint32_t bf[18][4];
#pragma unroll
            for (int ii = 0; ii < QD; ii++) ldsm4(bf[17 - ii], mema + (17 - ii) * 64);
#pragma unroll
            for (int ii = 0; ii < 18; ii++) {
                const int i = 17 - ii;
                mma16v(a[(2 * i) % QCH], 2 * i >= 36 - NSS ? wx[2 * i - 36 + NSS] : w[2 * i], bf[i][0], bf[i][1]);
                mma16v(a[(2 * i + 1) % QCH], 2 * i + 1 >= 36 - NSS ? wx[2 * i + 1 - 36 + NSS] : w[2 * i + 1], bf[i][2], bf[i][3]);
                if (i - QD >= 0) ldsm4(bf[i - QD], mema + (i - QD) * 64);
            }
#pragma unroll
            for (int i = 0; i < 4; i++) {
                a[0][i] = (a[2][i] + a[3][i]) + (a[0][i] + a[1][i]);
            }
            const uint32_t w0 = pack2(a[0][0], a[0][2]), w1 = pack2(a[0][1], a[0][3]);
            sts32(ldst, w0); sts32(ldst + 32, w1);
            if (!isv) bar_arrive(8, nq * 64 + 96);
            if (isv && s + 1 < NSEG) {
                uint32_t snd = (g & 1) ? w0 : w1, keep = (g & 1) ? w1 : w0;
                uint32_t rcv = __shfl_xor_sync(0xffffffffu, snd, 4);
                uint32_t lo = (g & 1) ? rcv : keep, hi = (g & 1) ? keep : rcv;
                uint32_t olo = __shfl_xor_sync(0xffffffffu, lo, 8), ohi = __shfl_xor_sync(0xffffffffu, hi, 8);
                stas4(rdst, (g & 2) ? olo : lo, (g & 2) ? ohi : hi, (g & 2) ? lo : olo, (g & 2) ? hi : ohi, rbar);
                __syncwarp();
                if (lane == 0) mbar_arrive(bV);
            }
            const uint32_t xd = xdesc(st);
            if (s + 2 < NSEG) {
                mbar_wait(bXF + 8 * st, ((s + 2) >> 1) & 1);
            }
            fence_async();
            bar_arrive(7, 288);
            if (warp == 1) bar_sync(6, 256); else bar_arrive(6, 256);
            if (warp < 2) {
                if (s + 1 < NSEG) { mbar_wait(bS, st); mbar_wait(bV, st); }
                if (lane == 0) {
                    if (warp == 0) {
                        if (s >= 1 && s + 3 < NSEG) {
                            mbar_expect(bXF + 8 * (st ^ 1), XT);
                            for (int j = 0; j < 3; j++)
                                tma2d_mc(sb + SM_X + (st ^ 1) * XT + (c * 3 + j) * 4096, &tmx, (c * 3 + j) * 64, (s + 3) * 32, bXF + 8 * (st ^ 1), 7);
                        }
                    } else {
                        if (s >= 1) flag_seg(s - 1);
                        bulk_store(reinterpret_cast<uint8_t*>(g_mr) + (size_t)(s * 32 + h) * 4096 + c * 1280,
                                   sb + SM_MR + s3 * MR_STAGE + nq * 256, (8 - nq) * 256);
                        asm volatile("cp.async.bulk.commit_group;" ::: "memory");
                        if (s + 2 < NSEG) fwd_v(st ^ 1, s3n);
                    }
                }
                __syncwarp();
            }
            if (s + 2 < NSEG) {
                bar_sync(5, 384);
                filler(xd, s3p);
            } else {
                bar_sync(5, 384);
            }
            s3 = s3n;
        }
        if (tid == 32) flag_seg(NSEG - 1);
    } else {
        asm volatile("setmaxnreg.dec.sync.aligned.u32 %0;" ::"n"(136));
        const int wq = warp - 8, wt = tid - 256;
        uint32_t woa = sb + SM_WO + wt * 16;
        uint32_t am0 = 0;
        {
            for (int i = wt; i < 576; i += 128) g_redh[blockIdx.x * 576 + i] = make_uint4(0u, 0u, 0u, 0u);
            float4* z = reinterpret_cast<float4*>(g_red) + blockIdx.x * 1024;
            for (int i = wt; i < 1024; i += 128) z[i] = make_float4(0.f, 0.f, 0.f, 0.f);
            constexpr int ZN = (SEQ - F_FIRST_SPLIT * 192) * (DM / 4) / 96;
            float4* za = reinterpret_cast<float4*>(g_acc + F_FIRST_SPLIT * 192 * DM) + blockIdx.x * ZN;
            for (int i = wt; i < ZN; i += 128) za[i] = make_float4(0.f, 0.f, 0.f, 0.f);
            if (wt == 96) {
                for (int sl = 0; sl < 2; sl++)
                    for (int j = 0; j < 3; j++)
                        tma2d_mc(sb + SM_X + sl * XT + (c * 3 + j) * 4096, &tmx, (c * 3 + j) * 64, sl * 32, bXF + 8 * sl, 7);
            }
            __syncwarp();
        }
        {
            asm volatile("barrier.cluster.arrive.relaxed.aligned;" ::: "memory");
            uint32_t wo[24][4];
            mbar_wait(bW + 16, 0);
#pragma unroll
            for (int k = 0; k < 24; k++) {
                const uint32_t q = sb + SM_WO + ((k & 7) * 16 + 2 * t) * 384 + (k >> 3) * 128 + wq * 32 + g * 4;
                wo[k][0] = lds32(q); wo[k][1] = lds32(q + 384); wo[k][2] = lds32(q + 8 * 384); wo[k][3] = lds32(q + 9 * 384);
            }
            bar_sync(4, 128);
#pragma unroll
            for (int k = 0; k < 24; k++) {
                uint32_t a = wo[k][0], b = wo[k][1], d = wo[k][2], e = wo[k][3];
                wo[k][0] = __byte_perm(a, b, 0x5410); wo[k][1] = __byte_perm(a, b, 0x7632);
                wo[k][2] = __byte_perm(d, e, 0x5410); wo[k][3] = __byte_perm(d, e, 0x7632);
                sts128(woa + k * 2048, wo[k]);
            }
            sts32(sb + SM_ZERO + wt * 4, 0u);
            for (int i = wt; i < 8 * 72; i += 128) {
                const int r = i / 72, cc = i % 72;
                uint4 v = __ldg(reinterpret_cast<const uint4*>(p.mem0 + r * DM) + cc);
                am0 = __vmaxu2(__vmaxu2(am0, __vmaxu2(v.x & 0x7fff7fffu, v.y & 0x7fff7fffu)), __vmaxu2(v.z & 0x7fff7fffu, v.w & 0x7fff7fffu));
                asm volatile("st.shared.v4.u32 [%0],{%1,%2,%3,%4};" ::"r"(sb + SM_MEM + r * MP + cc * 16), "r"(v.x), "r"(v.y), "r"(v.z), "r"(v.w) : "memory");
            }
        }
        __threadfence();
        bar_sync(4, 128);
        if (wt == 0) asm volatile("red.relaxed.gpu.global.add.u32 [%0],1;" ::"l"(g_sync) : "memory");
        asm volatile("barrier.cluster.wait.aligned;" ::: "memory");
        cluster_sync_relaxed();
        bar_arrive(1, 384);
        if (wq == 3) bar_sync(7, 288);
        uint32_t wa[8][4], wb[8][4], wc[WRES + 1][4];
#pragma unroll
        for (int k = 0; k < 8; k++) lds128(wa[k], woa + k * 2048);
#pragma unroll
        for (int k = 0; k < 8; k++) lds128(wb[k], woa + (8 + k) * 2048);
#pragma unroll
        for (int k = 0; k < WRES; k++) lds128(wc[k], woa + (16 + k) * 2048);

        int ex;
        {
            const uint32_t m = __reduce_max_sync(0xffffffffu, max(am0 & 0xffffu, am0 >> 16));
            ex = m ? min(max(4 - ((int)(m >> 7) - 127), -60), 60) : 0;
        }
        const float SC = 0.08838834764831845f * 1.4426950408889634f;
        uint32_t L16 = lane * 16;
        uint32_t AB = (l3 >> 1) * 256 + l7 * 32 + (((l3 & 1) ^ (l7 >> 2)) << 4);
        uint32_t AA = (l3 & 1) * 256 + l7 * 32 + (((l3 >> 1) ^ (l7 >> 2)) << 4);
        const uint32_t scu = sb + SM_SC + c * 1536 + (wq == 0 ? 1024 : (wq - 1) * 512);
        const uint32_t sc1 = mapa(scu, peer1), sc2 = mapa(scu, peer2), sb1 = mapa(bS, peer1), sb2 = mapa(bS, peer2);
        const uint32_t wou = sb + SM_WO + wq * 512;
        const int vs = vslot(c, 2 * wq);
        auto publish = [&](int xs, int stg) {
            if (xs >= 1) flag_seg(xs - 1);
            if (xs < NSEG) {
                bulk_store(reinterpret_cast<uint8_t*>(g_xr) + (size_t)(xs * 96 + blockIdx.x) * 8192, sb + SM_XR + stg * XR_STAGE, 8192);
                asm volatile("cp.async.bulk.commit_group;" ::: "memory");
            }
        };
        int s3 = 0;
        for (int s = 0; s + 1 < NSEG; s++) {
            const int st = s & 1;
            const uint32_t xr = sb + SM_XR + s3 * XR_STAGE, mr = sb + SM_MR + s3 * MR_STAGE;
            PIN(L16); PIN(AB); PIN(AA);
            if (wq < 3) {
                uint32_t kf[3][4], q0[4], q1[4];
                float ca[4] = {0.f, 0.f, 0.f, 0.f}, cb[4] = {0.f, 0.f, 0.f, 0.f}, cc[4] = {0.f, 0.f, 0.f, 0.f};
                if (wq) {
                    const uint32_t ka = xr + nq * 1024 + (wq - 1) * 512 + AB;
                    ldsm4(kf[0], ka); ldsm4(kf[1], ka + 1024); ldsm4(kf[2], nq == 3 ? ka + 2048 : sb + SM_ZERO + AB);
                    uint32_t da1 = sc1 + L16, da2 = sc2 + L16, qa = mr + AA;
                    PIN(da1); PIN(da2); PIN(qa);
                    bar_sync(8, nq * 64 + 96);
                    ldsm4(q0, qa); ldsm4(q1, qa + 512);
                    float da[4] = {0.f, 0.f, 0.f, 0.f}, db[4] = {0.f, 0.f, 0.f, 0.f}, dc[4] = {0.f, 0.f, 0.f, 0.f};
                    mma16(ca, q0, kf[0][0], kf[0][1]); mma16(da, q0, kf[0][2], kf[0][3]);
                    mma16(cb, q0, kf[1][0], kf[1][1]); mma16(db, q0, kf[1][2], kf[1][3]);
                    mma16(cc, q1, kf[2][0], kf[2][1]); mma16(dc, q1, kf[2][2], kf[2][3]);
                    const uint32_t rr[4] = {__float_as_uint((ca[0] + cb[2]) + cc[0]), __float_as_uint((ca[1] + cb[3]) + cc[1]),
                                            __float_as_uint((da[0] + db[2]) + dc[0]), __float_as_uint((da[1] + db[3]) + dc[1])};
                    stas4(da1, rr[0], rr[1], rr[2], rr[3], sb1); stas4(da2, rr[0], rr[1], rr[2], rr[3], sb2);
                    sts128(scu + L16, rr);
                } else {
                    uint32_t da1 = sc1 + (L16 >> 1), da2 = sc2 + (L16 >> 1), qa = mr + AA, ka = mr + nq * 256 + AB;
                    uint32_t kb = nq == 3 ? ka + 512 : sb + SM_ZERO + AB;
                    PIN(da1); PIN(da2); PIN(qa); PIN(ka); PIN(kb);
                    bar_sync(8, nq * 64 + 96);
                    ldsm4(q0, qa); ldsm4(kf[0], ka); ldsm4(q1, qa + 512); ldsm2(kf[1], kb);
                    mma16(ca, q0, kf[0][0], kf[0][1]); mma16(cb, q0, kf[0][2], kf[0][3]); mma16(cc, q1, kf[1][0], kf[1][1]);
                    const uint32_t r0 = __float_as_uint((ca[0] + cb[2]) + cc[0]), r1 = __float_as_uint((ca[1] + cb[3]) + cc[1]);
                    stas2(da1, r0, r1, sb1); stas2(da2, r0, r1, sb2);
                    asm volatile("st.shared.v2.u32 [%0],{%1,%2};" ::"r"(scu + (L16 >> 1)), "r"(r0), "r"(r1) : "memory");
                }
                __syncwarp();
                if (L16 == 0) mbar_arrive(bS);
            } else {
                if (lane == 0) {
                    if (s >= 1 && s + 4 < NSEG)
                        asm volatile("prefetch.global.L2 [%0];" ::"l"(g_redh + (((s + 3) >> 3) * 96 + blockIdx.x) * 72 + ((s + 3) & 7) * 8));
                    publish(s, s3);
                    if (s == 0) {
                        int it = 0;
                        while (ld_acq(g_sync) < 96) { if (++it > (1 << 22)) __trap(); }
                    }
                }
                __syncwarp();
            }
            uint32_t va[2][2][4], vb[4];
            mbar_wait(bVX + 8 * st, (s >> 1) & 1);
            const uint32_t v0a = xr + vs * 1024 + AB;
            ldsm4t(va[0][0], v0a); ldsm4t(va[1][0], v0a + 1024);
            uint4* rl = g_redh + (((s >> 3) * 96 + c * 32 + wq * 4) * 9 + (s & 7)) * 8 + (L16 >> 7) * 72 + ((L16 >> 4) & 7);
            PINL(rl);
            mbar_wait(bS, s & 1);
            float4 sa, sbb; float2 sm2;
            {
                const uint32_t scl = sb + SM_SC + L16;
                const float4 a0 = lds128f(scl), a1 = lds128f(scl + 1536), a2 = lds128f(scl + 3072);
                const float4 b0 = lds128f(scl + 512), b1 = lds128f(scl + 2048), b2 = lds128f(scl + 3584);
                const uint32_t scm = sb + SM_SC + 1024 + (L16 >> 1);
                const float2 m0 = lds64f(scm), m1 = lds64f(scm + 1536), m2 = lds64f(scm + 3072);
                sa.x = a0.x + a1.x + a2.x; sa.y = a0.y + a1.y + a2.y; sa.z = a0.z + a1.z + a2.z; sa.w = a0.w + a1.w + a2.w;
                sbb.x = b0.x + b1.x + b2.x; sbb.y = b0.y + b1.y + b2.y; sbb.z = b0.z + b1.z + b2.z; sbb.w = b0.w + b1.w + b2.w;
                sm2.x = m0.x + m1.x + m2.x; sm2.y = m0.y + m1.y + m2.y;
            }
            float mx = fmaxf(fmaxf(fmaxf(sa.x, sa.y), fmaxf(sa.z, sa.w)), fmaxf(fmaxf(sbb.x, sbb.y), fmaxf(sbb.z, sbb.w)));
            mx = fmaxf(mx, fmaxf(sm2.x, sm2.y));
            {
                const float x1 = __shfl_xor_sync(0xffffffffu, mx, 1), x2 = __shfl_xor_sync(0xffffffffu, mx, 2), x3 = __shfl_xor_sync(0xffffffffu, mx, 3);
                ldsm4t(va[0][1], v0a + 512); ldsm4t(va[1][1], v0a + 1024 + 512);
                mbar_wait(bV, s & 1);
                ldsm4t(vb, mr + vs * 256 + AB);
                mx = fmaxf(fmaxf(mx, x1), fmaxf(x2, x3));
            }
            uint32_t ws[8][4];
#pragma unroll
            for (int k = WRES; k < WRES + WO_PRE2 && k < 8; k++) lds128(ws[k], wou + L16 + (16 + k) * 2048);
            const float mo = mx * SC;
            const float e0 = ex2(fmaf(sa.x, SC, -mo)), e1 = ex2(fmaf(sa.y, SC, -mo)), e2 = ex2(fmaf(sa.z, SC, -mo)), e3 = ex2(fmaf(sa.w, SC, -mo));
            float o0[4] = {0.f, 0.f, 0.f, 0.f}, o1[4] = {0.f, 0.f, 0.f, 0.f}, o2[4] = {0.f, 0.f, 0.f, 0.f};
            const uint32_t one = 0x3f803f80u, one4[4] = {one, one, one, one};
            { const uint32_t p0 = pack2(e0, e1), p1 = pack2(e2, e3); mma16(o0, va[0][0], p0, p1); mma16(o1, va[1][0], p0, p1); mma16(o2, one4, p0, p1); }
            const float e4 = ex2(fmaf(sbb.x, SC, -mo)), e5 = ex2(fmaf(sbb.y, SC, -mo)), e6 = ex2(fmaf(sbb.z, SC, -mo)), e7 = ex2(fmaf(sbb.w, SC, -mo));
            { const uint32_t p0 = pack2(e4, e5), p1 = pack2(e6, e7); mma16(o0, va[0][1], p0, p1); mma16(o1, va[1][1], p0, p1); mma16(o2, one4, p0, p1); }
            const float e8 = ex2(fmaf(sm2.x, SC, -mo)), e9 = ex2(fmaf(sm2.y, SC, -mo));
            { const uint32_t p0 = pack2(e8, e9); mma8(o0, vb[0], vb[1], p0); mma8(o1, vb[2], vb[3], p0); mma8(o2, one, one, p0); }
            {
                const uint32_t oa = sb + SM_OB + wq * 512 + (L16 >> 2);
                sts32(oa, pack2(o0[0], o0[1])); sts32(oa + 128, pack2(o0[2], o0[3]));
                sts32(oa + 256, pack2(o1[0], o1[1])); sts32(oa + 384, pack2(o1[2], o1[3]));
            }
            bar_sync(4, 128);
            uint32_t ob[4][4];
#pragma unroll
            for (int j = 0; j < 4; j++) ldsm4t(ob[j], sb + SM_OB + L16 + 512 * j);
            const float fs = __int_as_float((127 + ex) << 23);
            const float i0 = rcp_fast(o2[0]) * fs, i1 = rcp_fast(o2[1]) * fs;
            float v[12];
            {
                float r[6][4];
#pragma unroll
                for (int i = 0; i < 6; i++) { r[i][0] = 0.f; r[i][1] = 0.f; r[i][2] = 0.f; r[i][3] = 0.f; }
#pragma unroll
                for (int k = WRES + WO_PRE2; k < WRES + WO_PRE3 && k < 8; k++) lds128(ws[k], wou + L16 + (16 + k) * 2048);
#pragma unroll
                for (int i = 0; i < 8; i++) {
                    mma16v(r[(i & 1) ? 3 : 0], wa[i], ob[i >> 1][(i & 1) * 2], ob[i >> 1][(i & 1) * 2 + 1]);
                    mma16v(r[(i & 1) ? 4 : 1], wb[i], ob[i >> 1][(i & 1) * 2], ob[i >> 1][(i & 1) * 2 + 1]);
                    mma16v(r[(i & 1) ? 5 : 2], i < WRES ? wc[i] : ws[i], ob[i >> 1][(i & 1) * 2], ob[i >> 1][(i & 1) * 2 + 1]);
                    if (i + WRES + WO_PRE3 < 8) lds128(ws[i + WRES + WO_PRE3], wou + L16 + (16 + i + WRES + WO_PRE3) * 2048);
                }
#pragma unroll
                for (int j = 0; j < 3; j++) {
                    { r[j][0] += r[3 + j][0]; r[j][1] += r[3 + j][1]; r[j][2] += r[3 + j][2]; r[j][3] += r[3 + j][3]; }
                    v[4 * j] = r[j][0] * i0; v[4 * j + 1] = r[j][2] * i0; v[4 * j + 2] = r[j][1] * i1; v[4 * j + 3] = r[j][3] * i1;
                }
                const float m8 = maxn(maxn(maxn(v[0], v[1]), maxn(v[2], v[3])), maxn(maxn(v[4], v[5]), maxn(v[6], v[7])));
                const float m = maxn(maxn(maxn(v[8], v[9]), maxn(v[10], v[11])), m8);
                const uint32_t tag = m < 1024.f ? (m >= 0.0625f ? 0x3c003c00u : 0x00003c00u) : 0x54003c00u;
                redh4(rl, v, tag);
                bar_arrive(5, 384);
                redh4(rl + 16 * 72, v + 6, tag);
            }
            const unsigned tred = clk32();
            if (wq == 3) bar_sync(7, 288);
            if (wt == 0) {
                if (s + 2 < NSEG) { mbar_expect(bS, 2560); mbar_expect(bV, (8 - nv) * 256); }
                if (s + 3 < NSEG) mbar_expect(bVX + 8 * st, (8 - nv) * 1024);
            }
            {
                const uint4* gl = rl - c * 32 * 72;
                uint32_t ma = sb + SM_MEM + wq * 32 + ((L16 >> 4) & 3) * (2 * MP) + (L16 >> 6) * 4;
                PINL(gl); PIN(ma);
                unsigned tl = tred + p.d0;
                spin_until(tl);
                uint4 u[2][3];
#pragma unroll
                for (int j = 0; j < 2; j++)
#pragma unroll
                    for (int cc = 0; cc < 3; cc++) u[j][cc] = ld_relaxed4u(gl + (cc * 32 + j * 16) * 72);
                const uint32_t rebias = (uint32_t)(112 - ex) * 0x00800080u;
                int it = 0;
                auto cvt = [&](uint32_t x) { return ((((x + 0x00030004u) & 0x7ff87ff8u) >> 3) + rebias) | (x & 0x80008000u); };
                auto put = [&](int j, int cc) {
                    sts32(ma + (cc * 192 + ((3 * j) >> 1) * 64) * 2 + ((3 * j) & 1) * MP, u[j][cc].x);
                    sts32(ma + (cc * 192 + ((3 * j + 1) >> 1) * 64) * 2 + ((3 * j + 1) & 1) * MP, u[j][cc].y);
                    sts32(ma + (cc * 192 + ((3 * j + 2) >> 1) * 64) * 2 + ((3 * j + 2) & 1) * MP, u[j][cc].z);
                };
#pragma unroll
                for (int j = 0; j < 2; j++)
#pragma unroll
                    for (int cc = 0; cc < 3; cc++) {
                        u[j][cc].x = cvt(u[j][cc].x); u[j][cc].y = cvt(u[j][cc].y); u[j][cc].z = cvt(u[j][cc].z);
                        put(j, cc);
                    }
                {
                    const uint32_t bad = ((u[0][0].w ^ 0x5000u) | (u[0][1].w ^ 0x5000u) | (u[0][2].w ^ 0x5000u)) |
                                         ((u[1][0].w ^ 0x5000u) | (u[1][1].w ^ 0x5000u) | (u[1][2].w ^ 0x5000u));
                    const uint32_t tg = max(max(max(u[0][0].w, u[0][1].w), u[0][2].w), max(max(u[1][0].w, u[1][1].w), u[1][2].w));
                    const bool clean = __all_sync(0xffffffffu, (bad & 0xffffu) == 0 && tg < 0x54000000u);
                    const bool big = __any_sync(0xffffffffu, tg >= 0x3c000000u);
                    if (__builtin_expect(!(clean && big), 0)) {
                        while (true) {
                            bool ok = true;
#pragma unroll
                            for (int j = 0; j < 2; j++)
#pragma unroll
                                for (int cc = 0; cc < 3; cc++) ok = ok && (u[j][cc].w & 0xffffu) == 0x5000u;
                            if (__all_sync(0xffffffffu, ok)) break;
                            if (++it > (1 << 20)) __trap();
                            uint32_t redo = 0;
#pragma unroll
                            for (int j = 0; j < 2; j++)
#pragma unroll
                                for (int cc = 0; cc < 3; cc++) {
                                    if ((u[j][cc].w & 0xffffu) != 0x5000u) redo |= 1u << (j * 3 + cc);
                                    reld_relaxed4u(u[j][cc], gl + (cc * 32 + j * 16) * 72);
                                }
#pragma unroll
                            for (int j = 0; j < 2; j++)
#pragma unroll
                                for (int cc = 0; cc < 3; cc++) {
                                    const bool rd = (redo >> (j * 3 + cc)) & 1;
                                    u[j][cc].x = rd ? cvt(u[j][cc].x) : u[j][cc].x; u[j][cc].y = rd ? cvt(u[j][cc].y) : u[j][cc].y;
                                    u[j][cc].z = rd ? cvt(u[j][cc].z) : u[j][cc].z;
                                    put(j, cc);
                                }
                        }
                        const uint32_t t2 = max(max(max(u[0][0].w, u[0][1].w), u[0][2].w), max(max(u[1][0].w, u[1][1].w), u[1][2].w));
                        if (__any_sync(0xffffffffu, t2 >= 0x54000000u) || !__any_sync(0xffffffffu, t2 >= 0x3c000000u)) {
                            const float isc = __int_as_float((127 - ex) << 23);
                            float* fl = red_line(s, c * 64 + wq * 4 + (L16 >> 7)) + ((L16 >> 2) & 28);
#pragma unroll
                            for (int i = 0; i < 4; i++) red4(fl + i * 16 * 256, v[3 * i], v[3 * i + 1], v[3 * i + 2], 1.0f);
                            const float* fg = fl - c * 64 * 256;
#pragma unroll
                            for (int j = 0; j < 2; j++)
#pragma unroll
                                for (int cc = 0; cc < 3; cc++) {
                                    float4 a, b;
                                    while (true) {
                                        a = ld_relaxed4(fg + (cc * 64 + j * 32) * 256); b = ld_relaxed4(fg + (cc * 64 + j * 32 + 16) * 256);
                                        if (__all_sync(0xffffffffu, a.w == 32.f && b.w == 32.f)) break;
                                        if (++it > (1 << 20)) __trap();
                                    }
                                    u[j][cc].x = pack2(a.x * isc, a.y * isc); u[j][cc].y = pack2(a.z * isc, b.x * isc); u[j][cc].z = pack2(b.y * isc, b.z * isc);
                                    put(j, cc);
                                }
                        }
                    }
                }
                bar_arrive(1, 384);
                uint32_t am = max(max(u[0][0].x << 1, u[0][1].y << 1), max(u[1][1].x << 1, u[1][2].y << 1));
                am = __reduce_max_sync(0xffffffffu, am >> 24);
                if (am) ex = min(max(4 - ((int)am - 127), -60), 60);
                s3 = s3 == 2 ? 0 : s3 + 1;
            }
        }
        if (wt == 96) publish(NSEG - 1, 0);
        __syncwarp();
        if (wq < 3) bar_sync(8, nq * 64 + 96);
        bar_arrive(5, 384);
        if (wt == 96) publish(NSEG, 1);
        __syncwarp();
        if (wq == 3) bar_sync(7, 288);
    }
    cluster_sync();
}

constexpr int H_STAGES = 4, H_STAGE = 57344;
constexpr int HELP_SMEM = H_STAGES * H_STAGE + 1024 + 256;
constexpr int NBLK = 11;
enum { T_EXIT = 0, T_G0, T_F, T_AB, T_AA, T_FS, T_FN };
enum { C_HG = 0, C_HB = 32, C_GATE = 33, C_G0 = 48, C_AB = 64, C_HF = 96, C_AA = 128, C_HAA = 160, C_F = 256 };
constexpr int NG0 = NBLK * 9;
constexpr int ABH = 6;
constexpr int ABT = (BH + ABH - 1) / ABH;
constexpr int NB_UNITS = NG0 + 16 * ABT;
__host__ __device__ constexpr int aa_units(int seg) { return seg < 36 ? 3 : 6; }
constexpr unsigned AA_CTAS = 4;
constexpr unsigned AA_CTAS2 = 8;
constexpr unsigned AA_CTAS3 = 18;
constexpr int AA_B3 = 9;
constexpr int AA_LATE = 61;
constexpr int NFB = 12;
__host__ __device__ constexpr int f_row0(int m) { return m < 10 ? m * 192 : 1856 + (m - 10) * 128; }
__host__ __device__ constexpr int f_rows(int m) { return m < 9 ? 192 : (m < 11 ? 128 : 64); }
__host__ __device__ constexpr int f_blk(int seg) { return seg < 54 ? seg / 6 : 9 + (seg - 54) / 4; }
constexpr int DRAIN_B = 5;
constexpr int SPIN_NS = 20;
constexpr int FNM = 0x7f0;
__host__ __device__ constexpr int f_ntiles(int m) { return m < 11 ? (((FNM >> m) & 1) ? 6 : 3) : 9; }

__device__ __forceinline__ void signal(unsigned* q, int lane, unsigned n = 1) {
    asm volatile("fence.proxy.async.global;" ::: "memory");
    __syncwarp();
    if (lane == 0) asm volatile("red.release.gpu.global.add.u32 [%0],%1;" ::"l"(q), "r"(n) : "memory");
}

__device__ __forceinline__ int pos_q(int d) { return (d / 3) * 8 + d % 3; }
__device__ __forceinline__ int pos_k(int d) { return (d / 3) * 8 + d % 3 + (d < 6 ? 3 : 2); }
__device__ __forceinline__ int mpos_k(int d) { return (d / 3) * 5 + d % 3; }
__device__ __forceinline__ int mpos_v(int d) { return d < 2 ? 3 + d : (d < 4 ? 6 + d : 8 + d); }
__device__ __forceinline__ int pos_v(int d) { return d < 2 ? 6 + d : (d < 4 ? 12 + d : 16 + d); }

__device__ __forceinline__ uint4 quad_tr(const uint32_t* v, int t) {
    uint32_t a0 = (t & 1) ? v[0] : v[1], a1 = (t & 1) ? v[2] : v[3];
    a0 = __shfl_xor_sync(0xffffffffu, a0, 1); a1 = __shfl_xor_sync(0xffffffffu, a1, 1);
    const uint32_t b0 = (t & 1) ? a0 : v[0], b1 = (t & 1) ? v[1] : a0, b2 = (t & 1) ? a1 : v[2], b3 = (t & 1) ? v[3] : a1;
    uint32_t c0 = (t & 2) ? b0 : b2, c1 = (t & 2) ? b1 : b3;
    c0 = __shfl_xor_sync(0xffffffffu, c0, 2); c1 = __shfl_xor_sync(0xffffffffu, c1, 2);
    uint4 o;
    o.x = (t & 2) ? c0 : b0; o.y = (t & 2) ? c1 : b1; o.z = (t & 2) ? b2 : c0; o.w = (t & 2) ? b3 : c1;
    return o;
}
template <int BN>
__device__ __forceinline__ void store_tile(const float* acc, bf16* q, int pitch, int t) {
#pragma unroll
    for (int j = 0; j < BN / 32; j++) {
        uint32_t lo[4], hi[4];
#pragma unroll
        for (int i = 0; i < 4; i++) {
            lo[i] = pack2(acc[16 * j + 4 * i], acc[16 * j + 4 * i + 1]); hi[i] = pack2(acc[16 * j + 4 * i + 2], acc[16 * j + 4 * i + 3]);
        }
        *reinterpret_cast<uint4*>(q + j * 32 + t * 8) = quad_tr(lo, t);
        *reinterpret_cast<uint4*>(q + (size_t)8 * pitch + j * 32 + t * 8) = quad_tr(hi, t);
    }
}

template <int MT>
__device__ __forceinline__ void attnA_unit(uint32_t xr, uint32_t mr, int s, int h, int lane, uint32_t rel) {
    const int g = lane >> 2, t = lane & 3, l7 = lane & 7, l3 = lane >> 3;
    const float SC = 0.08838834764831845f * 1.4426950408889634f;
    constexpr int NT = MT ? 5 : 3;
    const uint32_t offA = (l7 + (l3 & 1) * 8) * 32 + (((l3 >> 1) ^ (l7 >> 2)) << 4);
    const uint32_t offB = (l7 + (l3 >> 1) * 8) * 32 + (((l3 & 1) ^ (l7 >> 2)) << 4);
    float sa[NT][4];
#pragma unroll
    for (int n = 0; n < NT; n++)
#pragma unroll
        for (int i = 0; i < 4; i++) sa[n][i] = 0.f;
#pragma unroll
    for (int hf = 0; hf < 2; hf++) {
        uint32_t qf[4][4], k0[4][4], k1[4][4], km[4][2];
#pragma unroll
        for (int i = 0; i < 4; i++) {
            const int d = hf * 4 + i;
            ldsm4(qf[i], xr + pos_q(d) * 1024 + MT * 512 + offA);
            ldsm2(km[i], mr + mpos_k(d) * 256 + (offB & 255));
            ldsm4(k0[i], xr + pos_k(d) * 1024 + offB);
            if (MT) ldsm4(k1[i], xr + pos_k(d) * 1024 + 512 + offB);
        }
#pragma unroll
        for (int i = 0; i < 4; i++) {
            mma16(sa[0], qf[i], km[i][0], km[i][1]);
            mma16(sa[1], qf[i], k0[i][0], k0[i][1]); mma16(sa[2], qf[i], k0[i][2], k0[i][3]);
            if (MT) { mma16(sa[NT - 2], qf[i], k1[i][0], k1[i][1]); mma16(sa[NT - 1], qf[i], k1[i][2], k1[i][3]); }
        }
    }
    if (2 * t > g) sa[NT - 2][0] = -INFINITY;
    if (2 * t + 1 > g) sa[NT - 2][1] = -INFINITY;
    sa[NT - 1][0] = -INFINITY; sa[NT - 1][1] = -INFINITY;
    if (2 * t > g) sa[NT - 1][2] = -INFINITY;
    if (2 * t + 1 > g) sa[NT - 1][3] = -INFINITY;
    float m0 = fmaxf(sa[0][0], sa[0][1]), m1 = fmaxf(sa[0][2], sa[0][3]);
#pragma unroll
    for (int n = 1; n < NT; n++) { m0 = fmaxf(m0, fmaxf(sa[n][0], sa[n][1])); m1 = fmaxf(m1, fmaxf(sa[n][2], sa[n][3])); }
    m0 = fmaxf(m0, __shfl_xor_sync(0xffffffffu, m0, 1)); m1 = fmaxf(m1, __shfl_xor_sync(0xffffffffu, m1, 1));
    m0 = fmaxf(m0, __shfl_xor_sync(0xffffffffu, m0, 2)); m1 = fmaxf(m1, __shfl_xor_sync(0xffffffffu, m1, 2));
    m0 *= SC; m1 *= SC;
    float s0 = 0.f, s1 = 0.f;
#pragma unroll
    for (int n = 0; n < NT; n++) {
        sa[n][0] = ex2(fmaf(sa[n][0], SC, -m0)); sa[n][1] = ex2(fmaf(sa[n][1], SC, -m0));
        sa[n][2] = ex2(fmaf(sa[n][2], SC, -m1)); sa[n][3] = ex2(fmaf(sa[n][3], SC, -m1));
        s0 += sa[n][0] + sa[n][1]; s1 += sa[n][2] + sa[n][3];
    }
    s0 += __shfl_xor_sync(0xffffffffu, s0, 1); s1 += __shfl_xor_sync(0xffffffffu, s1, 1);
    s0 += __shfl_xor_sync(0xffffffffu, s0, 2); s1 += __shfl_xor_sync(0xffffffffu, s1, 2);
    s0 = rcp_fast(s0); s1 = rcp_fast(s1);
    uint32_t pa[NT][2];
#pragma unroll
    for (int n = 0; n < NT; n++) { pa[n][0] = pack2(sa[n][0] * s0, sa[n][1] * s0); pa[n][1] = pack2(sa[n][2] * s1, sa[n][3] * s1); }
    const uint32_t p0[4] = {pa[1][0], pa[1][1], pa[2][0], pa[2][1]}, p1[4] = {pa[NT - 2][0], pa[NT - 2][1], pa[NT - 1][0], pa[NT - 1][1]};
    bf16* op = g_O + (size_t)(s * 32 + MT * 16 + g) * OK + h * DH + t * 8;
#pragma unroll
    for (int dh = 0; dh < 2; dh++) {
        uint32_t f0[4][4], f1[4][4], f2[4][2];
#pragma unroll
        for (int n2 = 0; n2 < 4; n2++) {
            const int d = dh * 4 + n2;
            ldsm4t(f0[n2], xr + pos_v(d) * 1024 + offA);
            if (MT) ldsm4t(f1[n2], xr + pos_v(d) * 1024 + 512 + offA);
            ldsm2t(f2[n2], mr + mpos_v(d) * 256 + (offB & 255));
        }
        uint32_t lo[8], hi[8];
#pragma unroll
        for (int n2 = 0; n2 < 4; n2++) {
            float oa0[4] = {0.f, 0.f, 0.f, 0.f}, oa1[4] = {0.f, 0.f, 0.f, 0.f};
            mma16(oa0, p0, f0[n2][0], f0[n2][1]); mma16(oa1, p0, f0[n2][2], f0[n2][3]);
            if (MT) { mma16(oa0, p1, f1[n2][0], f1[n2][1]); mma16(oa1, p1, f1[n2][2], f1[n2][3]); }
            mma8(oa0, pa[0][0], pa[0][1], f2[n2][0]); mma8(oa1, pa[0][0], pa[0][1], f2[n2][1]);
            lo[2 * n2] = pack2(oa0[0], oa0[1]); hi[2 * n2] = pack2(oa0[2], oa0[3]);
            lo[2 * n2 + 1] = pack2(oa1[0], oa1[1]); hi[2 * n2 + 1] = pack2(oa1[2], oa1[3]);
        }
        if (dh == 1) { __syncwarp(); if (lane == 0) mbar_arrive(rel); }
#pragma unroll
        for (int q = 0; q < 2; q++) {
            *reinterpret_cast<uint4*>(op + dh * 64 + q * 32) = quad_tr(lo + 4 * q, t);
            *reinterpret_cast<uint4*>(op + (size_t)8 * OK + dh * 64 + q * 32) = quad_tr(hi + 4 * q, t);
        }
    }
}

template <int V> struct IC { static constexpr int value = V; };
__device__ __forceinline__ void attnB_unit(uint32_t sQ, int q0, int hh, int wq, int lane, uint32_t rel) {
    const int g = lane >> 2, t = lane & 3, l7 = lane & 7, l3 = lane >> 3;
    const uint32_t sK = sQ + 128 * 48, sV = sK + 384 * 48;
    const int sh = (hh & 3) * 2;
    uint32_t qa[2][4], qb[2][2];
#pragma unroll
    for (int m = 0; m < 2; m++) {
        ldsm4(qa[m], sQ + (wq * 32 + m * 16 + l7 + (l3 & 1) * 8) * 48 + (l3 >> 1) * 16);
        ldsm2(qb[m], sQ + (wq * 32 + m * 16 + l7 + (l3 & 1) * 8) * 48 + 32);
        if (2 * t < sh) { qa[m][0] = 0u; qa[m][1] = 0u; }
        if (16 + 2 * t >= sh + 18) { qb[m][0] = 0u; qb[m][1] = 0u; }
    }
    const bool one0 = (sh == 6 && g == 0), one2 = (sh != 6 && g == 7);
    float gt[2][2];
#pragma unroll
    for (int m = 0; m < 2; m++) { gt[m][0] = __ldcg(g_gate + q0 + wq * 32 + m * 16 + g); gt[m][1] = __ldcg(g_gate + q0 + wq * 32 + m * 16 + g + 8); }
    const float SC = 0.23570226039551584f * 1.4426950408889634f;
    float o[2][3][4];
    float mx[2][2];
#pragma unroll
    for (int m = 0; m < 2; m++) {
        mx[m][0] = -INFINITY; mx[m][1] = -INFINITY;
#pragma unroll
        for (int n = 0; n < 3; n++)
#pragma unroll
            for (int i = 0; i < 4; i++) o[m][n][i] = 0.f;
    }
    const int tfirst = max(0, (256 - q0) / 16 - 2 * wq);
    const uint32_t kb0 = sK + (wq * 32 + l7 + (l3 >> 1) * 8) * 48 + (l3 & 1) * 16;
    const uint32_t kb1 = sK + (wq * 32 + l7 + (l3 & 1) * 8) * 48 + 32;
    const uint32_t vb0 = sV + (wq * 32 + l7 + (l3 & 1) * 8) * 48 + (l3 >> 1) * 16;
    const uint32_t vb1 = sV + (wq * 32 + l7 + (l3 & 1) * 8) * 48 + 32;
    constexpr int CH = 3;
    auto chunk = [&](auto mode, int c0) {
        constexpr int MODE = decltype(mode)::value;
        auto dead = [](int m, int u) { return (MODE == 0 && m == 0 && u == 2) || (MODE == 2 && m == 1 && u == 0); };
        float sc[2][CH][2][4];
#pragma unroll
        for (int u = 0; u < CH; u++) {
            uint32_t kf[4], kg[2];
            const int ti = MODE == 3 ? max(c0 + u, tfirst) : c0 + u;
            ldsm4(kf, kb0 + ti * 768); ldsm2(kg, kb1 + ti * 768);
#pragma unroll
            for (int m = 0; m < 2; m++) {
                if (dead(m, u)) continue;
#pragma unroll
                for (int n = 0; n < 2; n++) {
#pragma unroll
                    for (int i = 0; i < 4; i++) sc[m][u][n][i] = 0.f;
                    mma16(sc[m][u][n], qa[m], kf[2 * n], kf[2 * n + 1]);
                    mma8(sc[m][u][n], qb[m][0], qb[m][1], kg[n]);
                }
            }
        }
#pragma unroll
        for (int m = 0; m < 2; m++)
#pragma unroll
            for (int u = 0; u < CH; u++)
#pragma unroll
                for (int n = 0; n < 2; n++)
#pragma unroll
                    for (int i = 0; i < 4; i++) {
                        const int dl = g + (i >> 1) * 8 - (n * 8 + 2 * t + (i & 1));
                        if (MODE == 0 && u == m + 1 && dl < 0) sc[m][u][n][i] = -INFINITY;
                        if (MODE == 2 && u == m && dl >= 0) sc[m][u][n][i] = -INFINITY;
                        if (MODE == 3) {
                            const int d = 256 + (m - c0 - u) * 16 + dl;
                            if (d < 0 || d >= 256 || c0 + u < tfirst) sc[m][u][n][i] = -INFINITY;
                        }
                    }
        float bs[2][2];
#pragma unroll
        for (int m = 0; m < 2; m++) {
            float n0 = mx[m][0], n1 = mx[m][1];
#pragma unroll
            for (int u = 0; u < CH; u++) {
                if (dead(m, u)) continue;
#pragma unroll
                for (int n = 0; n < 2; n++) {
                    n0 = fmaxf(n0, fmaxf(sc[m][u][n][0], sc[m][u][n][1])); n1 = fmaxf(n1, fmaxf(sc[m][u][n][2], sc[m][u][n][3]));
                }
            }
            n0 = fmaxf(n0, __shfl_xor_sync(0xffffffffu, n0, 1)); n1 = fmaxf(n1, __shfl_xor_sync(0xffffffffu, n1, 1));
            n0 = fmaxf(n0, __shfl_xor_sync(0xffffffffu, n0, 2)); n1 = fmaxf(n1, __shfl_xor_sync(0xffffffffu, n1, 2));
            if (MODE != 0) {
                const float f0 = ex2((mx[m][0] - n0) * SC), f1 = ex2((mx[m][1] - n1) * SC);
#pragma unroll
                for (int n = 0; n < 3; n++) { o[m][n][0] *= f0; o[m][n][1] *= f0; o[m][n][2] *= f1; o[m][n][3] *= f1; }
            }
            mx[m][0] = n0; mx[m][1] = n1;
            bs[m][0] = n0 * SC; bs[m][1] = n1 * SC;
        }
#pragma unroll
        for (int u = 0; u < CH; u++) {
            uint32_t vf[4], vg[2];
            const int ti = MODE == 3 ? max(c0 + u, tfirst) : c0 + u;
            ldsm4t(vf, vb0 + ti * 768); ldsm2t(vg, vb1 + ti * 768);
            if (one0) { vf[0] = 0x3f803f80u; vf[1] = 0x3f803f80u; }
            if (one2) { vg[0] = 0x3f803f80u; vg[1] = 0x3f803f80u; }
#pragma unroll
            for (int m = 0; m < 2; m++) {
                if (dead(m, u)) continue;
                uint32_t pa[4];
#pragma unroll
                for (int n = 0; n < 2; n++) {
                    pa[2 * n] = pack2(ex2(fmaf(sc[m][u][n][0], SC, -bs[m][0])), ex2(fmaf(sc[m][u][n][1], SC, -bs[m][0])));
                    pa[2 * n + 1] = pack2(ex2(fmaf(sc[m][u][n][2], SC, -bs[m][1])), ex2(fmaf(sc[m][u][n][3], SC, -bs[m][1])));
                }
                mma16(o[m][0], pa, vf[0], vf[1]); mma16(o[m][1], pa, vf[2], vf[3]); mma16(o[m][2], pa, vg[0], vg[1]);
            }
        }
    };
    if (tfirst == 0) {
        chunk(IC<0>{}, 15);
#pragma unroll 1
        for (int c0 = 12; c0 > 0; c0 -= CH) chunk(IC<1>{}, c0);
        chunk(IC<2>{}, 0);
    } else {
#pragma unroll 1
        for (int c0 = 15; c0 >= 0 && c0 + CH > tfirst; c0 -= CH) chunk(IC<3>{}, c0);
    }
    __syncwarp();
    if (lane == 0) mbar_arrive(rel);
#pragma unroll
    for (int m = 0; m < 2; m++) {
        const int src = sh == 6 ? (lane & ~3) : (lane | 3);
        const float s0 = __shfl_sync(0xffffffffu, sh == 6 ? o[m][0][0] : o[m][2][1], src);
        const float s1 = __shfl_sync(0xffffffffu, sh == 6 ? o[m][0][2] : o[m][2][3], src);
        const int r = q0 + wq * 32 + m * 16 + g;
        const float i0 = (1.f - gt[m][0]) * rcp_fast(s0), i1 = (1.f - gt[m][1]) * rcp_fast(s1);
        bf16* op = g_O + (size_t)r * OK + HD + hh * BD + 2 * t - sh;
#pragma unroll
        for (int n = 0; n < 3; n++) {
            const int col = n * 8 + 2 * t;
            if (col >= sh && col < sh + 18) {
                *reinterpret_cast<uint32_t*>(op + n * 8) = pack2(o[m][n][0] * i0, o[m][n][1] * i0);
                *reinterpret_cast<uint32_t*>(op + n * 8 + 8 * OK) = pack2(o[m][n][2] * i1, o[m][n][3] * i1);
            }
        }
    }
}

template <int BN>
__device__ __forceinline__ void gemm_unit(int ty, const uint32_t* d, uint32_t sb, uint32_t bF, uint32_t bE, int& sg, int& ph,
                                          int warp, int lane, bf16* __restrict__ out) {
    const int wg = warp >> 2, wq = warp & 3, g = lane >> 2, t = lane & 3;
    auto release = [&](int q) { __syncwarp(); if (lane == 0) mbar_arrive(bE + 8 * q); };
    const int n0 = d[2] * BN, kb0 = d[3] & 255, kb1 = d[3] >> 8;
    const int rb = (ty == T_G0 ? d[1] * 192 : f_row0(d[1])) + (BN == 64 ? wq : warp) * 16, r0 = rb + g;
    float g0 = 1.f, g1 = 1.f;
    if (ty != T_G0) { g0 = __ldcg(g_gate + r0); g1 = __ldcg(g_gate + r0 + 8); }
    if (ty != T_G0 && f_split(d[1]) > 1) {
        const float* pa = g_acc + (size_t)rb * DM + n0 * 16 + lane * 32;
#pragma unroll
        for (int i = 0; i < (BN + 63) / 64; i++) if (i * 64 + lane * 2 < BN) asm volatile("prefetch.global.L2 [%0];" ::"l"(pa + i * 1024));
    }
    float acc[BN / 2];
#pragma unroll
    for (int i = 0; i < BN / 2; i++) acc[i] = 0.f;
    int prev = -1;
    constexpr int KPS = BN == 64 ? 3 : 1;
    for (int kb = kb0; kb < kb1;) {
        if (kb > kb0) mbar_wait(bF + 8 * sg, ph);
        for (int j = 0; j < KPS && kb < kb1; j++, kb++) {
            const uint32_t a = sb + sg * H_STAGE + (BN == 64 ? j * 16384 : wg * 8192), b = BN == 64 ? a + 8192 : sb + sg * H_STAGE + 24576;
            if (kb == 64 && kb0 < 64) {
                wg_wait<0>();
#pragma unroll
                for (int i = 0; i < BN / 8; i++) { acc[4 * i] *= g0; acc[4 * i + 1] *= g0; acc[4 * i + 2] *= g1; acc[4 * i + 3] *= g1; }
            }
            const uint64_t da = desc_sw128(a, 16, 1024), db = desc_sw128(b, 8192, 1024);
            wg_fence();
#pragma unroll
            for (int k = 0; k < 4; k++) {
                if (BN == 192) wgmma_ss_n192(acc, da + (uint64_t)(k * 2), db + (uint64_t)(k * 128), 1);
                else if (BN == 96) wgmma_ss_n96(acc, da + (uint64_t)(k * 2), db + (uint64_t)(k * 128));
                else wgmma_ss_n64(acc, da + (uint64_t)(k * 2), db + (uint64_t)(k * 128));
            }
            wg_commit();
            wg_wait<1>();
            if (j == 0 && prev >= 0) release(prev);
        }
        prev = sg;
        if (++sg == H_STAGES) { sg = 0; ph ^= 1; }
    }
    wg_wait<0>();
    if (ty == T_G0) {
        release(prev);
        store_tile<BN>(acc, g_qkvB + (size_t)r0 * (3 * DM) + n0, 3 * DM, t);
        signal(g_ctr + C_G0 + d[1], lane);
        return;
    }
    if (kb1 <= 64) {
#pragma unroll
        for (int i = 0; i < BN / 8; i++) { acc[4 * i] *= g0; acc[4 * i + 1] *= g0; acc[4 * i + 2] *= g1; acc[4 * i + 3] *= g1; }
    }
    const int ks = f_split(d[1]);
    bool fin = true;
    if (ks == 1) release(prev);
    if (ks > 1) {
        float4* ga = reinterpret_cast<float4*>(g_acc + (size_t)rb * DM + n0 * 16) + lane;
#pragma unroll
        for (int i = 0; i < BN / 8; i++) red4(reinterpret_cast<float*>(ga + i * 32), acc[4 * i], acc[4 * i + 1], acc[4 * i + 2], acc[4 * i + 3]);
        release(prev);
        unsigned old = 0;
        if (lane == 0) asm volatile("atom.acq_rel.gpu.global.add.u32 %0,[%1],1;" : "=r"(old) : "l"(g_ctr + C_F + (d[1] * 9 + d[2]) * 12 + warp) : "memory");
        old = __shfl_sync(0xffffffffu, old, 0);
        fin = (old == (unsigned)ks - 1);
        if (fin) {
#pragma unroll
            for (int i = 0; i < BN / 8; i++) {
                const float4 u = __ldcg(ga + i * 32);
                acc[4 * i] = u.x; acc[4 * i + 1] = u.y; acc[4 * i + 2] = u.z; acc[4 * i + 3] = u.w;
            }
        }
    }
    if (fin) store_tile<BN>(acc, out + (size_t)r0 * DM + n0, DM, t);
}

struct HelpMaps { CUtensorMap x, wqkv, O, O128, O64, Wo, wo, qkv; };

__global__ void __launch_bounds__(512, 1) k_help(const __grid_constant__ HelpMaps tm, const bf16* __restrict__ x,
                                                  const bf16* __restrict__ gw, bf16* __restrict__ out) {
    extern __shared__ uint8_t smem_raw[];
    const uint32_t sb = (s2u(smem_raw) + 1023) & ~1023u;
    const uint32_t bF = sb + H_STAGES * H_STAGE, bE = bF + 8 * H_STAGES, dsc = bF + 128;
    const int tid = threadIdx.x, warp = __shfl_sync(0xffffffffu, tid >> 5, 0), lane = tid & 31;
    if (tid == 0) {
        for (int i = 0; i < H_STAGES; i++) { mbar_init(bF + 8 * i, 1); mbar_init(bE + 8 * i, 12); }
        asm volatile("fence.mbarrier_init.release.cluster;" ::: "memory");
    }
    __syncthreads();
    if (warp >= 12) {
        asm volatile("setmaxnreg.dec.sync.aligned.u32 56;");
        if (warp != 12) {
            while (true) {
                unsigned u = 0;
                if (lane == 0) u = atomicAdd(g_ctr + C_HG, 1);
                u = __shfl_sync(0xffffffffu, u, 0);
                if (u >= SEQ / 16) return;
#pragma unroll 1
                for (int r0 = u * 16; r0 < u * 16 + 16; r0 += 2) {
                    float a0 = 0.f, a1 = 0.f;
                    const __nv_bfloat162* xr = reinterpret_cast<const __nv_bfloat162*>(x + (size_t)r0 * DM);
#pragma unroll
                    for (int i = 0; i < 9; i++) {
                        const float2 b = __bfloat1622float2(reinterpret_cast<const __nv_bfloat162*>(gw)[lane + 32 * i]);
                        const float2 y = __bfloat1622float2(xr[lane + 32 * i]), z = __bfloat1622float2(xr[DM / 2 + lane + 32 * i]);
                        a0 += y.x * b.x + y.y * b.y; a1 += z.x * b.x + z.y * b.y;
                    }
#pragma unroll
                    for (int o = 16; o; o >>= 1) { a0 += __shfl_xor_sync(0xffffffffu, a0, o); a1 += __shfl_xor_sync(0xffffffffu, a1, o); }
                    if (lane < 2) g_gate[r0 + lane] = 1.f / (1.f + __expf(-(lane ? a1 : a0)));
                }
                signal(g_ctr + C_GATE, lane);
            }
        }
        int sg = 0, ph = 1;
        auto next = [&](int ty, int a, int b, int c2) {
            mbar_wait(bE + 8 * sg, ph);
            if (lane == 0) asm volatile("st.shared.v4.u32 [%0],{%1,%2,%3,%4};" ::"r"(dsc + 16 * sg), "r"(ty), "r"(a), "r"(b), "r"(c2) : "memory");
        };
        auto adv = [&]() { __syncwarp(); if (++sg == H_STAGES) { sg = 0; ph ^= 1; } };
        auto acquire = [&]() { asm volatile("fence.acq_rel.gpu;" ::: "memory"); };
        auto ticket = [&](unsigned* q) { unsigned u = 0; if (lane == 0) u = atomicAdd(q, 1); return __shfl_sync(0xffffffffu, u, 0); };
        auto gemm = [&](int ty, int m, int n, int kb0, int kb1) {
            for (int kb = kb0; kb < kb1; kb++) {
                next(ty, m, n, kb0 | (kb1 << 8));
                if (lane == 0) {
                    const uint32_t a = sb + sg * H_STAGE, b = a + 24576, bar = bF + 8 * sg;
                    const bool half = ty != T_G0 && m >= 9;
                    mbar_expect(bar, (ty == T_FN ? 40960 : 49152) - (half ? 8192 : 0));
                    tma2d(a, ty == T_G0 ? &tm.x : (half ? &tm.O128 : &tm.O), kb * 64, ty == T_G0 ? m * 192 : f_row0(m), bar);
                    const CUtensorMap* mb = ty == T_G0 ? &tm.wqkv : (kb >= 64 ? &tm.wo : &tm.Wo);
                    const int kr = (kb >= 64 ? kb - 64 : kb) * 64;
                    if (ty == T_FN) for (int j = 0; j < 2; j++) tma2d(b + j * 8192, mb, n * 96 + j * 64, kr, bar);
                    else for (int j = 0; j < 3; j++) tma2d(b + j * 8192, mb, n * 192 + j * 64, kr, bar);
                }
                adv();
            }
        };
        bool bdone = false;
        int idle = 0, rr = 0;
        const int fl = min(lane, 10);
        constexpr int NLATE = (NSEG - AA_LATE) * 6, NSMALL = 9 * f_split(11);
        auto attn_a = [&](int as, int u) {
            const int per = (15 + aa_units(as)) / aa_units(as), ns = min(per, 16 - u * per), h0 = u * per * 2;
            for (int i = 0; i < ns; i++) {
                next(T_AA, as, h0 + 2 * i, rr | (i + 3 >= ns ? 4 : 0)); rr = rr == 2 ? 0 : rr + 1;
                if (lane == 0) {
                    const uint32_t a = sb + sg * H_STAGE, bar = bF + 8 * sg;
                    mbar_expect(bar, 57344);
                    bulk_load(a, reinterpret_cast<uint8_t*>(g_xr) + (size_t)(as * 32 + h0 + 2 * i) * 24576, 49152, bar);
                    bulk_load(a + 49152, reinterpret_cast<uint8_t*>(g_mr) + (size_t)(as * 32 + h0 + 2 * i) * 4096, 8192, bar);
                }
                adv();
            }
        };
        auto spin_ge = [&](const unsigned* q, unsigned target) {
            int it = 0;
            while (ld_acq(q) < target) { __nanosleep(SPIN_NS); if (++it > (1 << 22)) __trap(); }
        };
        auto drain = [&]() {
            const int ls = sg == 0 ? H_STAGES - 1 : sg - 1;
            mbar_wait(bE + 8 * ls, sg == 0 ? ph : ph ^ 1);
        };
        while (true) {
            const unsigned tk0 = ld_relaxed1(g_ctr + C_HAA + lane), tk1 = ld_relaxed1(g_ctr + C_HAA + 32 + lane);
            const unsigned f0 = ld_relaxed1(g_flagA + lane), f1 = ld_relaxed1(g_flagA + 32 + lane);
            const unsigned tkf = ld_relaxed1(g_ctr + C_HF + min(lane, 12)), ca = ld_relaxed1(g_ctr + C_AA + fl);
            const unsigned cb0 = ld_relaxed1(g_ctr + C_AB + (lane > 10 ? 15 : f_row0(fl) / 128));
            const unsigned cb1 = ld_relaxed1(g_ctr + C_AB + (lane > 10 ? 15 : (f_row0(fl) + f_rows(fl) - 1) / 128));
            const bool e0 = tk0 < (unsigned)aa_units(lane), e1 = 32 + lane < AA_LATE && tk1 < (unsigned)aa_units(32 + lane);
            const unsigned a0 = __ballot_sync(0xffffffffu, e0 && f0 >= 192), a1 = __ballot_sync(0xffffffffu, e1 && f1 >= 192);
            const bool early_left = __any_sync(0xffffffffu, e0 || e1);
            const unsigned tl = __shfl_sync(0xffffffffu, tkf, 11), ts = __shfl_sync(0xffffffffu, tkf, 12);
            const bool fleft = lane < 11 && tkf < (unsigned)(f_ntiles(fl) * f_split(fl));
            const unsigned fl_m = __ballot_sync(0xffffffffu, fleft);
            const bool may = blockIdx.x >= (fl >= AA_B3 ? AA_CTAS3 : (fl >= 6 ? AA_CTAS2 : AA_CTAS)) || tl >= NLATE;
            const unsigned fr = __ballot_sync(0xffffffffu, fleft && ca >= (unsigned)(2 * f_rows(fl)) && cb0 >= 128 && cb1 >= 128 && may);
            if (a0 | a1) {
                const int as = a0 ? __ffs(a0) - 1 : 31 + __ffs(a1);
                const unsigned u = ticket(g_ctr + C_HAA + as);
                if (u < (unsigned)aa_units(as)) { acquire(); attn_a(as, u); continue; }
            }
            if (tl < NLATE && !early_left) {
                const bool ready = __shfl_sync(0xffffffffu, f1, (AA_LATE - 32 + tl / 6) & 31) >= 192;
                if (ready || (blockIdx.x < AA_CTAS3 && bdone)) {
                    drain();
                    const unsigned u = ticket(g_ctr + C_HF + 11);
                    if (u < NLATE) { spin_ge(g_flagA + AA_LATE + u / 6, 192); attn_a(AA_LATE + u / 6, u % 6); drain(); continue; }
                }
            }
            if (fr) {
                const int fm = __ffs(fr) - 1;
                const unsigned u = ticket(g_ctr + C_HF + fm);
                const int ks = f_split(fm), nt = f_ntiles(fm);
                if (u < (unsigned)(nt * ks)) {
                    const int kp = u / nt;
                    acquire();
                    gemm(nt == 3 ? T_F : T_FN, fm, u % nt, kp * 73 / ks, (kp + 1) * 73 / ks);
                    if (fm >= DRAIN_B) drain();
                    continue;
                }
            }
            if (ts < NSMALL && tl >= NLATE && __shfl_sync(0xffffffffu, cb0 >= 128, 11)) {
                const unsigned u = ticket(g_ctr + C_HF + 12);
                if (u < NSMALL) {
                    const int fm = 11, v = u;
                    const int nn = v % 9, kp = v / 9, kb0 = kp * 73 / f_split(fm), kb1 = (kp + 1) * 73 / f_split(fm);
                    for (int k0 = kb0; k0 < kb1; k0 += 3 * H_STAGES) {
                        const int sg0 = sg, k1 = min(kb1, k0 + 3 * H_STAGES);
                        for (int kb = k0; kb < k1; kb += 3) {
                            next(T_FS, fm, nn, kb0 | (kb1 << 8));
                            const int kk = kb + lane;
                            if (lane == 0) mbar_expect(bF + 8 * sg, min(3, k1 - kb) * 16384);
                            __syncwarp();
                            if (lane < 3 && kk < k1) {
                                tma2d(sb + sg * H_STAGE + lane * 16384 + 8192, kk >= 64 ? &tm.wo : &tm.Wo, nn * 64, (kk >= 64 ? kk - 64 : kk) * 64, bF + 8 * sg);
                                if (k0 > kb0) tma2d(sb + sg * H_STAGE + lane * 16384, &tm.O64, kk * 64, f_row0(fm), bF + 8 * sg);
                            }
                            adv();
                        }
                        if (k0 == kb0) {
                            spin_ge(g_ctr + C_AA + fm, 128);
                            if (k0 + lane < k1) {
                                const int q = (sg0 + lane / 3) % H_STAGES;
                                tma2d(sb + q * H_STAGE + (lane % 3) * 16384, &tm.O64, (k0 + lane) * 64, f_row0(fm), bF + 8 * q);
                            }
                            __syncwarp();
                        }
                    }
                    drain();
                    continue;
                }
            }
            if (a0 | a1 | fr) continue;
            if (!bdone) {
                const unsigned u = ticket(g_ctr + C_HB);
                if (u < NG0) {
                    gemm(T_G0, u / 9, u % 9, 0, 9);
                } else if (u < NB_UNITS) {
                    const int m = (u - NG0) / ABT, h0 = ((u - NG0) % ABT) * ABH, h1 = min(h0 + ABH, BH);
                    const int mm = min(max(0, m * 128 - 256) / 192 + lane, (m * 128 + 127) / 192);
                    const unsigned* q = lane == 31 ? g_ctr + C_GATE : g_ctr + C_G0 + mm;
                    int it = 0;
                    while (!__all_sync(0xffffffffu, ld_relaxed1(q) >= (lane == 31 ? 128u : 108u))) { __nanosleep(100); if (++it > (1 << 22)) __trap(); }
                    acquire();
                    for (int hh = h0; hh < h1; hh++) {
                        next(T_AB, m, hh, rr | (hh + 3 >= h1 ? 4 : 0)); rr = rr == 2 ? 0 : rr + 1;
                        if (lane == 0) {
                            const uint32_t a = sb + sg * H_STAGE, bar = bF + 8 * sg;
                            const int col = (hh >> 2) * 72 + (hh & 3) * 16;
                            mbar_expect(bar, 7 * 6144);
                            tma2d(a, &tm.qkv, col, m * 128, bar);
                            for (int j = 0; j < 3; j++) {
                                tma2d(a + (1 + j) * 6144, &tm.qkv, DM + col, (m - 2 + j) * 128, bar);
                                tma2d(a + (4 + j) * 6144, &tm.qkv, 2 * DM + col, (m - 2 + j) * 128, bar);
                            }
                        }
                        adv();
                    }
                } else bdone = true;
                continue;
            }
            if (fl_m == 0 && ts >= NSMALL) break;
            __nanosleep(150);
            if (++idle > (1 << 22)) __trap();
        }
        next(T_EXIT, 0, 0, 0);
        if (lane == 0) mbar_arrive(bF + 8 * sg);
    } else {
        asm volatile("setmaxnreg.inc.sync.aligned.u32 152;");
        const int wg = warp >> 2, wq = warp & 3;
        int sg = 0, ph = 0, skip = 0;
        unsigned pend = 0;
        auto release = [&](int q) { __syncwarp(); if (lane == 0) mbar_arrive(bE + 8 * q); };
        auto adv = [&]() { if (++sg == H_STAGES) { sg = 0; ph ^= 1; } };
        while (true) {
            mbar_wait(bF + 8 * sg, ph);
            uint32_t d[4];
            lds128(d, dsc + 16 * sg);
            const int ty = d[0];
            if (ty == T_EXIT) break;
            if ((ty == T_G0 && wg == 2 && d[1] == NBLK - 1) || ((ty == T_F || ty == T_FN) && wg == 2 && d[1] >= 9) || (ty == T_FS && wg != 0)) {
                release(sg); adv();
                if (ty == T_G0 && ++skip == 9) { skip = 0; signal(g_ctr + C_G0 + d[1], lane); }
            } else if (ty == T_G0 || ty == T_F) {
                gemm_unit<192>(ty, d, sb, bF, bE, sg, ph, warp, lane, out);
            } else if (ty == T_FN) {
                gemm_unit<96>(ty, d, sb, bF, bE, sg, ph, warp, lane, out);
            } else if (ty == T_FS) {
                gemm_unit<64>(ty, d, sb, bF, bE, sg, ph, warp, lane, out);
                if (tid == 0 && d[1] == NFB - 1) g_sync[0] = 0;
            } else {
                if ((int)(d[3] & 3) == wg) {
                    if (ty == T_AA) {
                        const uint32_t xr = sb + sg * H_STAGE + (wq >> 1) * 24576, mr = sb + sg * H_STAGE + 49152 + (wq >> 1) * 4096;
                        if ((wq + wg) & 1) attnA_unit<1>(xr, mr, d[1], d[2] + (wq >> 1), lane, bE + 8 * sg);
                        else attnA_unit<0>(xr, mr, d[1], d[2] + (wq >> 1), lane, bE + 8 * sg);
                        pend++;
                        if (d[3] & 4) { signal(g_ctr + C_AA + f_blk(d[1]), lane, pend); pend = 0; }
                    } else {
                        attnB_unit(sb + sg * H_STAGE, d[1] * 128, d[2], wq, lane, bE + 8 * sg);
                        pend++;
                        if (d[3] & 4) { signal(g_ctr + C_AB + d[1], lane, pend); pend = 0; }
                    }
                } else {
                    release(sg);
                }
                adv();
            }
        }
    }
}

__device__ float g_fmem[(NSEG + 1) * 8 * DM];
__device__ bf16 g_fq[8 * HD];
__device__ __forceinline__ int tile_off(int row, int e) { return row * 16 + ((((e >> 3) ^ (row >> 2)) & 1) << 3) + (e & 7); }

__global__ void fb_init(const bf16* __restrict__ mem0) {
    const int i = blockIdx.x * blockDim.x + threadIdx.x;
    if (i < (NSEG + 1) * 8 * DM) g_fmem[i] = i < 8 * DM ? __bfloat162float(mem0[i]) : 0.f;
    if (i < SEQ * DM) g_acc[i] = 0.f;
    if (i < 1920) g_ctr[i] = 0;
    if (i < NSEG) g_flagA[i] = 192;
}
__global__ void fb_proj(const bf16* __restrict__ x, const bf16* __restrict__ Wq, const bf16* __restrict__ Wk, const bf16* __restrict__ Wv, int seg) {
    __shared__ float in[8][DM];
    for (int i = threadIdx.x; i < 8 * DM; i += blockDim.x)
        in[i / DM][i % DM] = seg >= 0 ? __bfloat162float(__float2bfloat16(g_fmem[seg * 8 * DM + i])) : __bfloat162float(x[(size_t)blockIdx.y * 8 * DM + i]);
    __syncthreads();
    const int col = blockIdx.x * blockDim.x + threadIdx.x, ty = col / HD, hc = col % HD, h = hc / DH, d = (hc % DH) >> 4, e = hc & 15;
    const bf16* W = (ty == 0 ? Wq : (ty == 1 ? Wk : Wv)) + hc;
    float a[8] = {0.f, 0.f, 0.f, 0.f, 0.f, 0.f, 0.f, 0.f};
    for (int k = 0; k < DM; k++) {
        const float w = __bfloat162float(W[(size_t)k * HD]);
#pragma unroll
        for (int r = 0; r < 8; r++) a[r] += in[r][k] * w;
    }
    for (int r = 0; r < 8; r++) {
        const bf16 v = __float2bfloat16(a[r]);
        if (seg < 0) {
            const int pos = ty == 0 ? pos_q(d) : (ty == 1 ? pos_k(d) : pos_v(d));
            reinterpret_cast<bf16*>(g_xr)[((size_t)((blockIdx.y >> 2) * 32 + h) * 24 + pos) * 512 + tile_off((blockIdx.y & 3) * 8 + r, e)] = v;
        } else if (ty == 0) g_fq[r * HD + hc] = v;
        else reinterpret_cast<bf16*>(g_mr)[((size_t)(seg * 32 + h) * 16 + (ty == 1 ? mpos_k(d) : mpos_v(d))) * 128 + tile_off(r, e)] = v;
    }
}
__global__ void fb_attn(const bf16* __restrict__ Wo, int seg) {
    __shared__ float sc[8][40], o[8][DH];
    const int h = blockIdx.x, tid = threadIdx.x;
    const bf16* xr = reinterpret_cast<const bf16*>(g_xr) + (size_t)(seg * 32 + h) * 24 * 512;
    const bf16* mr = reinterpret_cast<const bf16*>(g_mr) + (size_t)(seg * 32 + h) * 16 * 128;
    {
        const int r = tid / 40, j = tid % 40;
        float a = 0.f;
        for (int c = 0; c < DH; c++) {
            const bf16 kv = j < 8 ? mr[mpos_k(c >> 4) * 128 + tile_off(j, c & 15)] : xr[pos_k(c >> 4) * 512 + tile_off(j - 8, c & 15)];
            a += __bfloat162float(g_fq[r * HD + h * DH + c]) * __bfloat162float(kv);
        }
        sc[r][j] = a * 0.08838834764831845f;
    }
    __syncthreads();
    if (tid < 8) {
        float m = sc[tid][0], z = 0.f;
        for (int j = 1; j < 40; j++) m = fmaxf(m, sc[tid][j]);
        for (int j = 0; j < 40; j++) { sc[tid][j] = __expf(sc[tid][j] - m); z += sc[tid][j]; }
        for (int j = 0; j < 40; j++) sc[tid][j] /= z;
    }
    __syncthreads();
    for (int i = tid; i < 8 * DH; i += 320) {
        const int r = i / DH, c = i % DH;
        float a = 0.f;
        for (int j = 0; j < 40; j++)
            a += sc[r][j] * __bfloat162float(j < 8 ? mr[mpos_v(c >> 4) * 128 + tile_off(j, c & 15)] : xr[pos_v(c >> 4) * 512 + tile_off(j - 8, c & 15)]);
        o[r][c] = __bfloat162float(__float2bfloat16(a));
    }
    __syncthreads();
    for (int n = tid; n < DM; n += 320) {
        float a[8] = {0.f, 0.f, 0.f, 0.f, 0.f, 0.f, 0.f, 0.f};
        for (int c = 0; c < DH; c++) {
            const float w = __bfloat162float(Wo[(size_t)(h * DH + c) * DM + n]);
#pragma unroll
            for (int r = 0; r < 8; r++) a[r] += o[r][c] * w;
        }
        for (int r = 0; r < 8; r++) atomicAdd(g_fmem + ((seg + 1) * 8 + r) * DM + n, a[r]);
    }
}

typedef CUresult (*EncodeFn)(CUtensorMap*, CUtensorMapDataType, cuuint32_t, void*, const cuuint64_t*, const cuuint64_t*,
                             const cuuint32_t*, const cuuint32_t*, CUtensorMapInterleave, CUtensorMapSwizzle,
                             CUtensorMapL2promotion, CUtensorMapFloatOOBfill);

static void make_map(EncodeFn fn, CUtensorMap* m, const void* ptr, uint64_t cols, uint64_t rows, uint32_t bc, uint32_t br,
                     CUtensorMapSwizzle sw = CU_TENSOR_MAP_SWIZZLE_128B, bool promote = false) {
    cuuint64_t dims[2] = {cols, rows};
    cuuint64_t strides[1] = {cols * 2};
    cuuint32_t box[2] = {bc, br};
    cuuint32_t es[2] = {1, 1};
    fn(m, CU_TENSOR_MAP_DATA_TYPE_BFLOAT16, 2, const_cast<void*>(ptr), dims, strides, box, es, CU_TENSOR_MAP_INTERLEAVE_NONE,
       sw, sw == CU_TENSOR_MAP_SWIZZLE_NONE && !promote ? CU_TENSOR_MAP_L2_PROMOTION_NONE : CU_TENSOR_MAP_L2_PROMOTION_L2_256B, CU_TENSOR_MAP_FLOAT_OOB_FILL_NONE);
}

extern "C" void kernel_launch(void* const* d_in, const int* in_sizes, int n_in, void* d_out, int out_size) {
    const bf16* x = (const bf16*)d_in[0];
    const bf16* mem0 = (const bf16*)d_in[1];
    const bf16* Wq = (const bf16*)d_in[2];
    const bf16* Wk = (const bf16*)d_in[3];
    const bf16* Wv = (const bf16*)d_in[4];
    const bf16* Wo = (const bf16*)d_in[5];
    const bf16* wqkv = (const bf16*)d_in[8];
    const bf16* wo = (const bf16*)d_in[9];
    const bf16* gw = (const bf16*)d_in[10];
    bf16* out = (bf16*)d_out;

    void* fp = nullptr;
    cudaDriverEntryPointQueryResult qr;
    cudaGetDriverEntryPoint("cuTensorMapEncodeTiled", &fp, cudaEnableDefault, &qr);
    EncodeFn enc = (EncodeFn)fp;
    void* pO = nullptr;
    cudaGetSymbolAddress(&pO, g_O);
    CUtensorMap tx32;
    HelpMaps hm;
    RecMaps rm;
    for (int r = 0; r < 2; r++) {
        make_map(enc, &rm.w[r][0], Wq, HD, DM, r ? 32 : 48, 144, CU_TENSOR_MAP_SWIZZLE_NONE, true);
        make_map(enc, &rm.w[r][1], Wk, HD, DM, r ? 32 : 48, 144, CU_TENSOR_MAP_SWIZZLE_NONE, true);
        make_map(enc, &rm.w[r][2], Wv, HD, DM, r ? 64 : 32, 144, CU_TENSOR_MAP_SWIZZLE_NONE, true);
    }
    make_map(enc, &rm.wo, Wo, DM, HD, 192, 128, CU_TENSOR_MAP_SWIZZLE_NONE, true);
    make_map(enc, &tx32, x, DM, SEQ, 64, 32);
    make_map(enc, &hm.x, x, DM, SEQ, 64, 192);
    make_map(enc, &hm.wqkv, wqkv, 3 * DM, DM, 64, 64);
    make_map(enc, &hm.O, pO, OK, SEQ, 64, 192);
    make_map(enc, &hm.O128, pO, OK, SEQ, 64, 128);
    make_map(enc, &hm.O64, pO, OK, SEQ, 64, 64);
    make_map(enc, &hm.Wo, Wo, DM, HD, 64, 64);
    make_map(enc, &hm.wo, wo, DM, DM, 64, 64);
    void* pQ = nullptr;
    cudaGetSymbolAddress(&pQ, g_qkvB);
    make_map(enc, &hm.qkv, pQ, 3 * DM, SEQ, 24, 128, CU_TENSOR_MAP_SWIZZLE_NONE);
    cudaFuncSetAttribute(k_rec, cudaFuncAttributeMaxDynamicSharedMemorySize, REC_SMEM);
    cudaFuncSetAttribute(k_help, cudaFuncAttributeMaxDynamicSharedMemorySize, HELP_SMEM);

    cudaStream_t st = cudaStreamPerThread;
    bool fast;
    int nsm = 132;
    cudaDeviceGetAttribute(&nsm, cudaDevAttrMultiProcessorCount, 0);
    {
        RecParams p{mem0, Wq, Wk, Wv, 880, 230};
        cudaLaunchConfig_t cfg = {};
        cfg.gridDim = dim3(96); cfg.blockDim = dim3(384); cfg.dynamicSmemBytes = REC_SMEM; cfg.stream = st;
        cudaLaunchAttribute at[1];
        at[0].id = cudaLaunchAttributeClusterDimension;
        at[0].val.clusterDim.x = 3; at[0].val.clusterDim.y = 1; at[0].val.clusterDim.z = 1;
        cfg.attrs = at; cfg.numAttrs = 1;
        int ncl = 0;
        fast = cudaOccupancyMaxActiveClusters(&ncl, k_rec, &cfg) == cudaSuccess && ncl >= NH;
        if (fast) {
            cudaLaunchKernelEx(&cfg, k_rec, tx32, rm, p);
        } else {
            fb_init<<<SEQ * DM / 256, 256, 0, st>>>(mem0);
            fb_proj<<<dim3(3 * HD / 256, SEQ / 8), 256, 0, st>>>(x, Wq, Wk, Wv, -1);
            for (int s = 0; s < NSEG; s++) {
                fb_proj<<<dim3(3 * HD / 128, 1), 128, 0, st>>>(x, Wq, Wk, Wv, s);
                if (s + 1 < NSEG) fb_attn<<<NH, 320, 0, st>>>(Wo, s);
            }
        }
    }
    {
        cudaLaunchConfig_t cfg = {};
        cfg.gridDim = dim3(nsm); cfg.blockDim = dim3(512); cfg.dynamicSmemBytes = HELP_SMEM; cfg.stream = st;
        cudaLaunchAttribute at[1];
        at[0].id = cudaLaunchAttributeProgrammaticStreamSerialization;
        at[0].val.programmaticStreamSerializationAllowed = 1;
        cfg.attrs = at; cfg.numAttrs = fast ? 1 : 0;
        cudaLaunchKernelEx(&cfg, k_help, hm, x, gw, out);
    }
}
```

```cpp
#include <cuda_runtime.h>
#include <cuda_bf16.h>
#include <cuda_fp16.h>
#include <cuda.h>
#include <stdint.h>

typedef __nv_bfloat16 bf16;

constexpr int SEQ = 2048, DM = 576, NH = 32, DH = 128, NSEG = 64;
constexpr int HD = NH * DH;
constexpr int OK = HD + DM;
constexpr int BH = 32, BD = 18;

__device__ bf16 g_O[SEQ * OK];
__device__ bf16 g_qkvB[SEQ * 3 * DM];
__device__ float g_acc[SEQ * DM];
__device__ float g_gate[SEQ];
__device__ float g_red[8 * 192 * 256];
__device__ uint4 g_redh[8 * 96 * 72];
__device__ unsigned g_sync[32];
__device__ unsigned g_ctr[1920];

__device__ __forceinline__ uint32_t s2u(const void* p) { return (uint32_t)__cvta_generic_to_shared(p); }
__device__ __forceinline__ uint32_t mapa(uint32_t a, uint32_t r) {
    uint32_t o; asm volatile("mapa.shared::cluster.u32 %0,%1,%2;" : "=r"(o) : "r"(a), "r"(r)); return o;
}
__device__ __forceinline__ void mbar_init(uint32_t a, int c) {
    asm volatile("mbarrier.init.shared::cta.b64 [%0],%1;" ::"r"(a), "r"(c) : "memory");
}
__device__ __forceinline__ void mbar_expect(uint32_t a, int bytes) {
    asm volatile("mbarrier.arrive.expect_tx.shared::cta.b64 _,[%0],%1;" ::"r"(a), "r"(bytes) : "memory");
}
__device__ __forceinline__ void mbar_arrive(uint32_t a) {
    asm volatile("mbarrier.arrive.shared::cta.b64 _,[%0];" ::"r"(a) : "memory");
}
__device__ __forceinline__ void mbar_wait(uint32_t a, int ph) {
    asm volatile("{.reg .pred p; .reg .u32 n; mov.u32 n,0;\n"
                 "WL%=: mbarrier.try_wait.parity.shared::cta.b64 p,[%0],%1; @p bra.uni WD%=;\n"
                 "add.u32 n,n,1; setp.lt.u32 p,n,4194304; @p bra.uni WL%=; trap;\n"
                 "WD%=: }" ::"r"(a), "r"(ph) : "memory");
}
__device__ __forceinline__ void bar_sync(int id, int n) { asm volatile("bar.sync %0,%1;" ::"r"(id), "r"(n) : "memory"); }
__device__ __forceinline__ void bar_arrive(int id, int n) { asm volatile("bar.arrive %0,%1;" ::"r"(id), "r"(n) : "memory"); }
__device__ __forceinline__ void cluster_sync() {
    asm volatile("barrier.cluster.arrive.release.aligned; barrier.cluster.wait.acquire.aligned;" ::: "memory");
}
__device__ __forceinline__ void cluster_sync_relaxed() {
    asm volatile("barrier.cluster.arrive.relaxed.aligned; barrier.cluster.wait.aligned;" ::: "memory");
}
__device__ __forceinline__ uint32_t lds32(uint32_t a) { uint32_t v; asm volatile("ld.shared.u32 %0,[%1];" : "=r"(v) : "r"(a) : "memory"); return v; }
__device__ __forceinline__ void fence_async() { asm volatile("fence.proxy.async.shared::cta;" ::: "memory"); }
__device__ __forceinline__ void ldsm4(uint32_t* r, uint32_t a) {
    asm volatile("ldmatrix.sync.aligned.m8n8.x4.shared.b16 {%0,%1,%2,%3},[%4];"
                 : "=r"(r[0]), "=r"(r[1]), "=r"(r[2]), "=r"(r[3]) : "r"(a) : "memory");
}
__device__ __forceinline__ void ldsm4t(uint32_t* r, uint32_t a) {
    asm volatile("ldmatrix.sync.aligned.m8n8.x4.trans.shared.b16 {%0,%1,%2,%3},[%4];"
                 : "=r"(r[0]), "=r"(r[1]), "=r"(r[2]), "=r"(r[3]) : "r"(a) : "memory");
}
__device__ __forceinline__ void ldsm2(uint32_t* r, uint32_t a) {
    asm volatile("ldmatrix.sync.aligned.m8n8.x2.shared.b16 {%0,%1},[%2];" : "=r"(r[0]), "=r"(r[1]) : "r"(a) : "memory");
}
__device__ __forceinline__ void ldsm2t(uint32_t* r, uint32_t a) {
    asm volatile("ldmatrix.sync.aligned.m8n8.x2.trans.shared.b16 {%0,%1},[%2];" : "=r"(r[0]), "=r"(r[1]) : "r"(a) : "memory");
}
__device__ __forceinline__ void mma16(float* c, const uint32_t* a, uint32_t b0, uint32_t b1) {
    asm("mma.sync.aligned.m16n8k16.row.col.f32.bf16.bf16.f32 {%0,%1,%2,%3},{%4,%5,%6,%7},{%8,%9},{%0,%1,%2,%3};"
                 : "+f"(c[0]), "+f"(c[1]), "+f"(c[2]), "+f"(c[3])
                 : "r"(a[0]), "r"(a[1]), "r"(a[2]), "r"(a[3]), "r"(b0), "r"(b1));
}
__device__ __forceinline__ void mma16v(float* c, const uint32_t* a, uint32_t b0, uint32_t b1) {
    asm volatile("mma.sync.aligned.m16n8k16.row.col.f32.bf16.bf16.f32 {%0,%1,%2,%3},{%4,%5,%6,%7},{%8,%9},{%0,%1,%2,%3};"
                 : "+f"(c[0]), "+f"(c[1]), "+f"(c[2]), "+f"(c[3])
                 : "r"(a[0]), "r"(a[1]), "r"(a[2]), "r"(a[3]), "r"(b0), "r"(b1));
}
__device__ __forceinline__ void mma8(float* c, uint32_t a0, uint32_t a1, uint32_t b0) {
    asm("mma.sync.aligned.m16n8k8.row.col.f32.bf16.bf16.f32 {%0,%1,%2,%3},{%4,%5},{%6},{%0,%1,%2,%3};"
                 : "+f"(c[0]), "+f"(c[1]), "+f"(c[2]), "+f"(c[3]) : "r"(a0), "r"(a1), "r"(b0));
}
__device__ __forceinline__ uint32_t pack2(float lo, float hi) {
    uint32_t r; asm("cvt.rn.bf16x2.f32 %0,%1,%2;" : "=r"(r) : "f"(hi), "f"(lo)); return r;
}
__device__ __forceinline__ float ex2(float x) { float y; asm("ex2.approx.ftz.f32 %0,%1;" : "=f"(y) : "f"(x)); return y; }
__device__ __forceinline__ void sts32(uint32_t a, uint32_t v) { asm volatile("st.shared.u32 [%0],%1;" ::"r"(a), "r"(v) : "memory"); }
__device__ __forceinline__ void sts128(uint32_t a, const uint32_t* v) {
    asm volatile("st.shared.v4.u32 [%0],{%1,%2,%3,%4};" ::"r"(a), "r"(v[0]), "r"(v[1]), "r"(v[2]), "r"(v[3]) : "memory");
}
__device__ __forceinline__ void lds128(uint32_t* v, uint32_t a) {
    asm volatile("ld.shared.v4.u32 {%0,%1,%2,%3},[%4];" : "=r"(v[0]), "=r"(v[1]), "=r"(v[2]), "=r"(v[3]) : "r"(a) : "memory");
}
__device__ __forceinline__ float2 lds64f(uint32_t a) {
    float2 v; asm volatile("ld.shared.v2.f32 {%0,%1},[%2];" : "=f"(v.x), "=f"(v.y) : "r"(a) : "memory"); return v;
}
__device__ __forceinline__ void tma2d(uint32_t dst, const CUtensorMap* m, int c0, int c1, uint32_t bar) {
    asm volatile("cp.async.bulk.tensor.2d.shared::cluster.global.mbarrier::complete_tx::bytes [%0],[%1,{%3,%4}],[%2];"
                 ::"r"(dst), "l"(m), "r"(bar), "r"(c0), "r"(c1) : "memory");
}
__device__ __forceinline__ void tma2d_mc(uint32_t dst, const CUtensorMap* m, int c0, int c1, uint32_t bar, uint16_t mask) {
    asm volatile("cp.async.bulk.tensor.2d.shared::cluster.global.mbarrier::complete_tx::bytes.multicast::cluster [%0],[%1,{%3,%4}],[%2],%5;"
                 ::"r"(dst), "l"(m), "r"(bar), "r"(c0), "r"(c1), "h"(mask) : "memory");
}
__device__ __forceinline__ uint64_t desc_sw128(uint32_t addr, uint32_t lbo, uint32_t sbo) {
    return (uint64_t)((addr & 0x3FFFF) >> 4) | ((uint64_t)(lbo >> 4) << 16) | ((uint64_t)(sbo >> 4) << 32) | (1ull << 62);
}
__device__ __forceinline__ void wg_fence() { asm volatile("wgmma.fence.sync.aligned;" ::: "memory"); }
__device__ __forceinline__ void wg_commit() { asm volatile("wgmma.commit_group.sync.aligned;" ::: "memory"); }
template <int N> __device__ __forceinline__ void wg_wait() { asm volatile("wgmma.wait_group.sync.aligned %0;" ::"n"(N) : "memory"); }

__device__ __forceinline__ void wgmma_rs_n32(float* d, const uint32_t* a, uint32_t dlo, int acc) {
    asm volatile("{.reg .pred p; .reg .b64 dd; setp.ne.b32 p,%21,0; mov.b64 dd,{%20,0x40000040};\n"
                 "wgmma.mma_async.sync.aligned.m64n32k16.f32.bf16.bf16 "
                 "{%0,%1,%2,%3,%4,%5,%6,%7,%8,%9,%10,%11,%12,%13,%14,%15},{%16,%17,%18,%19},dd,p,1,1,0;}"
                 : "+f"(d[0]), "+f"(d[1]), "+f"(d[2]), "+f"(d[3]), "+f"(d[4]), "+f"(d[5]), "+f"(d[6]), "+f"(d[7]),
                   "+f"(d[8]), "+f"(d[9]), "+f"(d[10]), "+f"(d[11]), "+f"(d[12]), "+f"(d[13]), "+f"(d[14]), "+f"(d[15])
                 : "r"(a[0]), "r"(a[1]), "r"(a[2]), "r"(a[3]), "r"(dlo), "r"(acc));
}

__device__ __forceinline__ void wgmma_ss_n32(float* d, uint32_t alo, uint32_t dlo, int acc) {
    asm volatile("{.reg .pred p; .reg .b64 da,dd; setp.ne.b32 p,%18,0; mov.b64 da,{%16,0x00000008}; mov.b64 dd,{%17,0x40000040};\n"
                 "wgmma.mma_async.sync.aligned.m64n32k16.f32.bf16.bf16 "
                 "{%0,%1,%2,%3,%4,%5,%6,%7,%8,%9,%10,%11,%12,%13,%14,%15},da,dd,p,1,1,0,0;}"
                 : "+f"(d[0]), "+f"(d[1]), "+f"(d[2]), "+f"(d[3]), "+f"(d[4]), "+f"(d[5]), "+f"(d[6]), "+f"(d[7]),
                   "+f"(d[8]), "+f"(d[9]), "+f"(d[10]), "+f"(d[11]), "+f"(d[12]), "+f"(d[13]), "+f"(d[14]), "+f"(d[15])
                 : "r"(alo), "r"(dlo), "r"(acc));
}

#define R8(b) "+f"(d[b]), "+f"(d[b + 1]), "+f"(d[b + 2]), "+f"(d[b + 3]), "+f"(d[b + 4]), "+f"(d[b + 5]), "+f"(d[b + 6]), "+f"(d[b + 7])
__device__ __forceinline__ void wgmma_ss_n192(float* d, uint64_t da, uint64_t db, int acc) {
    asm volatile("{.reg .pred p; setp.ne.b32 p,%98,0;\n"
                 "wgmma.mma_async.sync.aligned.m64n192k16.f32.bf16.bf16 "
                 "{%0,%1,%2,%3,%4,%5,%6,%7,%8,%9,%10,%11,%12,%13,%14,%15,%16,%17,%18,%19,%20,%21,%22,%23,"
                 "%24,%25,%26,%27,%28,%29,%30,%31,%32,%33,%34,%35,%36,%37,%38,%39,%40,%41,%42,%43,%44,%45,%46,%47,"
                 "%48,%49,%50,%51,%52,%53,%54,%55,%56,%57,%58,%59,%60,%61,%62,%63,%64,%65,%66,%67,%68,%69,%70,%71,"
                 "%72,%73,%74,%75,%76,%77,%78,%79,%80,%81,%82,%83,%84,%85,%86,%87,%88,%89,%90,%91,%92,%93,%94,%95},"
                 "%96,%97,p,1,1,0,1;}"
                 : R8(0), R8(8), R8(16), R8(24), R8(32), R8(40), R8(48), R8(56), R8(64), R8(72), R8(80), R8(88)
                 : "l"(da), "l"(db), "r"(acc));
}

__device__ __forceinline__ void wgmma_ss_n96(float* d, uint64_t da, uint64_t db) {
    asm volatile("wgmma.mma_async.sync.aligned.m64n96k16.f32.bf16.bf16 "
                 "{%0,%1,%2,%3,%4,%5,%6,%7,%8,%9,%10,%11,%12,%13,%14,%15,%16,%17,%18,%19,%20,%21,%22,%23,"
                 "%24,%25,%26,%27,%28,%29,%30,%31,%32,%33,%34,%35,%36,%37,%38,%39,%40,%41,%42,%43,%44,%45,%46,%47},%48,%49,1,1,1,0,1;"
                 : R8(0), R8(8), R8(16), R8(24), R8(32), R8(40) : "l"(da), "l"(db));
}
__device__ __forceinline__ void wgmma_ss_n64(float* d, uint64_t da, uint64_t db) {
    asm volatile("wgmma.mma_async.sync.aligned.m64n64k16.f32.bf16.bf16 "
                 "{%0,%1,%2,%3,%4,%5,%6,%7,%8,%9,%10,%11,%12,%13,%14,%15,%16,%17,%18,%19,%20,%21,%22,%23,"
                 "%24,%25,%26,%27,%28,%29,%30,%31},%32,%33,1,1,1,0,1;"
                 : R8(0), R8(8), R8(16), R8(24) : "l"(da), "l"(db));
}

constexpr int NSS = 1;
constexpr int QCH = 4, QD = 4;
constexpr int WRES = 2, WO_PRE2 = 3, WO_PRE3 = 4;
constexpr int MP = 1168;
constexpr int XT = 36864;
constexpr int XR_STAGE = 14 * 1024;
constexpr int MR_STAGE = 14 * 256;
constexpr int SM_X = 0;
constexpr int SM_XR = 2 * XT;
constexpr int SM_MR = SM_XR + 3 * XR_STAGE;
constexpr int SM_MEM = SM_XR + 2 * XT;
constexpr int SM_SC = SM_MEM + 8 * MP;
constexpr int SM_OB = SM_SC + 3 * 1536;
constexpr int SM_ZERO = SM_OB + 2048;
constexpr int SM_WO = SM_ZERO + 512;
constexpr int SM_WS = SM_WO + 49152;
constexpr int SM_BAR = SM_WS + NSS * 4096;
constexpr int REC_SMEM = SM_BAR + 128 + 1024;

__device__ uint4 g_xr[NSEG * NH * 24 * 64];
__device__ uint4 g_mr[NSEG * NH * 16 * 16];
__device__ unsigned g_flagA[NSEG];

constexpr unsigned long long FSP = 0x111123564ull;
__host__ __device__ constexpr int f_split(int m) { return m < 3 ? 1 : (int)((FSP >> (4 * (11 - m))) & 15); }
constexpr int F_FIRST_SPLIT = f_split(3) > 1 ? 3 : (f_split(4) > 1 ? 4 : (f_split(5) > 1 ? 5 : (f_split(6) > 1 ? 6 : 7)));
struct RecMaps { CUtensorMap w[2][3], wo; };
struct RecParams {
    const bf16* mem0; const bf16* Wq; const bf16* Wk; const bf16* Wv;
    int d0, dv;
};

__device__ __forceinline__ float* red_line(int s, int line) { return g_red + ((s >> 3) * 192 + line) * 256 + (s & 7) * 32; }

#define PIN(x) asm volatile("" : "+r"(x))
#define PINL(x) asm volatile("" : "+l"(x))
__device__ __forceinline__ float4 ld_relaxed4(const float* q) {
    float4 v;
    asm volatile("ld.relaxed.gpu.global.v4.f32 {%0,%1,%2,%3},[%4];" : "=f"(v.x), "=f"(v.y), "=f"(v.z), "=f"(v.w) : "l"(q) : "memory");
    return v;
}
__device__ __forceinline__ unsigned ld_acq(const unsigned* q) {
    unsigned v; asm volatile("ld.acquire.gpu.global.u32 %0,[%1];" : "=r"(v) : "l"(q) : "memory"); return v;
}
__device__ __forceinline__ unsigned ld_relaxed1(const unsigned* q) {
    unsigned v; asm volatile("ld.relaxed.gpu.global.u32 %0,[%1];" : "=r"(v) : "l"(q) : "memory"); return v;
}
__device__ __forceinline__ uint4 ld_relaxed4u(const uint4* q) {
    uint4 v;
    asm volatile("ld.relaxed.gpu.global.v4.u32 {%0,%1,%2,%3},[%4];" : "=r"(v.x), "=r"(v.y), "=r"(v.z), "=r"(v.w) : "l"(q) : "memory");
    return v;
}
__device__ __forceinline__ void reld_relaxed4u(uint4& v, const uint4* q) {
    asm volatile("{.reg .pred p; .reg .b32 q; and.b32 q,%3,0xffff; setp.ne.u32 p,q,0x5000;\n"
                 "@p ld.relaxed.gpu.global.v4.u32 {%0,%1,%2,%3},[%4];}"
                 : "+r"(v.x), "+r"(v.y), "+r"(v.z), "+r"(v.w) : "l"(q) : "memory");
}
__device__ __forceinline__ uint32_t packh2(float lo, float hi) {
    uint32_t r; asm("cvt.rn.f16x2.f32 %0,%1,%2;" : "=r"(r) : "f"(hi), "f"(lo)); return r;
}
__device__ __forceinline__ float maxn(float a, float b) {
    float r; asm("max.NaN.f32 %0,%1,%2;" : "=f"(r) : "f"(fabsf(a)), "f"(fabsf(b))); return r;
}
__device__ __forceinline__ void redh4(uint4* q, const float* v, uint32_t tag) {
    asm volatile("red.relaxed.gpu.global.add.noftz.v4.f16x2 [%0],{%1,%2,%3,%4};"
                 ::"l"(q), "r"(packh2(v[0], v[1])), "r"(packh2(v[2], v[3])), "r"(packh2(v[4], v[5])), "r"(tag) : "memory");
}
__device__ __forceinline__ void red4(float* q, float a, float b, float c2, float d) {
    asm volatile("red.relaxed.gpu.global.add.v4.f32 [%0],{%1,%2,%3,%4};" ::"l"(q), "f"(a), "f"(b), "f"(c2), "f"(d) : "memory");
}
__device__ __forceinline__ unsigned clk32() { return (unsigned)clock64(); }
__device__ __forceinline__ void spin_until(unsigned tl) {
    asm volatile("{.reg .pred p; .reg .u64 c; .reg .u32 lo,hi; .reg .s32 d;\n"
                 "SP%=: mov.u64 c,%%clock64; mov.b64 {lo,hi},c; sub.s32 d,lo,%0; setp.lt.s32 p,d,0; @p bra.uni SP%=;}" ::"r"(tl) : "memory");
}
__device__ __forceinline__ float rcp_fast(float x) { float y; asm("rcp.approx.ftz.f32 %0,%1;" : "=f"(y) : "f"(x)); return y; }
__device__ __forceinline__ void bulk_store(void* gdst, uint32_t src, int bytes) {
    asm volatile("cp.async.bulk.global.shared::cta.bulk_group [%0],[%1],%2;" ::"l"(gdst), "r"(src), "r"(bytes) : "memory");
}
__device__ __forceinline__ void bulk_load(uint32_t dst, const void* gsrc, int bytes, uint32_t bar) {
    asm volatile("cp.async.bulk.shared::cluster.global.mbarrier::complete_tx::bytes [%0],[%1],%2,[%3];"
                 ::"r"(dst), "l"(gsrc), "r"(bytes), "r"(bar) : "memory");
}
__device__ __forceinline__ void bulk_s2s(uint32_t rdst, uint32_t src, int bytes, uint32_t rbar) {
    asm volatile("cp.async.bulk.shared::cluster.shared::cta.mbarrier::complete_tx::bytes [%0],[%1],%2,[%3];"
                 ::"r"(rdst), "r"(src), "r"(bytes), "r"(rbar) : "memory");
}
__device__ __forceinline__ void stas4(uint32_t rdst, uint32_t a, uint32_t b, uint32_t c2, uint32_t d, uint32_t rbar) {
    asm volatile("st.async.weak.shared::cluster.mbarrier::complete_tx::bytes.v4.b32 [%0],{%1,%2,%3,%4},[%5];"
                 ::"r"(rdst), "r"(a), "r"(b), "r"(c2), "r"(d), "r"(rbar) : "memory");
}
__device__ __forceinline__ void stas2(uint32_t rdst, uint32_t a, uint32_t b, uint32_t rbar) {
    asm volatile("st.async.weak.shared::cluster.mbarrier::complete_tx::bytes.v2.b32 [%0],{%1,%2},[%3];"
                 ::"r"(rdst), "r"(a), "r"(b), "r"(rbar) : "memory");
}
__device__ __forceinline__ float4 lds128f(uint32_t a) {
    float4 v; asm volatile("ld.shared.v4.f32 {%0,%1,%2,%3},[%4];" : "=f"(v.x), "=f"(v.y), "=f"(v.z), "=f"(v.w) : "r"(a) : "memory"); return v;
}

__device__ __forceinline__ void flag_seg(int seg) {
    asm volatile("cp.async.bulk.wait_group 0;" ::: "memory");
    asm volatile("red.relaxed.gpu.global.add.u32 [%0],1;" ::"l"(g_flagA + seg) : "memory");
}

__global__ void __launch_bounds__(384, 1) k_rec(const __grid_constant__ CUtensorMap tmx, const __grid_constant__ RecMaps rm, const RecParams p) {
    extern __shared__ uint8_t smem_raw[];
    const uint32_t sb = (s2u(smem_raw) + 1023) & ~1023u;
    const int tid = threadIdx.x, warp = __shfl_sync(0xffffffffu, tid >> 5, 0), lane = tid & 31, g = lane >> 2, t = lane & 3;
    const int l7 = lane & 7, l3 = lane >> 3;
    const int c = blockIdx.x % 3, h = blockIdx.x / 3;
    const int nq = c < 2 ? 3 : 2, nv = 8 - 2 * nq, v0 = 2 * c;
    const uint32_t bXF = sb + SM_BAR, bVX = bXF + 16, bS = bVX + 16, bV = bS + 8, bW = bV + 8;
    const uint32_t peer1 = (c + 1) % 3, peer2 = (c + 2) % 3;
    auto vslot = [](int r, int d) { return (r < 2 ? 6 : 4) + ((d - 2 * r) & 7); };

    if (blockIdx.x == 0) {
        for (int i = tid; i < 1920; i += 384) g_ctr[i] = 0;
        if (tid < NSEG) g_flagA[tid] = 0;
        __threadfence();
        __syncthreads();
    }
    asm volatile("griddepcontrol.launch_dependents;" ::: "memory");
    auto wbox = [&](int ch, int ty) {
        tma2d(sb + SM_XR + (ch & 1) * XT + ty * nq * 4608, &rm.w[c == 2][ty], h * DH + c * (ty == 2 ? 32 : 48), ch * 144, bW + 8 * (ch & 1));
    };
    if (lane == 0 && warp >= 1 && warp < 6)
        asm volatile("prefetch.tensormap [%0];" ::"l"(warp < 4 ? &rm.w[c == 2][warp - 1] : (warp == 4 ? &rm.wo : &tmx)) : "memory");
    if (tid == 0) {
        for (int i = 0; i < 2; i++) { mbar_init(bXF + 8 * i, 1); mbar_init(bVX + 8 * i, 1); mbar_init(bW + 8 * i, 1); }
        mbar_init(bS, 4); mbar_init(bV, nv + 1); mbar_init(bW + 16, 1);
        asm volatile("fence.mbarrier_init.release.cluster;" ::: "memory");
        for (int i = 0; i < 2; i++) { mbar_expect(bW + 8 * i, XT); mbar_expect(bXF + 8 * i, XT); mbar_expect(bVX + 8 * i, (8 - nv) * 1024); }
        mbar_expect(bW + 16, 49152); mbar_expect(bS, 2560); mbar_expect(bV, (8 - nv) * 256);
    }
    __syncthreads();
    if (lane == 0) {
        if (warp >= 1 && warp < 4) { wbox(0, warp - 1); wbox(1, warp - 1); }
        if (warp == 4) tma2d(sb + SM_WO, &rm.wo, c * 192, h * DH, bW + 16);
        if (warp >= 5 && warp < 8) {
            const bf16* W = warp == 5 ? p.Wq : (warp == 6 ? p.Wk : p.Wv);
            asm volatile("cp.async.bulk.prefetch.L2.global [%0],24576;" ::"l"(reinterpret_cast<const uint8_t*>(W) + (size_t)(96 + blockIdx.x) * 24576) : "memory");
        }
    }
    __syncwarp();
    cluster_sync_relaxed();

    if (warp < 8) {
        asm volatile("setmaxnreg.inc.sync.aligned.u32 %0;" ::"n"(184));
        const bool isv = warp >= 2 * nq;
        const int slot = warp;
        uint32_t w[36][4];
        {
            const uint32_t pitch = (isv ? nv : nq) * 32;
            const uint32_t src = sb + SM_XR + (isv ? nq * 9216 + (warp - 2 * nq) * 32 : (warp >= nq ? nq * 4608 + (warp - nq) * 32 : warp * 32)) + 2 * t * pitch + g * 4;
#pragma unroll
            for (int ch = 0; ch < 4; ch++) {
                mbar_wait(bW + 8 * (ch & 1), ch >> 1);
#pragma unroll
                for (int kk = 0; kk < 9; kk++) {
                    const uint32_t q = src + (ch & 1) * XT + kk * 16 * pitch;
                    const uint32_t a = lds32(q), b = lds32(q + pitch), d = lds32(q + 8 * pitch), e = lds32(q + 9 * pitch);
                    uint32_t* o = w[ch * 9 + kk];
                    o[0] = __byte_perm(a, b, 0x5410); o[1] = __byte_perm(a, b, 0x7632);
                    o[2] = __byte_perm(d, e, 0x5410); o[3] = __byte_perm(d, e, 0x7632);
                }
                if (ch < 2) {
                    bar_sync(9, 256);
                    if (tid == 0) mbar_expect(bW + 8 * ch, XT);
                    if (lane == 0 && warp >= 1 && warp < 4) wbox(ch + 2, warp - 1);
                    __syncwarp();
                }
            }
#pragma unroll
            for (int k = 0; k < NSS; k++) {
                const uint32_t a = sb + SM_WS + k * 4096 + (warp >> 2) * 2048 + (warp & 3) * 256 + lane * 4;
                sts32(a, w[36 - NSS + k][0]); sts32(a + 128, w[36 - NSS + k][1]);
                sts32(a + 1024, w[36 - NSS + k][2]); sts32(a + 1152, w[36 - NSS + k][3]);
            }
            fence_async();
            bar_sync(9, 256);
            asm volatile("barrier.cluster.arrive.relaxed.aligned;" ::: "memory");
        }
        const uint32_t wsd = (((sb + SM_WS + (warp >> 2) * 2048) & 0x3FFFF) >> 4) | (64u << 16);
        const uint32_t woff = 2 * t * 32 + (((g >> 2) ^ (t >> 1)) << 4) + (g & 3) * 4;

        float d[16];
        auto xdesc = [&](int sl) { return __shfl_sync(0xffffffffu, (((sb + SM_X + sl * XT) & 0x3FFFF) >> 4) | 0x10000u, 0); };
        auto filler = [&](uint32_t xd, int stg) {
            wg_fence();
#pragma unroll
            for (int k = 36 - NSS; k < 36; k++) wgmma_ss_n32(d, wsd + (k - 36 + NSS) * 256, xd + ((k >> 2) * 256 + (k & 3) * 2), k > 36 - NSS);
#pragma unroll
            for (int k = 0; k < 36 - NSS; k++) wgmma_rs_n32(d, w[k], xd + ((k >> 2) * 256 + (k & 3) * 2), 1);
            wg_commit();
            wg_wait<0>();
            const uint32_t dst = sb + SM_XR + stg * XR_STAGE + slot * 1024 + woff;
#pragma unroll
            for (int j = 0; j < 4; j++) {
                sts32(dst + j * 256, pack2(d[4 * j], d[4 * j + 2]));
                sts32(dst + j * 256 + 32, pack2(d[4 * j + 1], d[4 * j + 3]));
            }
        };
        auto fwd_v = [&](int sl, int stg) {
            const uint32_t base = sb + SM_XR + stg * XR_STAGE;
            bulk_s2s(mapa(base + vslot(peer1, v0) * 1024, peer1), base + 2 * nq * 1024, nv * 1024, mapa(bVX + 8 * sl, peer1));
            bulk_s2s(mapa(base + vslot(peer2, v0) * 1024, peer2), base + 2 * nq * 1024, nv * 1024, mapa(bVX + 8 * sl, peer2));
        };

        mbar_wait(bXF, 0);
        filler(xdesc(0), 0);
        fence_async();
        bar_arrive(7, 288);
        bar_sync(9, 256);
        asm volatile("barrier.cluster.wait.aligned;" ::: "memory");
        if (tid == 32) fwd_v(0, 0);
        __syncwarp();
        mbar_wait(bXF + 8, 0);
        filler(xdesc(1), 1);
        bar_sync(9, 256);
        if (tid == 0) { mbar_expect(bXF, XT); mbar_expect(bXF + 8, XT); }
        cluster_sync_relaxed();
        if (tid == 0) {
            for (int sl = 0; sl < 2; sl++)
                for (int j = 0; j < 3; j++)
                    tma2d_mc(sb + SM_X + sl * XT + (c * 3 + j) * 4096, &tmx, (c * 3 + j) * 64, (2 + sl) * 32, bXF + 8 * sl, 7);
        }
        __syncwarp();
        uint32_t mema = sb + SM_MEM + l7 * MP + l3 * 16;
        const uint32_t xpeer = (g & 2) ? peer2 : peer1;
        const uint32_t rdst0 = mapa(sb + SM_MR + vslot(xpeer, v0 + warp - 2 * nq) * 256 + (2 * t + (g & 1)) * 32 + (((g >> 2) ^ (t >> 1)) << 4), xpeer);
        uint32_t rbar = mapa(bV, xpeer);
        int s3 = 0;
        for (int s = 0; s < NSEG; s++) {
            const int st = s & 1, s3n = s3 == 2 ? 0 : s3 + 1, s3p = s3 == 0 ? 2 : s3 - 1;
            uint32_t rdst = rdst0 + s3 * MR_STAGE;
            uint32_t ldst = sb + SM_MR + s3 * MR_STAGE + slot * 256 + woff;
            PIN(rdst); PIN(rbar); PIN(ldst); PIN(mema);
            float a[QCH][4];
#pragma unroll
            for (int i = 0; i < QCH; i++) { a[i][0] = 0.f; a[i][1] = 0.f; a[i][2] = 0.f; a[i][3] = 0.f; }
            uint32_t wx[NSS][4];
#pragma unroll
            for (int k = 0; k < NSS; k++)
                ldsm4(wx[k], sb + SM_WS + k * 4096 + (warp >> 2) * 2048 + (warp & 3) * 256 + (l3 >> 1) * 1024 + (l3 & 1) * 128 + l7 * 16);
            bar_sync(1, 384);
            if (isv) spin_until(clk32() + p.dv);
            uint32_t bf[18][4];
#pragma unroll
            for (int ii = 0; ii < QD; ii++) ldsm4(bf[17 - ii], mema + (17 - ii) * 64);
#pragma unroll
            for (int ii = 0; ii < 18; ii++) {
                const int i = 17 - ii;
                mma16v(a[(2 * i) % QCH], 2 * i >= 36 - NSS ? wx[2 * i - 36 + NSS] : w[2 * i], bf[i][0], bf[i][1]);
                mma16v(a[(2 * i + 1) % QCH], 2 * i + 1 >= 36 - NSS ? wx[2 * i + 1 - 36 + NSS] : w[2 * i + 1], bf[i][2], bf[i][3]);
                if (i - QD >= 0) ldsm4(bf[i - QD], mema + (i - QD) * 64);
            }
#pragma unroll
            for (int i = 0; i < 4; i++) {
                a[0][i] = (a[2][i] + a[3][i]) + (a[0][i] + a[1][i]);
            }
            const uint32_t w0 = pack2(a[0][0], a[0][2]), w1 = pack2(a[0][1], a[0][3]);
            sts32(ldst, w0); sts32(ldst + 32, w1);
            if (!isv) bar_arrive(8, nq * 64 + 96);
            if (isv && s + 1 < NSEG) {
                uint32_t snd = (g & 1) ? w0 : w1, keep = (g & 1) ? w1 : w0;
                uint32_t rcv = __shfl_xor_sync(0xffffffffu, snd, 4);
                uint32_t lo = (g & 1) ? rcv : keep, hi = (g & 1) ? keep : rcv;
                uint32_t olo = __shfl_xor_sync(0xffffffffu, lo, 8), ohi = __shfl_xor_sync(0xffffffffu, hi, 8);
                stas4(rdst, (g & 2) ? olo : lo, (g & 2) ? ohi : hi, (g & 2) ? lo : olo, (g & 2) ? hi : ohi, rbar);
                __syncwarp();
                if (lane == 0) mbar_arrive(bV);
            }
            const uint32_t xd = xdesc(st);
            if (s + 2 < NSEG) {
                mbar_wait(bXF + 8 * st, ((s + 2) >> 1) & 1);
            }
            fence_async();
            bar_arrive(7, 288);
            if (warp == 1) bar_sync(6, 256); else bar_arrive(6, 256);
            if (warp < 2) {
                if (s + 1 < NSEG) { mbar_wait(bS, st); mbar_wait(bV, st); }
                if (lane == 0) {
                    if (warp == 0) {
                        if (s >= 1 && s + 3 < NSEG) {
                            mbar_expect(bXF + 8 * (st ^ 1), XT);
                            for (int j = 0; j < 3; j++)
                                tma2d_mc(sb + SM_X + (st ^ 1) * XT + (c * 3 + j) * 4096, &tmx, (c * 3 + j) * 64, (s + 3) * 32, bXF + 8 * (st ^ 1), 7);
                        }
                    } else {
                        if (s >= 1) flag_seg(s - 1);
                        bulk_store(reinterpret_cast<uint8_t*>(g_mr) + (size_t)(s * 32 + h) * 4096 + c * 1280,
                                   sb + SM_MR + s3 * MR_STAGE + nq * 256, (8 - nq) * 256);
                        asm volatile("cp.async.bulk.commit_group;" ::: "memory");
                        if (s + 2 < NSEG) fwd_v(st ^ 1, s3n);
                    }
                }
                __syncwarp();
            }
            if (s + 2 < NSEG) {
                bar_sync(5, 384);
                filler(xd, s3p);
            } else {
                bar_sync(5, 384);
            }
            s3 = s3n;
        }
        if (tid == 32) flag_seg(NSEG - 1);
    } else {
        asm volatile("setmaxnreg.dec.sync.aligned.u32 %0;" ::"n"(136));
        const int wq = warp - 8, wt = tid - 256;
        uint32_t woa = sb + SM_WO + wt * 16;
        uint32_t am0 = 0;
        {
            for (int i = wt; i < 576; i += 128) g_redh[blockIdx.x * 576 + i] = make_uint4(0u, 0u, 0u, 0u);
            float4* z = reinterpret_cast<float4*>(g_red) + blockIdx.x * 1024;
            for (int i = wt; i < 1024; i += 128) z[i] = make_float4(0.f, 0.f, 0.f, 0.f);
            constexpr int ZN = (SEQ - F_FIRST_SPLIT * 192) * (DM / 4) / 96;
            float4* za = reinterpret_cast<float4*>(g_acc + F_FIRST_SPLIT * 192 * DM) + blockIdx.x * ZN;
            for (int i = wt; i < ZN; i += 128) za[i] = make_float4(0.f, 0.f, 0.f, 0.f);
            if (wt == 96) {
                for (int sl = 0; sl < 2; sl++)
                    for (int j = 0; j < 3; j++)
                        tma2d_mc(sb + SM_X + sl * XT + (c * 3 + j) * 4096, &tmx, (c * 3 + j) * 64, sl * 32, bXF + 8 * sl, 7);
            }
            __syncwarp();
        }
        {
            asm volatile("barrier.cluster.arrive.relaxed.aligned;" ::: "memory");
            uint32_t wo[24][4];
            mbar_wait(bW + 16, 0);
#pragma unroll
            for (int k = 0; k < 24; k++) {
                const uint32_t q = sb + SM_WO + ((k & 7) * 16 + 2 * t) * 384 + (k >> 3) * 128 + wq * 32 + g * 4;
                wo[k][0] = lds32(q); wo[k][1] = lds32(q + 384); wo[k][2] = lds32(q + 8 * 384); wo[k][3] = lds32(q + 9 * 384);
            }
            bar_sync(4, 128);
#pragma unroll
            for (int k = 0; k < 24; k++) {
                uint32_t a = wo[k][0], b = wo[k][1], d = wo[k][2], e = wo[k][3];
                wo[k][0] = __byte_perm(a, b, 0x5410); wo[k][1] = __byte_perm(a, b, 0x7632);
                wo[k][2] = __byte_perm(d, e, 0x5410); wo[k][3] = __byte_perm(d, e, 0x7632);
                sts128(woa + k * 2048, wo[k]);
            }
            sts32(sb + SM_ZERO + wt * 4, 0u);
            for (int i = wt; i < 8 * 72; i += 128) {
                const int r = i / 72, cc = i % 72;
                uint4 v = __ldg(reinterpret_cast<const uint4*>(p.mem0 + r * DM) + cc);
                am0 = __vmaxu2(__vmaxu2(am0, __vmaxu2(v.x & 0x7fff7fffu, v.y & 0x7fff7fffu)), __vmaxu2(v.z & 0x7fff7fffu, v.w & 0x7fff7fffu));
                asm volatile("st.shared.v4.u32 [%0],{%1,%2,%3,%4};" ::"r"(sb + SM_MEM + r * MP + cc * 16), "r"(v.x), "r"(v.y), "r"(v.z), "r"(v.w) : "memory");
            }
        }
        __threadfence();
        bar_sync(4, 128);
        if (wt == 0) asm volatile("red.relaxed.gpu.global.add.u32 [%0],1;" ::"l"(g_sync) : "memory");
        asm volatile("barrier.cluster.wait.aligned;" ::: "memory");
        cluster_sync_relaxed();
        bar_arrive(1, 384);
        if (wq == 3) bar_sync(7, 288);
        uint32_t wa[8][4], wb[8][4], wc[WRES + 1][4];
#pragma unroll
        for (int k = 0; k < 8; k++) lds128(wa[k], woa + k * 2048);
#pragma unroll
        for (int k = 0; k < 8; k++) lds128(wb[k], woa + (8 + k) * 2048);
#pragma unroll
        for (int k = 0; k < WRES; k++) lds128(wc[k], woa + (16 + k) * 2048);

        int ex;
        {
            const uint32_t m = __reduce_max_sync(0xffffffffu, max(am0 & 0xffffu, am0 >> 16));
            ex = m ? min(max(4 - ((int)(m >> 7) - 127), -60), 60) : 0;
        }
        const float SC = 0.08838834764831845f * 1.4426950408889634f;
        uint32_t L16 = lane * 16;
        uint32_t AB = (l3 >> 1) * 256 + l7 * 32 + (((l3 & 1) ^ (l7 >> 2)) << 4);
        uint32_t AA = (l3 & 1) * 256 + l7 * 32 + (((l3 >> 1) ^ (l7 >> 2)) << 4);
        const uint32_t scu = sb + SM_SC + c * 1536 + (wq == 0 ? 1024 : (wq - 1) * 512);
        const uint32_t sc1 = mapa(scu, peer1), sc2 = mapa(scu, peer2), sb1 = mapa(bS, peer1), sb2 = mapa(bS, peer2);
        const uint32_t wou = sb + SM_WO + wq * 512;
        const int vs = vslot(c, 2 * wq);
        auto publish = [&](int xs, int stg) {
            if (xs >= 1) flag_seg(xs - 1);
            if (xs < NSEG) {
                bulk_store(reinterpret_cast<uint8_t*>(g_xr) + (size_t)(xs * 96 + blockIdx.x) * 8192, sb + SM_XR + stg * XR_STAGE, 8192);
                asm volatile("cp.async.bulk.commit_group;" ::: "memory");
            }
        };
        int s3 = 0;
        for (int s = 0; s + 1 < NSEG; s++) {
            const int st = s & 1;
            const uint32_t xr = sb + SM_XR + s3 * XR_STAGE, mr = sb + SM_MR + s3 * MR_STAGE;
            PIN(L16); PIN(AB); PIN(AA);
            if (wq < 3) {
                uint32_t kf[3][4], q0[4], q1[4];
                float ca[4] = {0.f, 0.f, 0.f, 0.f}, cb[4] = {0.f, 0.f, 0.f, 0.f}, cc[4] = {0.f, 0.f, 0.f, 0.f};
                if (wq) {
                    const uint32_t ka = xr + nq * 1024 + (wq - 1) * 512 + AB;
                    ldsm4(kf[0], ka); ldsm4(kf[1], ka + 1024); ldsm4(kf[2], nq == 3 ? ka + 2048 : sb + SM_ZERO + AB);
                    uint32_t da1 = sc1 + L16, da2 = sc2 + L16, qa = mr + AA;
                    PIN(da1); PIN(da2); PIN(qa);
                    bar_sync(8, nq * 64 + 96);
                    ldsm4(q0, qa); ldsm4(q1, qa + 512);
                    float da[4] = {0.f, 0.f, 0.f, 0.f}, db[4] = {0.f, 0.f, 0.f, 0.f}, dc[4] = {0.f, 0.f, 0.f, 0.f};
                    mma16(ca, q0, kf[0][0], kf[0][1]); mma16(da, q0, kf[0][2], kf[0][3]);
                    mma16(cb, q0, kf[1][0], kf[1][1]); mma16(db, q0, kf[1][2], kf[1][3]);
                    mma16(cc, q1, kf[2][0], kf[2][1]); mma16(dc, q1, kf[2][2], kf[2][3]);
                    const uint32_t rr[4] = {__float_as_uint((ca[0] + cb[2]) + cc[0]), __float_as_uint((ca[1] + cb[3]) + cc[1]),
                                            __float_as_uint((da[0] + db[2]) + dc[0]), __float_as_uint((da[1] + db[3]) + dc[1])};
                    stas4(da1, rr[0], rr[1], rr[2], rr[3], sb1); stas4(da2, rr[0], rr[1], rr[2], rr[3], sb2);
                    sts128(scu + L16, rr);
                } else {
                    uint32_t da1 = sc1 + (L16 >> 1), da2 = sc2 + (L16 >> 1), qa = mr + AA, ka = mr + nq * 256 + AB;
                    uint32_t kb = nq == 3 ? ka + 512 : sb + SM_ZERO + AB;
                    PIN(da1); PIN(da2); PIN(qa); PIN(ka); PIN(kb);
                    bar_sync(8, nq * 64 + 96);
                    ldsm4(q0, qa); ldsm4(kf[0], ka); ldsm4(q1, qa + 512); ldsm2(kf[1], kb);
                    mma16(ca, q0, kf[0][0], kf[0][1]); mma16(cb, q0, kf[0][2], kf[0][3]); mma16(cc, q1, kf[1][0], kf[1][1]);
                    const uint32_t r0 = __float_as_uint((ca[0] + cb[2]) + cc[0]), r1 = __float_as_uint((ca[1] + cb[3]) + cc[1]);
                    stas2(da1, r0, r1, sb1); stas2(da2, r0, r1, sb2);
                    asm volatile("st.shared.v2.u32 [%0],{%1,%2};" ::"r"(scu + (L16 >> 1)), "r"(r0), "r"(r1) : "memory");
                }
                __syncwarp();
                if (L16 == 0) mbar_arrive(bS);
            } else {
                if (lane == 0) {
                    if (s >= 1 && s + 4 < NSEG)
                        asm volatile("prefetch.global.L2 [%0];" ::"l"(g_redh + (((s + 3) >> 3) * 96 + blockIdx.x) * 72 + ((s + 3) & 7) * 8));
                    publish(s, s3);
                    if (s == 0) {
                        int it = 0;
                        while (ld_acq(g_sync) < 96) { if (++it > (1 << 22)) __trap(); }
                    }
                }
                __syncwarp();
            }
            uint32_t va[2][2][4], vb[4];
            mbar_wait(bVX + 8 * st, (s >> 1) & 1);
            const uint32_t v0a = xr + vs * 1024 + AB;
            ldsm4t(va[0][0], v0a); ldsm4t(va[1][0], v0a + 1024);
            uint4* rl = g_redh + (((s >> 3) * 96 + c * 32 + wq * 4) * 9 + (s & 7)) * 8 + (L16 >> 7) * 72 + ((L16 >> 4) & 7);
            PINL(rl);
            mbar_wait(bS, s & 1);
            float4 sa, sbb; float2 sm2;
            {
                const uint32_t scl = sb + SM_SC + L16;
                const float4 a0 = lds128f(scl), a1 = lds128f(scl + 1536), a2 = lds128f(scl + 3072);
                const float4 b0 = lds128f(scl + 512), b1 = lds128f(scl + 2048), b2 = lds128f(scl + 3584);
                const uint32_t scm = sb + SM_SC + 1024 + (L16 >> 1);
                const float2 m0 = lds64f(scm), m1 = lds64f(scm + 1536), m2 = lds64f(scm + 3072);
                sa.x = a0.x + a1.x + a2.x; sa.y = a0.y + a1.y + a2.y; sa.z = a0.z + a1.z + a2.z; sa.w = a0.w + a1.w + a2.w;
                sbb.x = b0.x + b1.x + b2.x; sbb.y = b0.y + b1.y + b2.y; sbb.z = b0.z + b1.z + b2.z; sbb.w = b0.w + b1.w + b2.w;
                sm2.x = m0.x + m1.x + m2.x; sm2.y = m0.y + m1.y + m2.y;
            }
            float mx = fmaxf(fmaxf(fmaxf(sa.x, sa.y), fmaxf(sa.z, sa.w)), fmaxf(fmaxf(sbb.x, sbb.y), fmaxf(sbb.z, sbb.w)));
            mx = fmaxf(mx, fmaxf(sm2.x, sm2.y));
            {
                const float x1 = __shfl_xor_sync(0xffffffffu, mx, 1), x2 = __shfl_xor_sync(0xffffffffu, mx, 2), x3 = __shfl_xor_sync(0xffffffffu, mx, 3);
                ldsm4t(va[0][1], v0a + 512); ldsm4t(va[1][1], v0a + 1024 + 512);
                mbar_wait(bV, s & 1);
                ldsm4t(vb, mr + vs * 256 + AB);
                mx = fmaxf(fmaxf(mx, x1), fmaxf(x2, x3));
            }
            uint32_t ws[8][4];
#pragma unroll
            for (int k = WRES; k < WRES + WO_PRE2 && k < 8; k++) lds128(ws[k], wou + L16 + (16 + k) * 2048);
            const float mo = mx * SC;
            const float e0 = ex2(fmaf(sa.x, SC, -mo)), e1 = ex2(fmaf(sa.y, SC, -mo)), e2 = ex2(fmaf(sa.z, SC, -mo)), e3 = ex2(fmaf(sa.w, SC, -mo));
            float o0[4] = {0.f, 0.f, 0.f, 0.f}, o1[4] = {0.f, 0.f, 0.f, 0.f}, o2[4] = {0.f, 0.f, 0.f, 0.f};
            const uint32_t one = 0x3f803f80u, one4[4] = {one, one, one, one};
            { const uint32_t p0 = pack2(e0, e1), p1 = pack2(e2, e3); mma16(o0, va[0][0], p0, p1); mma16(o1, va[1][0], p0, p1); mma16(o2, one4, p0, p1); }
            const float e4 = ex2(fmaf(sbb.x, SC, -mo)), e5 = ex2(fmaf(sbb.y, SC, -mo)), e6 = ex2(fmaf(sbb.z, SC, -mo)), e7 = ex2(fmaf(sbb.w, SC, -mo));
            { const uint32_t p0 = pack2(e4, e5), p1 = pack2(e6, e7); mma16(o0, va[0][1], p0, p1); mma16(o1, va[1][1], p0, p1); mma16(o2, one4, p0, p1); }
            const float e8 = ex2(fmaf(sm2.x, SC, -mo)), e9 = ex2(fmaf(sm2.y, SC, -mo));
            { const uint32_t p0 = pack2(e8, e9); mma8(o0, vb[0], vb[1], p0); mma8(o1, vb[2], vb[3], p0); mma8(o2, one, one, p0); }
            {
                const uint32_t oa = sb + SM_OB + wq * 512 + (L16 >> 2);
                sts32(oa, pack2(o0[0], o0[1])); sts32(oa + 128, pack2(o0[2], o0[3]));
                sts32(oa + 256, pack2(o1[0], o1[1])); sts32(oa + 384, pack2(o1[2], o1[3]));
            }
            bar_sync(4, 128);
            uint32_t ob[4][4];
#pragma unroll
            for (int j = 0; j < 4; j++) ldsm4t(ob[j], sb + SM_OB + L16 + 512 * j);
            const float fs = __int_as_float((127 + ex) << 23);
            const float i0 = rcp_fast(o2[0]) * fs, i1 = rcp_fast(o2[1]) * fs;
            float v[12];
            {
                float r[6][4];
#pragma unroll
                for (int i = 0; i < 6; i++) { r[i][0] = 0.f; r[i][1] = 0.f; r[i][2] = 0.f; r[i][3] = 0.f; }
#pragma unroll
                for (int k = WRES + WO_PRE2; k < WRES + WO_PRE3 && k < 8; k++) lds128(ws[k], wou + L16 + (16 + k) * 2048);
#pragma unroll
                for (int i = 0; i < 8; i++) {
                    mma16v(r[(i & 1) ? 3 : 0], wa[i], ob[i >> 1][(i & 1) * 2], ob[i >> 1][(i & 1) * 2 + 1]);
                    mma16v(r[(i & 1) ? 4 : 1], wb[i], ob[i >> 1][(i & 1) * 2], ob[i >> 1][(i & 1) * 2 + 1]);
                    mma16v(r[(i & 1) ? 5 : 2], i < WRES ? wc[i] : ws[i], ob[i >> 1][(i & 1) * 2], ob[i >> 1][(i & 1) * 2 + 1]);
                    if (i + WRES + WO_PRE3 < 8) lds128(ws[i + WRES + WO_PRE3], wou + L16 + (16 + i + WRES + WO_PRE3) * 2048);
                }
#pragma unroll
                for (int j = 0; j < 3; j++) {
                    { r[j][0] += r[3 + j][0]; r[j][1] += r[3 + j][1]; r[j][2] += r[3 + j][2]; r[j][3] += r[3 + j][3]; }
                    v[4 * j] = r[j][0] * i0; v[4 * j + 1] = r[j][2] * i0; v[4 * j + 2] = r[j][1] * i1; v[4 * j + 3] = r[j][3] * i1;
                }
                const float m8 = maxn(maxn(maxn(v[0], v[1]), maxn(v[2], v[3])), maxn(maxn(v[4], v[5]), maxn(v[6], v[7])));
                const float m = maxn(maxn(maxn(v[8], v[9]), maxn(v[10], v[11])), m8);
                const uint32_t tag = m < 1024.f ? (m >= 0.0625f ? 0x3c003c00u : 0x00003c00u) : 0x54003c00u;
                redh4(rl, v, tag);
                bar_arrive(5, 384);
                redh4(rl + 16 * 72, v + 6, tag);
            }
            const unsigned tred = clk32();
            if (wq == 3) bar_sync(7, 288);
            if (wt == 0) {
                if (s + 2 < NSEG) { mbar_expect(bS, 2560); mbar_expect(bV, (8 - nv) * 256); }
                if (s + 3 < NSEG) mbar_expect(bVX + 8 * st, (8 - nv) * 1024);
            }
            {
                const uint4* gl = rl - c * 32 * 72;
                uint32_t ma = sb + SM_MEM + wq * 32 + ((L16 >> 4) & 3) * (2 * MP) + (L16 >> 6) * 4;
                PINL(gl); PIN(ma);
                unsigned tl = tred + p.d0;
                spin_until(tl);
                uint4 u[2][3];
#pragma unroll
                for (int j = 0; j < 2; j++)
#pragma unroll
                    for (int cc = 0; cc < 3; cc++) u[j][cc] = ld_relaxed4u(gl + (cc * 32 + j * 16) * 72);
                const uint32_t rebias = (uint32_t)(112 - ex) * 0x00800080u;
                int it = 0;
                auto cvt = [&](uint32_t x) { return ((((x + 0x00030004u) & 0x7ff87ff8u) >> 3) + rebias) | (x & 0x80008000u); };
                auto put = [&](int j, int cc) {
                    sts32(ma + (cc * 192 + ((3 * j) >> 1) * 64) * 2 + ((3 * j) & 1) * MP, u[j][cc].x);
                    sts32(ma + (cc * 192 + ((3 * j + 1) >> 1) * 64) * 2 + ((3 * j + 1) & 1) * MP, u[j][cc].y);
                    sts32(ma + (cc * 192 + ((3 * j + 2) >> 1) * 64) * 2 + ((3 * j + 2) & 1) * MP, u[j][cc].z);
                };
#pragma unroll
                for (int j = 0; j < 2; j++)
#pragma unroll
                    for (int cc = 0; cc < 3; cc++) {
                        u[j][cc].x = cvt(u[j][cc].x); u[j][cc].y = cvt(u[j][cc].y); u[j][cc].z = cvt(u[j][cc].z);
                        put(j, cc);
                    }
                {
                    const uint32_t bad = ((u[0][0].w ^ 0x5000u) | (u[0][1].w ^ 0x5000u) | (u[0][2].w ^ 0x5000u)) |
                                         ((u[1][0].w ^ 0x5000u) | (u[1][1].w ^ 0x5000u) | (u[1][2].w ^ 0x5000u));
                    const uint32_t tg = max(max(max(u[0][0].w, u[0][1].w), u[0][2].w), max(max(u[1][0].w, u[1][1].w), u[1][2].w));
                    const bool clean = __all_sync(0xffffffffu, (bad & 0xffffu) == 0 && tg < 0x54000000u);
                    const bool big = __any_sync(0xffffffffu, tg >= 0x3c000000u);
                    if (__builtin_expect(!(clean && big), 0)) {
                        while (true) {
                            bool ok = true;
#pragma unroll
                            for (int j = 0; j < 2; j++)
#pragma unroll
                                for (int cc = 0; cc < 3; cc++) ok = ok && (u[j][cc].w & 0xffffu) == 0x5000u;
                            if (__all_sync(0xffffffffu, ok)) break;
                            if (++it > (1 << 20)) __trap();
                            uint32_t redo = 0;
#pragma unroll
                            for (int j = 0; j < 2; j++)
#pragma unroll
                                for (int cc = 0; cc < 3; cc++) {
                                    if ((u[j][cc].w & 0xffffu) != 0x5000u) redo |= 1u << (j * 3 + cc);
                                    reld_relaxed4u(u[j][cc], gl + (cc * 32 + j * 16) * 72);
                                }
#pragma unroll
                            for (int j = 0; j < 2; j++)
#pragma unroll
                                for (int cc = 0; cc < 3; cc++) {
                                    const bool rd = (redo >> (j * 3 + cc)) & 1;
                                    u[j][cc].x = rd ? cvt(u[j][cc].x) : u[j][cc].x; u[j][cc].y = rd ? cvt(u[j][cc].y) : u[j][cc].y;
                                    u[j][cc].z = rd ? cvt(u[j][cc].z) : u[j][cc].z;
                                    put(j, cc);
                                }
                        }
                        const uint32_t t2 = max(max(max(u[0][0].w, u[0][1].w), u[0][2].w), max(max(u[1][0].w, u[1][1].w), u[1][2].w));
                        if (__any_sync(0xffffffffu, t2 >= 0x54000000u) || !__any_sync(0xffffffffu, t2 >= 0x3c000000u)) {
                            const float isc = __int_as_float((127 - ex) << 23);
                            float* fl = red_line(s, c * 64 + wq * 4 + (L16 >> 7)) + ((L16 >> 2) & 28);
#pragma unroll
                            for (int i = 0; i < 4; i++) red4(fl + i * 16 * 256, v[3 * i], v[3 * i + 1], v[3 * i + 2], 1.0f);
                            const float* fg = fl - c * 64 * 256;
#pragma unroll
                            for (int j = 0; j < 2; j++)
#pragma unroll
                                for (int cc = 0; cc < 3; cc++) {
                                    float4 a, b;
                                    while (true) {
                                        a = ld_relaxed4(fg + (cc * 64 + j * 32) * 256); b = ld_relaxed4(fg + (cc * 64 + j * 32 + 16) * 256);
                                        if (__all_sync(0xffffffffu, a.w == 32.f && b.w == 32.f)) break;
                                        if (++it > (1 << 20)) __trap();
                                    }
                                    u[j][cc].x = pack2(a.x * isc, a.y * isc); u[j][cc].y = pack2(a.z * isc, b.x * isc); u[j][cc].z = pack2(b.y * isc, b.z * isc);
                                    put(j, cc);
                                }
                        }
                    }
                }
                bar_arrive(1, 384);
                uint32_t am = max(max(u[0][0].x << 1, u[0][1].y << 1), max(u[1][1].x << 1, u[1][2].y << 1));
                am = __reduce_max_sync(0xffffffffu, am >> 24);
                if (am) ex = min(max(4 - ((int)am - 127), -60), 60);
                s3 = s3 == 2 ? 0 : s3 + 1;
            }
        }
        if (wt == 96) publish(NSEG - 1, 0);
        __syncwarp();
        if (wq < 3) bar_sync(8, nq * 64 + 96);
        bar_arrive(5, 384);
        if (wt == 96) publish(NSEG, 1);
        __syncwarp();
        if (wq == 3) bar_sync(7, 288);
    }
    cluster_sync();
}

constexpr int H_STAGES = 4, H_STAGE = 57344;
constexpr int HELP_SMEM = H_STAGES * H_STAGE + 1024 + 256;
constexpr int NBLK = 11;
enum { T_EXIT = 0, T_G0, T_F, T_AB, T_AA, T_FS, T_FN };
enum { C_HG = 0, C_HB = 32, C_GATE = 33, C_G0 = 48, C_AB = 64, C_HF = 96, C_AA = 128, C_HAA = 160, C_F = 256 };
constexpr int NG0 = NBLK * 9;
constexpr int ABH = 6;
constexpr int ABT = (BH + ABH - 1) / ABH;
constexpr int NB_UNITS = NG0 + 16 * ABT;
__host__ __device__ constexpr int aa_units(int seg) { return seg < 36 ? 3 : 6; }
constexpr unsigned AA_CTAS = 4;
constexpr unsigned AA_CTAS2 = 8;
constexpr unsigned AA_CTAS3 = 18;
constexpr int AA_B3 = 9;
constexpr int AA_LATE = 61;
constexpr int NFB = 12;
__host__ __device__ constexpr int f_row0(int m) { return m < 10 ? m * 192 : 1856 + (m - 10) * 128; }
__host__ __device__ constexpr int f_rows(int m) { return m < 9 ? 192 : (m < 11 ? 128 : 64); }
__host__ __device__ constexpr int f_blk(int seg) { return seg < 54 ? seg / 6 : 9 + (seg - 54) / 4; }
constexpr int DRAIN_B = 5;
constexpr int SPIN_NS = 20;
constexpr int FNM = 0x7f0;
__host__ __device__ constexpr int f_ntiles(int m) { return m < 11 ? (((FNM >> m) & 1) ? 6 : 3) : 9; }

__device__ __forceinline__ void signal(unsigned* q, int lane, unsigned n = 1) {
    __syncwarp();
    if (lane == 0) asm volatile("red.release.gpu.global.add.u32 [%0],%1;" ::"l"(q), "r"(n) : "memory");
}

__device__ __forceinline__ int pos_q(int d) { return (d / 3) * 8 + d % 3; }
__device__ __forceinline__ int pos_k(int d) { return (d / 3) * 8 + d % 3 + (d < 6 ? 3 : 2); }
__device__ __forceinline__ int mpos_k(int d) { return (d / 3) * 5 + d % 3; }
__device__ __forceinline__ int mpos_v(int d) { return d < 2 ? 3 + d : (d < 4 ? 6 + d : 8 + d); }
__device__ __forceinline__ int pos_v(int d) { return d < 2 ? 6 + d : (d < 4 ? 12 + d : 16 + d); }

__device__ __forceinline__ uint4 quad_tr(const uint32_t* v, int t) {
    uint32_t a0 = (t & 1) ? v[0] : v[1], a1 = (t & 1) ? v[2] : v[3];
    a0 = __shfl_xor_sync(0xffffffffu, a0, 1); a1 = __shfl_xor_sync(0xffffffffu, a1, 1);
    const uint32_t b0 = (t & 1) ? a0 : v[0], b1 = (t & 1) ? v[1] : a0, b2 = (t & 1) ? a1 : v[2], b3 = (t & 1) ? v[3] : a1;
    uint32_t c0 = (t & 2) ? b0 : b2, c1 = (t & 2) ? b1 : b3;
    c0 = __shfl_xor_sync(0xffffffffu, c0, 2); c1 = __shfl_xor_sync(0xffffffffu, c1, 2);
    uint4 o;
    o.x = (t & 2) ? c0 : b0; o.y = (t & 2) ? c1 : b1; o.z = (t & 2) ? b2 : c0; o.w = (t & 2) ? b3 : c1;
    return o;
}
template <int BN>
__device__ __forceinline__ void store_tile(const float* acc, bf16* q, int pitch, int t) {
#pragma unroll
    for (int j = 0; j < BN / 32; j++) {
        uint32_t lo[4], hi[4];
#pragma unroll
        for (int i = 0; i < 4; i++) {
            lo[i] = pack2(acc[16 * j + 4 * i], acc[16 * j + 4 * i + 1]); hi[i] = pack2(acc[16 * j + 4 * i + 2], acc[16 * j + 4 * i + 3]);
        }
        *reinterpret_cast<uint4*>(q + j * 32 + t * 8) = quad_tr(lo, t);
        *reinterpret_cast<uint4*>(q + (size_t)8 * pitch + j * 32 + t * 8) = quad_tr(hi, t);
    }
}

template <int MT>
__device__ __forceinline__ void attnA_unit(uint32_t xr, uint32_t mr, int s, int h, int lane, uint32_t rel) {
    const int g = lane >> 2, t = lane & 3, l7 = lane & 7, l3 = lane >> 3;
    const float SC = 0.08838834764831845f * 1.4426950408889634f;
    constexpr int NT = MT ? 5 : 3;
    const uint32_t offA = (l7 + (l3 & 1) * 8) * 32 + (((l3 >> 1) ^ (l7 >> 2)) << 4);
    const uint32_t offB = (l7 + (l3 >> 1) * 8) * 32 + (((l3 & 1) ^ (l7 >> 2)) << 4);
    float sa[NT][4];
#pragma unroll
    for (int n = 0; n < NT; n++)
#pragma unroll
        for (int i = 0; i < 4; i++) sa[n][i] = 0.f;
#pragma unroll
    for (int hf = 0; hf < 2; hf++) {
        uint32_t qf[4][4], k0[4][4], k1[4][4], km[4][2];
#pragma unroll
        for (int i = 0; i < 4; i++) {
            const int d = hf * 4 + i;
            ldsm4(qf[i], xr + pos_q(d) * 1024 + MT * 512 + offA);
            ldsm2(km[i], mr + mpos_k(d) * 256 + (offB & 255));
            ldsm4(k0[i], xr + pos_k(d) * 1024 + offB);
            if (MT) ldsm4(k1[i], xr + pos_k(d) * 1024 + 512 + offB);
        }
#pragma unroll
        for (int i = 0; i < 4; i++) {
            mma16(sa[0], qf[i], km[i][0], km[i][1]);
            mma16(sa[1], qf[i], k0[i][0], k0[i][1]); mma16(sa[2], qf[i], k0[i][2], k0[i][3]);
            if (MT) { mma16(sa[NT - 2], qf[i], k1[i][0], k1[i][1]); mma16(sa[NT - 1], qf[i], k1[i][2], k1[i][3]); }
        }
    }
    if (2 * t > g) sa[NT - 2][0] = -INFINITY;
    if (2 * t + 1 > g) sa[NT - 2][1] = -INFINITY;
    sa[NT - 1][0] = -INFINITY; sa[NT - 1][1] = -INFINITY;
    if (2 * t > g) sa[NT - 1][2] = -INFINITY;
    if (2 * t + 1 > g) sa[NT - 1][3] = -INFINITY;
    float m0 = fmaxf(sa[0][0], sa[0][1]), m1 = fmaxf(sa[0][2], sa[0][3]);
#pragma unroll
    for (int n = 1; n < NT; n++) { m0 = fmaxf(m0, fmaxf(sa[n][0], sa[n][1])); m1 = fmaxf(m1, fmaxf(sa[n][2], sa[n][3])); }
    m0 = fmaxf(m0, __shfl_xor_sync(0xffffffffu, m0, 1)); m1 = fmaxf(m1, __shfl_xor_sync(0xffffffffu, m1, 1));
    m0 = fmaxf(m0, __shfl_xor_sync(0xffffffffu, m0, 2)); m1 = fmaxf(m1, __shfl_xor_sync(0xffffffffu, m1, 2));
    m0 *= SC; m1 *= SC;
    float s0 = 0.f, s1 = 0.f;
#pragma unroll
    for (int n = 0; n < NT; n++) {
        sa[n][0] = ex2(fmaf(sa[n][0], SC, -m0)); sa[n][1] = ex2(fmaf(sa[n][1], SC, -m0));
        sa[n][2] = ex2(fmaf(sa[n][2], SC, -m1)); sa[n][3] = ex2(fmaf(sa[n][3], SC, -m1));
        s0 += sa[n][0] + sa[n][1]; s1 += sa[n][2] + sa[n][3];
    }
    s0 += __shfl_xor_sync(0xffffffffu, s0, 1); s1 += __shfl_xor_sync(0xffffffffu, s1, 1);
    s0 += __shfl_xor_sync(0xffffffffu, s0, 2); s1 += __shfl_xor_sync(0xffffffffu, s1, 2);
    s0 = rcp_fast(s0); s1 = rcp_fast(s1);
    uint32_t pa[NT][2];
#pragma unroll
    for (int n = 0; n < NT; n++) { pa[n][0] = pack2(sa[n][0] * s0, sa[n][1] * s0); pa[n][1] = pack2(sa[n][2] * s1, sa[n][3] * s1); }
    const uint32_t p0[4] = {pa[1][0], pa[1][1], pa[2][0], pa[2][1]}, p1[4] = {pa[NT - 2][0], pa[NT - 2][1], pa[NT - 1][0], pa[NT - 1][1]};
    bf16* op = g_O + (size_t)(s * 32 + MT * 16 + g) * OK + h * DH + t * 8;
#pragma unroll
    for (int dh = 0; dh < 2; dh++) {
        uint32_t f0[4][4], f1[4][4], f2[4][2];
#pragma unroll
        for (int n2 = 0; n2 < 4; n2++) {
            const int d = dh * 4 + n2;
            ldsm4t(f0[n2], xr + pos_v(d) * 1024 + offA);
            if (MT) ldsm4t(f1[n2], xr + pos_v(d) * 1024 + 512 + offA);
            ldsm2t(f2[n2], mr + mpos_v(d) * 256 + (offB & 255));
        }
        uint32_t lo[8], hi[8];
#pragma unroll
        for (int n2 = 0; n2 < 4; n2++) {
            float oa0[4] = {0.f, 0.f, 0.f, 0.f}, oa1[4] = {0.f, 0.f, 0.f, 0.f};
            mma16(oa0, p0, f0[n2][0], f0[n2][1]); mma16(oa1, p0, f0[n2][2], f0[n2][3]);
            if (MT) { mma16(oa0, p1, f1[n2][0], f1[n2][1]); mma16(oa1, p1, f1[n2][2], f1[n2][3]); }
            mma8(oa0, pa[0][0], pa[0][1], f2[n2][0]); mma8(oa1, pa[0][0], pa[0][1], f2[n2][1]);
            lo[2 * n2] = pack2(oa0[0], oa0[1]); hi[2 * n2] = pack2(oa0[2], oa0[3]);
            lo[2 * n2 + 1] = pack2(oa1[0], oa1[1]); hi[2 * n2 + 1] = pack2(oa1[2], oa1[3]);
        }
        if (dh == 1) { __syncwarp(); if (lane == 0) mbar_arrive(rel); }
#pragma unroll
        for (int q = 0; q < 2; q++) {
            *reinterpret_cast<uint4*>(op + dh * 64 + q * 32) = quad_tr(lo + 4 * q, t);
            *reinterpret_cast<uint4*>(op + (size_t)8 * OK + dh * 64 + q * 32) = quad_tr(hi + 4 * q, t);
        }
    }
}

template <int V> struct IC { static constexpr int value = V; };
__device__ __forceinline__ void attnB_unit(uint32_t sQ, int q0, int hh, int wq, int lane, uint32_t rel) {
    const int g = lane >> 2, t = lane & 3, l7 = lane & 7, l3 = lane >> 3;
    const uint32_t sK = sQ + 128 * 48, sV = sK + 384 * 48;
    const int sh = (hh & 3) * 2;
    uint32_t qa[2][4], qb[2][2];
#pragma unroll
    for (int m = 0; m < 2; m++) {
        ldsm4(qa[m], sQ + (wq * 32 + m * 16 + l7 + (l3 & 1) * 8) * 48 + (l3 >> 1) * 16);
        ldsm2(qb[m], sQ + (wq * 32 + m * 16 + l7 + (l3 & 1) * 8) * 48 + 32);
        if (2 * t < sh) { qa[m][0] = 0u; qa[m][1] = 0u; }
        if (16 + 2 * t >= sh + 18) { qb[m][0] = 0u; qb[m][1] = 0u; }
    }
    const bool one0 = (sh == 6 && g == 0), one2 = (sh != 6 && g == 7);
    float gt[2][2];
#pragma unroll
    for (int m = 0; m < 2; m++) { gt[m][0] = __ldcg(g_gate + q0 + wq * 32 + m * 16 + g); gt[m][1] = __ldcg(g_gate + q0 + wq * 32 + m * 16 + g + 8); }
    const float SC = 0.23570226039551584f * 1.4426950408889634f;
    float o[2][3][4];
    float mx[2][2];
#pragma unroll
    for (int m = 0; m < 2; m++) {
        mx[m][0] = -INFINITY; mx[m][1] = -INFINITY;
#pragma unroll
        for (int n = 0; n < 3; n++)
#pragma unroll
            for (int i = 0; i < 4; i++) o[m][n][i] = 0.f;
    }
    const int tfirst = max(0, (256 - q0) / 16 - 2 * wq);
    const uint32_t kb0 = sK + (wq * 32 + l7 + (l3 >> 1) * 8) * 48 + (l3 & 1) * 16;
    const uint32_t kb1 = sK + (wq * 32 + l7 + (l3 & 1) * 8) * 48 + 32;
    const uint32_t vb0 = sV + (wq * 32 + l7 + (l3 & 1) * 8) * 48 + (l3 >> 1) * 16;
    const uint32_t vb1 = sV + (wq * 32 + l7 + (l3 & 1) * 8) * 48 + 32;
    constexpr int CH = 3;
    auto chunk = [&](auto mode, int c0) {
        constexpr int MODE = decltype(mode)::value;
        auto dead = [](int m, int u) { return (MODE == 0 && m == 0 && u == 2) || (MODE == 2 && m == 1 && u == 0); };
        float sc[2][CH][2][4];
#pragma unroll
        for (int u = 0; u < CH; u++) {
            uint32_t kf[4], kg[2];
            const int ti = MODE == 3 ? max(c0 + u, tfirst) : c0 + u;
            ldsm4(kf, kb0 + ti * 768); ldsm2(kg, kb1 + ti * 768);
#pragma unroll
            for (int m = 0; m < 2; m++) {
                if (dead(m, u)) continue;
#pragma unroll
                for (int n = 0; n < 2; n++) {
#pragma unroll
                    for (int i = 0; i < 4; i++) sc[m][u][n][i] = 0.f;
                    mma16(sc[m][u][n], qa[m], kf[2 * n], kf[2 * n + 1]);
                    mma8(sc[m][u][n], qb[m][0], qb[m][1], kg[n]);
                }
            }
        }
#pragma unroll
        for (int m = 0; m < 2; m++)
#pragma unroll
            for (int u = 0; u < CH; u++)
#pragma unroll
                for (int n = 0; n < 2; n++)
#pragma unroll
                    for (int i = 0; i < 4; i++) {
                        const int dl = g + (i >> 1) * 8 - (n * 8 + 2 * t + (i & 1));
                        if (MODE == 0 && u == m + 1 && dl < 0) sc[m][u][n][i] = -INFINITY;
                        if (MODE == 2 && u == m && dl >= 0) sc[m][u][n][i] = -INFINITY;
                        if (MODE == 3) {
                            const int d = 256 + (m - c0 - u) * 16 + dl;
                            if (d < 0 || d >= 256 || c0 + u < tfirst) sc[m][u][n][i] = -INFINITY;
                        }
                    }
        float bs[2][2];
#pragma unroll
        for (int m = 0; m < 2; m++) {
            float n0 = mx[m][0], n1 = mx[m][1];
#pragma unroll
            for (int u = 0; u < CH; u++) {
                if (dead(m, u)) continue;
#pragma unroll
                for (int n = 0; n < 2; n++) {
                    n0 = fmaxf(n0, fmaxf(sc[m][u][n][0], sc[m][u][n][1])); n1 = fmaxf(n1, fmaxf(sc[m][u][n][2], sc[m][u][n][3]));
                }
            }
            n0 = fmaxf(n0, __shfl_xor_sync(0xffffffffu, n0, 1)); n1 = fmaxf(n1, __shfl_xor_sync(0xffffffffu, n1, 1));
            n0 = fmaxf(n0, __shfl_xor_sync(0xffffffffu, n0, 2)); n1 = fmaxf(n1, __shfl_xor_sync(0xffffffffu, n1, 2));
            if (MODE != 0) {
                const float f0 = ex2((mx[m][0] - n0) * SC), f1 = ex2((mx[m][1] - n1) * SC);
#pragma unroll
                for (int n = 0; n < 3; n++) { o[m][n][0] *= f0; o[m][n][1] *= f0; o[m][n][2] *= f1; o[m][n][3] *= f1; }
            }
            mx[m][0] = n0; mx[m][1] = n1;
            bs[m][0] = n0 * SC; bs[m][1] = n1 * SC;
        }
#pragma unroll
        for (int u = 0; u < CH; u++) {
            uint32_t vf[4], vg[2];
            const int ti = MODE == 3 ? max(c0 + u, tfirst) : c0 + u;
            ldsm4t(vf, vb0 + ti * 768); ldsm2t(vg, vb1 + ti * 768);
            if (one0) { vf[0] = 0x3f803f80u; vf[1] = 0x3f803f80u; }
            if (one2) { vg[0] = 0x3f803f80u; vg[1] = 0x3f803f80u; }
#pragma unroll
            for (int m = 0; m < 2; m++) {
                if (dead(m, u)) continue;
                uint32_t pa[4];
#pragma unroll
                for (int n = 0; n < 2; n++) {
                    pa[2 * n] = pack2(ex2(fmaf(sc[m][u][n][0], SC, -bs[m][0])), ex2(fmaf(sc[m][u][n][1], SC, -bs[m][0])));
                    pa[2 * n + 1] = pack2(ex2(fmaf(sc[m][u][n][2], SC, -bs[m][1])), ex2(fmaf(sc[m][u][n][3], SC, -bs[m][1])));
                }
                mma16(o[m][0], pa, vf[0], vf[1]); mma16(o[m][1], pa, vf[2], vf[3]); mma16(o[m][2], pa, vg[0], vg[1]);
            }
        }
    };
    if (tfirst == 0) {
        chunk(IC<0>{}, 15);
#pragma unroll 1
        for (int c0 = 12; c0 > 0; c0 -= CH) chunk(IC<1>{}, c0);
        chunk(IC<2>{}, 0);
    } else {
#pragma unroll 1
        for (int c0 = 15; c0 >= 0 && c0 + CH > tfirst; c0 -= CH) chunk(IC<3>{}, c0);
    }
    __syncwarp();
    if (lane == 0) mbar_arrive(rel);
#pragma unroll
    for (int m = 0; m < 2; m++) {
        const int src = sh == 6 ? (lane & ~3) : (lane | 3);
        const float s0 = __shfl_sync(0xffffffffu, sh == 6 ? o[m][0][0] : o[m][2][1], src);
        const float s1 = __shfl_sync(0xffffffffu, sh == 6 ? o[m][0][2] : o[m][2][3], src);
        const int r = q0 + wq * 32 + m * 16 + g;
        const float i0 = (1.f - gt[m][0]) * rcp_fast(s0), i1 = (1.f - gt[m][1]) * rcp_fast(s1);
        bf16* op = g_O + (size_t)r * OK + HD + hh * BD + 2 * t - sh;
#pragma unroll
        for (int n = 0; n < 3; n++) {
            const int col = n * 8 + 2 * t;
            if (col >= sh && col < sh + 18) {
                *reinterpret_cast<uint32_t*>(op + n * 8) = pack2(o[m][n][0] * i0, o[m][n][1] * i0);
                *reinterpret_cast<uint32_t*>(op + n * 8 + 8 * OK) = pack2(o[m][n][2] * i1, o[m][n][3] * i1);
            }
        }
    }
}

template <int BN>
__device__ __forceinline__ void gemm_unit(int ty, const uint32_t* d, uint32_t sb, uint32_t bF, uint32_t bE, int& sg, int& ph,
                                          int warp, int lane, bf16* __restrict__ out) {
    const int wg = warp >> 2, wq = warp & 3, g = lane >> 2, t = lane & 3;
    auto release = [&](int q) { __syncwarp(); if (lane == 0) mbar_arrive(bE + 8 * q); };
    const int n0 = d[2] * BN, kb0 = d[3] & 255, kb1 = d[3] >> 8;
    const int rb = (ty == T_G0 ? d[1] * 192 : f_row0(d[1])) + (BN == 64 ? wq : warp) * 16, r0 = rb + g;
    float g0 = 1.f, g1 = 1.f;
    if (ty != T_G0) { g0 = __ldcg(g_gate + r0); g1 = __ldcg(g_gate + r0 + 8); }
    if (ty != T_G0 && f_split(d[1]) > 1) {
        const float* pa = g_acc + (size_t)rb * DM + n0 * 16 + lane * 32;
#pragma unroll
        for (int i = 0; i < (BN + 63) / 64; i++) if (i * 64 + lane * 2 < BN) asm volatile("prefetch.global.L2 [%0];" ::"l"(pa + i * 1024));
    }
    float acc[BN / 2];
#pragma unroll
    for (int i = 0; i < BN / 2; i++) acc[i] = 0.f;
    int prev = -1;
    constexpr int KPS = BN == 64 ? 3 : 1;
    for (int kb = kb0; kb < kb1;) {
        if (kb > kb0) mbar_wait(bF + 8 * sg, ph);
        for (int j = 0; j < KPS && kb < kb1; j++, kb++) {
            const uint32_t a = sb + sg * H_STAGE + (BN == 64 ? j * 16384 : wg * 8192), b = BN == 64 ? a + 8192 : sb + sg * H_STAGE + 24576;
            if (kb == 64 && kb0 < 64) {
                wg_wait<0>();
#pragma unroll
                for (int i = 0; i < BN / 8; i++) { acc[4 * i] *= g0; acc[4 * i + 1] *= g0; acc[4 * i + 2] *= g1; acc[4 * i + 3] *= g1; }
            }
            const uint64_t da = desc_sw128(a, 16, 1024), db = desc_sw128(b, 8192, 1024);
            wg_fence();
#pragma unroll
            for (int k = 0; k < 4; k++) {
                if (BN == 192) wgmma_ss_n192(acc, da + (uint64_t)(k * 2), db + (uint64_t)(k * 128), 1);
                else if (BN == 96) wgmma_ss_n96(acc, da + (uint64_t)(k * 2), db + (uint64_t)(k * 128));
                else wgmma_ss_n64(acc, da + (uint64_t)(k * 2), db + (uint64_t)(k * 128));
            }
            wg_commit();
            wg_wait<1>();
            if (j == 0 && prev >= 0) release(prev);
        }
        prev = sg;
        if (++sg == H_STAGES) { sg = 0; ph ^= 1; }
    }
    wg_wait<0>();
    if (ty == T_G0) {
        release(prev);
        store_tile<BN>(acc, g_qkvB + (size_t)r0 * (3 * DM) + n0, 3 * DM, t);
        signal(g_ctr + C_G0 + d[1], lane);
        return;
    }
    if (kb1 <= 64) {
#pragma unroll
        for (int i = 0; i < BN / 8; i++) { acc[4 * i] *= g0; acc[4 * i + 1] *= g0; acc[4 * i + 2] *= g1; acc[4 * i + 3] *= g1; }
    }
    const int ks = f_split(d[1]);
    bool fin = true;
    if (ks == 1) release(prev);
    if (ks > 1) {
        float4* ga = reinterpret_cast<float4*>(g_acc + (size_t)rb * DM + n0 * 16) + lane;
#pragma unroll
        for (int i = 0; i < BN / 8; i++) red4(reinterpret_cast<float*>(ga + i * 32), acc[4 * i], acc[4 * i + 1], acc[4 * i + 2], acc[4 * i + 3]);
        release(prev);
        unsigned old = 0;
        if (lane == 0) asm volatile("atom.acq_rel.gpu.global.add.u32 %0,[%1],1;" : "=r"(old) : "l"(g_ctr + C_F + (d[1] * 9 + d[2]) * 12 + warp) : "memory");
        old = __shfl_sync(0xffffffffu, old, 0);
        fin = (old == (unsigned)ks - 1);
        if (fin) {
#pragma unroll
            for (int i = 0; i < BN / 8; i++) {
                const float4 u = __ldcg(ga + i * 32);
                acc[4 * i] = u.x; acc[4 * i + 1] = u.y; acc[4 * i + 2] = u.z; acc[4 * i + 3] = u.w;
            }
        }
    }
    if (fin) store_tile<BN>(acc, out + (size_t)r0 * DM + n0, DM, t);
}

struct HelpMaps { CUtensorMap x, wqkv, O, O128, O64, Wo, wo, qkv; };

__global__ void __launch_bounds__(512, 1) k_help(const __grid_constant__ HelpMaps tm, const bf16* __restrict__ x,
                                                  const bf16* __restrict__ gw, bf16* __restrict__ out) {
    extern __shared__ uint8_t smem_raw[];
    const uint32_t sb = (s2u(smem_raw) + 1023) & ~1023u;
    const uint32_t bF = sb + H_STAGES * H_STAGE, bE = bF + 8 * H_STAGES, dsc = bF + 128;
    const int tid = threadIdx.x, warp = __shfl_sync(0xffffffffu, tid >> 5, 0), lane = tid & 31;
    if (lane == 0 && warp >= 1 && warp <= (int)(sizeof(HelpMaps) / sizeof(CUtensorMap)))
        asm volatile("prefetch.tensormap [%0];" ::"l"(&tm.x + (warp - 1)) : "memory");
    if (tid == 0) {
        for (int i = 0; i < H_STAGES; i++) { mbar_init(bF + 8 * i, 1); mbar_init(bE + 8 * i, 12); }
        asm volatile("fence.mbarrier_init.release.cluster;" ::: "memory");
    }
    __syncthreads();
    if (warp >= 12) {
        asm volatile("setmaxnreg.dec.sync.aligned.u32 56;");
        if (warp != 12) {
            while (true) {
                unsigned u = 0;
                if (lane == 0) u = atomicAdd(g_ctr + C_HG, 1);
                u = __shfl_sync(0xffffffffu, u, 0);
                if (u >= SEQ / 16) return;
#pragma unroll 1
                for (int r0 = u * 16; r0 < u * 16 + 16; r0 += 2) {
                    float a0 = 0.f, a1 = 0.f;
                    const __nv_bfloat162* xr = reinterpret_cast<const __nv_bfloat162*>(x + (size_t)r0 * DM);
#pragma unroll
                    for (int i = 0; i < 9; i++) {
                        const float2 b = __bfloat1622float2(reinterpret_cast<const __nv_bfloat162*>(gw)[lane + 32 * i]);
                        const float2 y = __bfloat1622float2(xr[lane + 32 * i]), z = __bfloat1622float2(xr[DM / 2 + lane + 32 * i]);
                        a0 += y.x * b.x + y.y * b.y; a1 += z.x * b.x + z.y * b.y;
                    }
#pragma unroll
                    for (int o = 16; o; o >>= 1) { a0 += __shfl_xor_sync(0xffffffffu, a0, o); a1 += __shfl_xor_sync(0xffffffffu, a1, o); }
                    if (lane < 2) g_gate[r0 + lane] = 1.f / (1.f + __expf(-(lane ? a1 : a0)));
                }
                signal(g_ctr + C_GATE, lane);
            }
        }
        int sg = 0, ph = 1;
        auto next = [&](int ty, int a, int b, int c2) {
            mbar_wait(bE + 8 * sg, ph);
            if (lane == 0) asm volatile("st.shared.v4.u32 [%0],{%1,%2,%3,%4};" ::"r"(dsc + 16 * sg), "r"(ty), "r"(a), "r"(b), "r"(c2) : "memory");
        };
        auto adv = [&]() { __syncwarp(); if (++sg == H_STAGES) { sg = 0; ph ^= 1; } };
        auto acquire = [&]() { asm volatile("fence.acq_rel.gpu; fence.proxy.async.global;" ::: "memory"); };
        auto ticket = [&](unsigned* q) { unsigned u = 0; if (lane == 0) u = atomicAdd(q, 1); return __shfl_sync(0xffffffffu, u, 0); };
        auto gemm = [&](int ty, int m, int n, int kb0, int kb1) {
            for (int kb = kb0; kb < kb1; kb++) {
                next(ty, m, n, kb0 | (kb1 << 8));
                if (lane == 0) {
                    const uint32_t a = sb + sg * H_STAGE, b = a + 24576, bar = bF + 8 * sg;
                    const bool half = ty != T_G0 && m >= 9;
                    mbar_expect(bar, (ty == T_FN ? 40960 : 49152) - (half ? 8192 : 0));
                    tma2d(a, ty == T_G0 ? &tm.x : (half ? &tm.O128 : &tm.O), kb * 64, ty == T_G0 ? m * 192 : f_row0(m), bar);
                    const CUtensorMap* mb = ty == T_G0 ? &tm.wqkv : (kb >= 64 ? &tm.wo : &tm.Wo);
                    const int kr = (kb >= 64 ? kb - 64 : kb) * 64;
                    if (ty == T_FN) for (int j = 0; j < 2; j++) tma2d(b + j * 8192, mb, n * 96 + j * 64, kr, bar);
                    else for (int j = 0; j < 3; j++) tma2d(b + j * 8192, mb, n * 192 + j * 64, kr, bar);
                }
                adv();
            }
        };
        bool bdone = false;
        int idle = 0, rr = 0;
        const int fl = min(lane, 10);
        constexpr int NLATE = (NSEG - AA_LATE) * 6, NSMALL = 9 * f_split(11);
        auto attn_a = [&](int as, int u) {
            const int per = (15 + aa_units(as)) / aa_units(as), ns = min(per, 16 - u * per), h0 = u * per * 2;
            for (int i = 0; i < ns; i++) {
                next(T_AA, as, h0 + 2 * i, rr | (i + 3 >= ns ? 4 : 0)); rr = rr == 2 ? 0 : rr + 1;
                if (lane == 0) {
                    const uint32_t a = sb + sg * H_STAGE, bar = bF + 8 * sg;
                    mbar_expect(bar, 57344);
                    bulk_load(a, reinterpret_cast<uint8_t*>(g_xr) + (size_t)(as * 32 + h0 + 2 * i) * 24576, 49152, bar);
                    bulk_load(a + 49152, reinterpret_cast<uint8_t*>(g_mr) + (size_t)(as * 32 + h0 + 2 * i) * 4096, 8192, bar);
                }
                adv();
            }
        };
        auto spin_ge = [&](const unsigned* q, unsigned target) {
            int it = 0;
            while (ld_acq(q) < target) { __nanosleep(SPIN_NS); if (++it > (1 << 22)) __trap(); }
        };
        auto drain = [&]() {
            const int ls = sg == 0 ? H_STAGES - 1 : sg - 1;
            mbar_wait(bE + 8 * ls, sg == 0 ? ph : ph ^ 1);
        };
        while (true) {
            const unsigned tk0 = ld_relaxed1(g_ctr + C_HAA + lane), tk1 = ld_relaxed1(g_ctr + C_HAA + 32 + lane);
            const unsigned f0 = ld_relaxed1(g_flagA + lane), f1 = ld_relaxed1(g_flagA + 32 + lane);
            const unsigned tkf = ld_relaxed1(g_ctr + C_HF + min(lane, 12)), ca = ld_relaxed1(g_ctr + C_AA + fl);
            const unsigned cb0 = ld_relaxed1(g_ctr + C_AB + (lane > 10 ? 15 : f_row0(fl) / 128));
            const unsigned cb1 = ld_relaxed1(g_ctr + C_AB + (lane > 10 ? 15 : (f_row0(fl) + f_rows(fl) - 1) / 128));
            const bool e0 = tk0 < (unsigned)aa_units(lane), e1 = 32 + lane < AA_LATE && tk1 < (unsigned)aa_units(32 + lane);
            const unsigned a0 = __ballot_sync(0xffffffffu, e0 && f0 >= 192), a1 = __ballot_sync(0xffffffffu, e1 && f1 >= 192);
            const bool early_left = __any_sync(0xffffffffu, e0 || e1);
            const unsigned tl = __shfl_sync(0xffffffffu, tkf, 11), ts = __shfl_sync(0xffffffffu, tkf, 12);
            const bool fleft = lane < 11 && tkf < (unsigned)(f_ntiles(fl) * f_split(fl));
            const unsigned fl_m = __ballot_sync(0xffffffffu, fleft);
            const bool may = blockIdx.x >= (fl >= AA_B3 ? AA_CTAS3 : (fl >= 6 ? AA_CTAS2 : AA_CTAS)) || tl >= NLATE;
            const unsigned fr = __ballot_sync(0xffffffffu, fleft && ca >= (unsigned)(2 * f_rows(fl)) && cb0 >= 128 && cb1 >= 128 && may);
            if (a0 | a1) {
                const int as = a0 ? __ffs(a0) - 1 : 31 + __ffs(a1);
                const unsigned u = ticket(g_ctr + C_HAA + as);
                if (u < (unsigned)aa_units(as)) { acquire(); attn_a(as, u); continue; }
            }
            if (tl < NLATE && !early_left) {
                const bool ready = __shfl_sync(0xffffffffu, f1, (AA_LATE - 32 + tl / 6) & 31) >= 192;
                if (ready || (blockIdx.x < AA_CTAS3 && bdone)) {
                    drain();
                    const unsigned u = ticket(g_ctr + C_HF + 11);
                    if (u < NLATE) { spin_ge(g_flagA + AA_LATE + u / 6, 192); attn_a(AA_LATE + u / 6, u % 6); drain(); continue; }
                }
            }
            if (fr) {
                const int fm = __ffs(fr) - 1;
                const unsigned u = ticket(g_ctr + C_HF + fm);
                const int ks = f_split(fm), nt = f_ntiles(fm);
                if (u < (unsigned)(nt * ks)) {
                    const int kp = u / nt;
                    acquire();
                    gemm(nt == 3 ? T_F : T_FN, fm, u % nt, kp * 73 / ks, (kp + 1) * 73 / ks);
                    if (fm >= DRAIN_B) drain();
                    continue;
                }
            }
            if (ts < NSMALL && tl >= NLATE && __shfl_sync(0xffffffffu, cb0 >= 128, 11)) {
                const unsigned u = ticket(g_ctr + C_HF + 12);
                if (u < NSMALL) {
                    acquire();
                    const int fm = 11, v = u;
                    const int nn = v % 9, kp = v / 9, kb0 = kp * 73 / f_split(fm), kb1 = (kp + 1) * 73 / f_split(fm);
                    for (int k0 = kb0; k0 < kb1; k0 += 3 * H_STAGES) {
                        const int sg0 = sg, k1 = min(kb1, k0 + 3 * H_STAGES);
                        for (int kb = k0; kb < k1; kb += 3) {
                            next(T_FS, fm, nn, kb0 | (kb1 << 8));
                            const int kk = kb + lane;
                            if (lane == 0) mbar_expect(bF + 8 * sg, min(3, k1 - kb) * 16384);
                            __syncwarp();
                            if (lane < 3 && kk < k1) {
                                tma2d(sb + sg * H_STAGE + lane * 16384 + 8192, kk >= 64 ? &tm.wo : &tm.Wo, nn * 64, (kk >= 64 ? kk - 64 : kk) * 64, bF + 8 * sg);
                                if (k0 > kb0) tma2d(sb + sg * H_STAGE + lane * 16384, &tm.O64, kk * 64, f_row0(fm), bF + 8 * sg);
                            }
                            adv();
                        }
                        if (k0 == kb0) {
                            spin_ge(g_ctr + C_AA + fm, 128);
                            if (k0 + lane < k1) {
                                const int q = (sg0 + lane / 3) % H_STAGES;
                                tma2d(sb + q * H_STAGE + (lane % 3) * 16384, &tm.O64, (k0 + lane) * 64, f_row0(fm), bF + 8 * q);
                            }
                            __syncwarp();
                        }
                    }
                    drain();
                    continue;
                }
            }
            if (a0 | a1 | fr) continue;
            if (!bdone) {
                const unsigned u = ticket(g_ctr + C_HB);
                if (u < NG0) {
                    gemm(T_G0, u / 9, u % 9, 0, 9);
                } else if (u < NB_UNITS) {
                    const int m = (u - NG0) / ABT, h0 = ((u - NG0) % ABT) * ABH, h1 = min(h0 + ABH, BH);
                    const int mm = min(max(0, m * 128 - 256) / 192 + lane, (m * 128 + 127) / 192);
                    const unsigned* q = lane == 31 ? g_ctr + C_GATE : g_ctr + C_G0 + mm;
                    int it = 0;
                    while (!__all_sync(0xffffffffu, ld_relaxed1(q) >= (lane == 31 ? 128u : 108u))) { __nanosleep(100); if (++it > (1 << 22)) __trap(); }
                    acquire();
                    for (int hh = h0; hh < h1; hh++) {
                        next(T_AB, m, hh, rr | (hh + 3 >= h1 ? 4 : 0)); rr = rr == 2 ? 0 : rr + 1;
                        if (lane == 0) {
                            const uint32_t a = sb + sg * H_STAGE, bar = bF + 8 * sg;
                            const int col = (hh >> 2) * 72 + (hh & 3) * 16;
                            mbar_expect(bar, 7 * 6144);
                            tma2d(a, &tm.qkv, col, m * 128, bar);
                            for (int j = 0; j < 3; j++) {
                                tma2d(a + (1 + j) * 6144, &tm.qkv, DM + col, (m - 2 + j) * 128, bar);
                                tma2d(a + (4 + j) * 6144, &tm.qkv, 2 * DM + col, (m - 2 + j) * 128, bar);
                            }
                        }
                        adv();
                    }
                } else bdone = true;
                continue;
            }
            if (fl_m == 0 && ts >= NSMALL) break;
            __nanosleep(150);
            if (++idle > (1 << 22)) __trap();
        }
        next(T_EXIT, 0, 0, 0);
        if (lane == 0) mbar_arrive(bF + 8 * sg);
    } else {
        asm volatile("setmaxnreg.inc.sync.aligned.u32 152;");
        const int wg = warp >> 2, wq = warp & 3;
        int sg = 0, ph = 0, skip = 0;
        unsigned pend = 0;
        auto release = [&](int q) { __syncwarp(); if (lane == 0) mbar_arrive(bE + 8 * q); };
        auto adv = [&]() { if (++sg == H_STAGES) { sg = 0; ph ^= 1; } };
        while (true) {
            mbar_wait(bF + 8 * sg, ph);
            uint32_t d[4];
            lds128(d, dsc + 16 * sg);
            const int ty = d[0];
            if (ty == T_EXIT) break;
            if ((ty == T_G0 && wg == 2 && d[1] == NBLK - 1) || ((ty == T_F || ty == T_FN) && wg == 2 && d[1] >= 9) || (ty == T_FS && wg != 0)) {
                release(sg); adv();
                if (ty == T_G0 && ++skip == 9) { skip = 0; signal(g_ctr + C_G0 + d[1], lane); }
            } else if (ty == T_G0 || ty == T_F) {
                gemm_unit<192>(ty, d, sb, bF, bE, sg, ph, warp, lane, out);
            } else if (ty == T_FN) {
                gemm_unit<96>(ty, d, sb, bF, bE, sg, ph, warp, lane, out);
            } else if (ty == T_FS) {
                gemm_unit<64>(ty, d, sb, bF, bE, sg, ph, warp, lane, out);
                if (tid == 0 && d[1] == NFB - 1) g_sync[0] = 0;
            } else {
                if ((int)(d[3] & 3) == wg) {
                    if (ty == T_AA) {
                        const uint32_t xr = sb + sg * H_STAGE + (wq >> 1) * 24576, mr = sb + sg * H_STAGE + 49152 + (wq >> 1) * 4096;
                        if ((wq + wg) & 1) attnA_unit<1>(xr, mr, d[1], d[2] + (wq >> 1), lane, bE + 8 * sg);
                        else attnA_unit<0>(xr, mr, d[1], d[2] + (wq >> 1), lane, bE + 8 * sg);
                        pend++;
                        if (d[1] >= 62) asm volatile("fence.proxy.async.global;" ::: "memory");
                        if (d[3] & 4) { signal(g_ctr + C_AA + f_blk(d[1]), lane, pend); pend = 0; }
                    } else {
                        attnB_unit(sb + sg * H_STAGE, d[1] * 128, d[2], wq, lane, bE + 8 * sg);
                        pend++;
                        if (d[3] & 4) { signal(g_ctr + C_AB + d[1], lane, pend); pend = 0; }
                    }
                } else {
                    release(sg);
                }
                adv();
            }
        }
    }
}

__device__ float g_fmem[(NSEG + 1) * 8 * DM];
__device__ bf16 g_fq[8 * HD];
__device__ __forceinline__ int tile_off(int row, int e) { return row * 16 + ((((e >> 3) ^ (row >> 2)) & 1) << 3) + (e & 7); }

__global__ void fb_init(const bf16* __restrict__ mem0) {
    const int i = blockIdx.x * blockDim.x + threadIdx.x;
    if (i < (NSEG + 1) * 8 * DM) g_fmem[i] = i < 8 * DM ? __bfloat162float(mem0[i]) : 0.f;
    if (i < SEQ * DM) g_acc[i] = 0.f;
    if (i < 1920) g_ctr[i] = 0;
    if (i < NSEG) g_flagA[i] = 192;
}
__global__ void fb_proj(const bf16* __restrict__ x, const bf16* __restrict__ Wq, const bf16* __restrict__ Wk, const bf16* __restrict__ Wv, int seg) {
    __shared__ float in[8][DM];
    for (int i = threadIdx.x; i < 8 * DM; i += blockDim.x)
        in[i / DM][i % DM] = seg >= 0 ? __bfloat162float(__float2bfloat16(g_fmem[seg * 8 * DM + i])) : __bfloat162float(x[(size_t)blockIdx.y * 8 * DM + i]);
    __syncthreads();
    const int col = blockIdx.x * blockDim.x + threadIdx.x, ty = col / HD, hc = col % HD, h = hc / DH, d = (hc % DH) >> 4, e = hc & 15;
    const bf16* W = (ty == 0 ? Wq : (ty == 1 ? Wk : Wv)) + hc;
    float a[8] = {0.f, 0.f, 0.f, 0.f, 0.f, 0.f, 0.f, 0.f};
    for (int k = 0; k < DM; k++) {
        const float w = __bfloat162float(W[(size_t)k * HD]);
#pragma unroll
        for (int r = 0; r < 8; r++) a[r] += in[r][k] * w;
    }
    for (int r = 0; r < 8; r++) {
        const bf16 v = __float2bfloat16(a[r]);
        if (seg < 0) {
            const int pos = ty == 0 ? pos_q(d) : (ty == 1 ? pos_k(d) : pos_v(d));
            reinterpret_cast<bf16*>(g_xr)[((size_t)((blockIdx.y >> 2) * 32 + h) * 24 + pos) * 512 + tile_off((blockIdx.y & 3) * 8 + r, e)] = v;
        } else if (ty == 0) g_fq[r * HD + hc] = v;
        else reinterpret_cast<bf16*>(g_mr)[((size_t)(seg * 32 + h) * 16 + (ty == 1 ? mpos_k(d) : mpos_v(d))) * 128 + tile_off(r, e)] = v;
    }
}
__global__ void fb_attn(const bf16* __restrict__ Wo, int seg) {
    __shared__ float sc[8][40], o[8][DH];
    const int h = blockIdx.x, tid = threadIdx.x;
    const bf16* xr = reinterpret_cast<const bf16*>(g_xr) + (size_t)(seg * 32 + h) * 24 * 512;
    const bf16* mr = reinterpret_cast<const bf16*>(g_mr) + (size_t)(seg * 32 + h) * 16 * 128;
    {
        const int r = tid / 40, j = tid % 40;
        float a = 0.f;
        for (int c = 0; c < DH; c++) {
            const bf16 kv = j < 8 ? mr[mpos_k(c >> 4) * 128 + tile_off(j, c & 15)] : xr[pos_k(c >> 4) * 512 + tile_off(j - 8, c & 15)];
            a += __bfloat162float(g_fq[r * HD + h * DH + c]) * __bfloat162float(kv);
        }
        sc[r][j] = a * 0.08838834764831845f;
    }
    __syncthreads();
    if (tid < 8) {
        float m = sc[tid][0], z = 0.f;
        for (int j = 1; j < 40; j++) m = fmaxf(m, sc[tid][j]);
        for (int j = 0; j < 40; j++) { sc[tid][j] = __expf(sc[tid][j] - m); z += sc[tid][j]; }
        for (int j = 0; j < 40; j++) sc[tid][j] /= z;
    }
    __syncthreads();
    for (int i = tid; i < 8 * DH; i += 320) {
        const int r = i / DH, c = i % DH;
        float a = 0.f;
        for (int j = 0; j < 40; j++)
            a += sc[r][j] * __bfloat162float(j < 8 ? mr[mpos_v(c >> 4) * 128 + tile_off(j, c & 15)] : xr[pos_v(c >> 4) * 512 + tile_off(j - 8, c & 15)]);
        o[r][c] = __bfloat162float(__float2bfloat16(a));
    }
    __syncthreads();
    for (int n = tid; n < DM; n += 320) {
        float a[8] = {0.f, 0.f, 0.f, 0.f, 0.f, 0.f, 0.f, 0.f};
        for (int c = 0; c < DH; c++) {
            const float w = __bfloat162float(Wo[(size_t)(h * DH + c) * DM + n]);
#pragma unroll
            for (int r = 0; r < 8; r++) a[r] += o[r][c] * w;
        }
        for (int r = 0; r < 8; r++) atomicAdd(g_fmem + ((seg + 1) * 8 + r) * DM + n, a[r]);
    }
}

typedef CUresult (*EncodeFn)(CUtensorMap*, CUtensorMapDataType, cuuint32_t, void*, const cuuint64_t*, const cuuint64_t*,
                             const cuuint32_t*, const cuuint32_t*, CUtensorMapInterleave, CUtensorMapSwizzle,
                             CUtensorMapL2promotion, CUtensorMapFloatOOBfill);

static void make_map(EncodeFn fn, CUtensorMap* m, const void* ptr, uint64_t cols, uint64_t rows, uint32_t bc, uint32_t br,
                     CUtensorMapSwizzle sw = CU_TENSOR_MAP_SWIZZLE_128B, bool promote = false) {
    cuuint64_t dims[2] = {cols, rows};
    cuuint64_t strides[1] = {cols * 2};
    cuuint32_t box[2] = {bc, br};
    cuuint32_t es[2] = {1, 1};
    fn(m, CU_TENSOR_MAP_DATA_TYPE_BFLOAT16, 2, const_cast<void*>(ptr), dims, strides, box, es, CU_TENSOR_MAP_INTERLEAVE_NONE,
       sw, sw == CU_TENSOR_MAP_SWIZZLE_NONE && !promote ? CU_TENSOR_MAP_L2_PROMOTION_NONE : CU_TENSOR_MAP_L2_PROMOTION_L2_256B, CU_TENSOR_MAP_FLOAT_OOB_FILL_NONE);
}

extern "C" void kernel_launch(void* const* d_in, const int* in_sizes, int n_in, void* d_out, int out_size) {
    const bf16* x = (const bf16*)d_in[0];
    const bf16* mem0 = (const bf16*)d_in[1];
    const bf16* Wq = (const bf16*)d_in[2];
    const bf16* Wk = (const bf16*)d_in[3];
    const bf16* Wv = (const bf16*)d_in[4];
    const bf16* Wo = (const bf16*)d_in[5];
    const bf16* wqkv = (const bf16*)d_in[8];
    const bf16* wo = (const bf16*)d_in[9];
    const bf16* gw = (const bf16*)d_in[10];
    bf16* out = (bf16*)d_out;

    void* fp = nullptr;
    cudaDriverEntryPointQueryResult qr;
    cudaGetDriverEntryPoint("cuTensorMapEncodeTiled", &fp, cudaEnableDefault, &qr);
    EncodeFn enc = (EncodeFn)fp;
    void* pO = nullptr;
    cudaGetSymbolAddress(&pO, g_O);
    CUtensorMap tx32;
    HelpMaps hm;
    RecMaps rm;
    for (int r = 0; r < 2; r++) {
        make_map(enc, &rm.w[r][0], Wq, HD, DM, r ? 32 : 48, 144, CU_TENSOR_MAP_SWIZZLE_NONE, true);
        make_map(enc, &rm.w[r][1], Wk, HD, DM, r ? 32 : 48, 144, CU_TENSOR_MAP_SWIZZLE_NONE, true);
        make_map(enc, &rm.w[r][2], Wv, HD, DM, r ? 64 : 32, 144, CU_TENSOR_MAP_SWIZZLE_NONE, true);
    }
    make_map(enc, &rm.wo, Wo, DM, HD, 192, 128, CU_TENSOR_MAP_SWIZZLE_NONE, true);
    make_map(enc, &tx32, x, DM, SEQ, 64, 32);
    make_map(enc, &hm.x, x, DM, SEQ, 64, 192);
    make_map(enc, &hm.wqkv, wqkv, 3 * DM, DM, 64, 64);
    make_map(enc, &hm.O, pO, OK, SEQ, 64, 192);
    make_map(enc, &hm.O128, pO, OK, SEQ, 64, 128);
    make_map(enc, &hm.O64, pO, OK, SEQ, 64, 64);
    make_map(enc, &hm.Wo, Wo, DM, HD, 64, 64);
    make_map(enc, &hm.wo, wo, DM, DM, 64, 64);
    void* pQ = nullptr;
    cudaGetSymbolAddress(&pQ, g_qkvB);
    make_map(enc, &hm.qkv, pQ, 3 * DM, SEQ, 24, 128, CU_TENSOR_MAP_SWIZZLE_NONE);
    cudaFuncSetAttribute(k_rec, cudaFuncAttributeMaxDynamicSharedMemorySize, REC_SMEM);
    cudaFuncSetAttribute(k_help, cudaFuncAttributeMaxDynamicSharedMemorySize, HELP_SMEM);

    cudaStream_t st = cudaStreamPerThread;
    bool fast;
    int nsm = 132;
    cudaDeviceGetAttribute(&nsm, cudaDevAttrMultiProcessorCount, 0);
    {
        RecParams p{mem0, Wq, Wk, Wv, 880, 230};
        cudaLaunchConfig_t cfg = {};
        cfg.gridDim = dim3(96); cfg.blockDim = dim3(384); cfg.dynamicSmemBytes = REC_SMEM; cfg.stream = st;
        cudaLaunchAttribute at[1];
        at[0].id = cudaLaunchAttributeClusterDimension;
        at[0].val.clusterDim.x = 3; at[0].val.clusterDim.y = 1; at[0].val.clusterDim.z = 1;
        cfg.attrs = at; cfg.numAttrs = 1;
        int ncl = 0;
        fast = cudaOccupancyMaxActiveClusters(&ncl, k_rec, &cfg) == cudaSuccess && ncl >= NH;
        if (fast) {
            cudaLaunchKernelEx(&cfg, k_rec, tx32, rm, p);
        } else {
            fb_init<<<SEQ * DM / 256, 256, 0, st>>>(mem0);
            fb_proj<<<dim3(3 * HD / 256, SEQ / 8), 256, 0, st>>>(x, Wq, Wk, Wv, -1);
            for (int s = 0; s < NSEG; s++) {
                fb_proj<<<dim3(3 * HD / 128, 1), 128, 0, st>>>(x, Wq, Wk, Wv, s);
                if (s + 1 < NSEG) fb_attn<<<NH, 320, 0, st>>>(Wo, s);
            }
        }
    }
    {
        cudaLaunchConfig_t cfg = {};
        cfg.gridDim = dim3(nsm); cfg.blockDim = dim3(512); cfg.dynamicSmemBytes = HELP_SMEM; cfg.stream = st;
        cudaLaunchAttribute at[1];
        at[0].id = cudaLaunchAttributeProgrammaticStreamSerialization;
        at[0].val.programmaticStreamSerializationAllowed = 1;
        cfg.attrs = at; cfg.numAttrs = fast ? 1 : 0;
        cudaLaunchKernelEx(&cfg, k_help, hm, x, gw, out);
    }
}
```

```cpp
#include <cuda_runtime.h>
#include <cuda_bf16.h>
#include <cuda_fp16.h>
#include <cuda.h>
#include <stdint.h>

typedef __nv_bfloat16 bf16;

constexpr int SEQ = 2048, DM = 576, NH = 32, DH = 128, NSEG = 64;
constexpr int HD = NH * DH;
constexpr int OK = HD + DM;
constexpr int BH = 32, BD = 18;

__device__ bf16 g_O[SEQ * OK];
__device__ bf16 g_qkvB[SEQ * 3 * DM];
__device__ float g_acc[SEQ * DM];
__device__ float g_gate[SEQ];
__device__ float g_red[8 * 192 * 256];
__device__ uint4 g_redh[8 * 96 * 72];
__device__ unsigned g_sync[32];
__device__ unsigned g_ctr[1920];

__device__ __forceinline__ uint32_t s2u(const void* p) { return (uint32_t)__cvta_generic_to_shared(p); }
__device__ __forceinline__ uint32_t mapa(uint32_t a, uint32_t r) {
    uint32_t o; asm volatile("mapa.shared::cluster.u32 %0,%1,%2;" : "=r"(o) : "r"(a), "r"(r)); return o;
}
__device__ __forceinline__ void mbar_init(uint32_t a, int c) {
    asm volatile("mbarrier.init.shared::cta.b64 [%0],%1;" ::"r"(a), "r"(c) : "memory");
}
__device__ __forceinline__ void mbar_expect(uint32_t a, int bytes) {
    asm volatile("mbarrier.arrive.expect_tx.shared::cta.b64 _,[%0],%1;" ::"r"(a), "r"(bytes) : "memory");
}
__device__ __forceinline__ void mbar_arrive(uint32_t a) {
    asm volatile("mbarrier.arrive.shared::cta.b64 _,[%0];" ::"r"(a) : "memory");
}
__device__ __forceinline__ void mbar_wait(uint32_t a, int ph) {
    asm volatile("{.reg .pred p; .reg .u32 n; mov.u32 n,0;\n"
                 "WL%=: mbarrier.try_wait.parity.shared::cta.b64 p,[%0],%1; @p bra.uni WD%=;\n"
                 "add.u32 n,n,1; setp.lt.u32 p,n,4194304; @p bra.uni WL%=; trap;\n"
                 "WD%=: }" ::"r"(a), "r"(ph) : "memory");
}
__device__ __forceinline__ void bar_sync(int id, int n) { asm volatile("bar.sync %0,%1;" ::"r"(id), "r"(n) : "memory"); }
__device__ __forceinline__ void bar_arrive(int id, int n) { asm volatile("bar.arrive %0,%1;" ::"r"(id), "r"(n) : "memory"); }
__device__ __forceinline__ void cluster_sync() {
    asm volatile("barrier.cluster.arrive.release.aligned; barrier.cluster.wait.acquire.aligned;" ::: "memory");
}
__device__ __forceinline__ void cluster_sync_relaxed() {
    asm volatile("barrier.cluster.arrive.relaxed.aligned; barrier.cluster.wait.aligned;" ::: "memory");
}
__device__ __forceinline__ uint32_t lds32(uint32_t a) { uint32_t v; asm volatile("ld.shared.u32 %0,[%1];" : "=r"(v) : "r"(a) : "memory"); return v; }
__device__ __forceinline__ void fence_async() { asm volatile("fence.proxy.async.shared::cta;" ::: "memory"); }
__device__ __forceinline__ void ldsm4(uint32_t* r, uint32_t a) {
    asm volatile("ldmatrix.sync.aligned.m8n8.x4.shared.b16 {%0,%1,%2,%3},[%4];"
                 : "=r"(r[0]), "=r"(r[1]), "=r"(r[2]), "=r"(r[3]) : "r"(a) : "memory");
}
__device__ __forceinline__ void ldsm4t(uint32_t* r, uint32_t a) {
    asm volatile("ldmatrix.sync.aligned.m8n8.x4.trans.shared.b16 {%0,%1,%2,%3},[%4];"
                 : "=r"(r[0]), "=r"(r[1]), "=r"(r[2]), "=r"(r[3]) : "r"(a) : "memory");
}
__device__ __forceinline__ void ldsm2(uint32_t* r, uint32_t a) {
    asm volatile("ldmatrix.sync.aligned.m8n8.x2.shared.b16 {%0,%1},[%2];" : "=r"(r[0]), "=r"(r[1]) : "r"(a) : "memory");
}
__device__ __forceinline__ void ldsm2t(uint32_t* r, uint32_t a) {
    asm volatile("ldmatrix.sync.aligned.m8n8.x2.trans.shared.b16 {%0,%1},[%2];" : "=r"(r[0]), "=r"(r[1]) : "r"(a) : "memory");
}
__device__ __forceinline__ void mma16(float* c, const uint32_t* a, uint32_t b0, uint32_t b1) {
    asm("mma.sync.aligned.m16n8k16.row.col.f32.bf16.bf16.f32 {%0,%1,%2,%3},{%4,%5,%6,%7},{%8,%9},{%0,%1,%2,%3};"
                 : "+f"(c[0]), "+f"(c[1]), "+f"(c[2]), "+f"(c[3])
                 : "r"(a[0]), "r"(a[1]), "r"(a[2]), "r"(a[3]), "r"(b0), "r"(b1));
}
__device__ __forceinline__ void mma16v(float* c, const uint32_t* a, uint32_t b0, uint32_t b1) {
    asm volatile("mma.sync.aligned.m16n8k16.row.col.f32.bf16.bf16.f32 {%0,%1,%2,%3},{%4,%5,%6,%7},{%8,%9},{%0,%1,%2,%3};"
                 : "+f"(c[0]), "+f"(c[1]), "+f"(c[2]), "+f"(c[3])
                 : "r"(a[0]), "r"(a[1]), "r"(a[2]), "r"(a[3]), "r"(b0), "r"(b1));
}
__device__ __forceinline__ void mma8(float* c, uint32_t a0, uint32_t a1, uint32_t b0) {
    asm("mma.sync.aligned.m16n8k8.row.col.f32.bf16.bf16.f32 {%0,%1,%2,%3},{%4,%5},{%6},{%0,%1,%2,%3};"
                 : "+f"(c[0]), "+f"(c[1]), "+f"(c[2]), "+f"(c[3]) : "r"(a0), "r"(a1), "r"(b0));
}
__device__ __forceinline__ uint32_t pack2(float lo, float hi) {
    uint32_t r; asm("cvt.rn.bf16x2.f32 %0,%1,%2;" : "=r"(r) : "f"(hi), "f"(lo)); return r;
}
__device__ __forceinline__ float ex2(float x) { float y; asm("ex2.approx.ftz.f32 %0,%1;" : "=f"(y) : "f"(x)); return y; }
__device__ __forceinline__ void sts32(uint32_t a, uint32_t v) { asm volatile("st.shared.u32 [%0],%1;" ::"r"(a), "r"(v) : "memory"); }
__device__ __forceinline__ void sts128(uint32_t a, const uint32_t* v) {
    asm volatile("st.shared.v4.u32 [%0],{%1,%2,%3,%4};" ::"r"(a), "r"(v[0]), "r"(v[1]), "r"(v[2]), "r"(v[3]) : "memory");
}
__device__ __forceinline__ void lds128(uint32_t* v, uint32_t a) {
    asm volatile("ld.shared.v4.u32 {%0,%1,%2,%3},[%4];" : "=r"(v[0]), "=r"(v[1]), "=r"(v[2]), "=r"(v[3]) : "r"(a) : "memory");
}
__device__ __forceinline__ float2 lds64f(uint32_t a) {
    float2 v; asm volatile("ld.shared.v2.f32 {%0,%1},[%2];" : "=f"(v.x), "=f"(v.y) : "r"(a) : "memory"); return v;
}
__device__ __forceinline__ void tma2d(uint32_t dst, const CUtensorMap* m, int c0, int c1, uint32_t bar) {
    asm volatile("cp.async.bulk.tensor.2d.shared::cluster.global.mbarrier::complete_tx::bytes [%0],[%1,{%3,%4}],[%2];"
                 ::"r"(dst), "l"(m), "r"(bar), "r"(c0), "r"(c1) : "memory");
}
__device__ __forceinline__ void tma2d_mc(uint32_t dst, const CUtensorMap* m, int c0, int c1, uint32_t bar, uint16_t mask) {
    asm volatile("cp.async.bulk.tensor.2d.shared::cluster.global.mbarrier::complete_tx::bytes.multicast::cluster [%0],[%1,{%3,%4}],[%2],%5;"
                 ::"r"(dst), "l"(m), "r"(bar), "r"(c0), "r"(c1), "h"(mask) : "memory");
}
__device__ __forceinline__ uint64_t desc_sw128(uint32_t addr, uint32_t lbo, uint32_t sbo) {
    return (uint64_t)((addr & 0x3FFFF) >> 4) | ((uint64_t)(lbo >> 4) << 16) | ((uint64_t)(sbo >> 4) << 32) | (1ull << 62);
}
__device__ __forceinline__ void wg_fence() { asm volatile("wgmma.fence.sync.aligned;" ::: "memory"); }
__device__ __forceinline__ void wg_commit() { asm volatile("wgmma.commit_group.sync.aligned;" ::: "memory"); }
template <int N> __device__ __forceinline__ void wg_wait() { asm volatile("wgmma.wait_group.sync.aligned %0;" ::"n"(N) : "memory"); }

__device__ __forceinline__ void wgmma_rs_n32(float* d, const uint32_t* a, uint32_t dlo, int acc) {
    asm volatile("{.reg .pred p; .reg .b64 dd; setp.ne.b32 p,%21,0; mov.b64 dd,{%20,0x40000040};\n"
                 "wgmma.mma_async.sync.aligned.m64n32k16.f32.bf16.bf16 "
                 "{%0,%1,%2,%3,%4,%5,%6,%7,%8,%9,%10,%11,%12,%13,%14,%15},{%16,%17,%18,%19},dd,p,1,1,0;}"
                 : "+f"(d[0]), "+f"(d[1]), "+f"(d[2]), "+f"(d[3]), "+f"(d[4]), "+f"(d[5]), "+f"(d[6]), "+f"(d[7]),
                   "+f"(d[8]), "+f"(d[9]), "+f"(d[10]), "+f"(d[11]), "+f"(d[12]), "+f"(d[13]), "+f"(d[14]), "+f"(d[15])
                 : "r"(a[0]), "r"(a[1]), "r"(a[2]), "r"(a[3]), "r"(dlo), "r"(acc));
}

__device__ __forceinline__ void wgmma_ss_n32(float* d, uint32_t alo, uint32_t dlo, int acc) {
    asm volatile("{.reg .pred p; .reg .b64 da,dd; setp.ne.b32 p,%18,0; mov.b64 da,{%16,0x00000008}; mov.b64 dd,{%17,0x40000040};\n"
                 "wgmma.mma_async.sync.aligned.m64n32k16.f32.bf16.bf16 "
                 "{%0,%1,%2,%3,%4,%5,%6,%7,%8,%9,%10,%11,%12,%13,%14,%15},da,dd,p,1,1,0,0;}"
                 : "+f"(d[0]), "+f"(d[1]), "+f"(d[2]), "+f"(d[3]), "+f"(d[4]), "+f"(d[5]), "+f"(d[6]), "+f"(d[7]),
                   "+f"(d[8]), "+f"(d[9]), "+f"(d[10]), "+f"(d[11]), "+f"(d[12]), "+f"(d[13]), "+f"(d[14]), "+f"(d[15])
                 : "r"(alo), "r"(dlo), "r"(acc));
}

#define R8(b) "+f"(d[b]), "+f"(d[b + 1]), "+f"(d[b + 2]), "+f"(d[b + 3]), "+f"(d[b + 4]), "+f"(d[b + 5]), "+f"(d[b + 6]), "+f"(d[b + 7])
__device__ __forceinline__ void wgmma_ss_n192(float* d, uint64_t da, uint64_t db, int acc) {
    asm volatile("{.reg .pred p; setp.ne.b32 p,%98,0;\n"
                 "wgmma.mma_async.sync.aligned.m64n192k16.f32.bf16.bf16 "
                 "{%0,%1,%2,%3,%4,%5,%6,%7,%8,%9,%10,%11,%12,%13,%14,%15,%16,%17,%18,%19,%20,%21,%22,%23,"
                 "%24,%25,%26,%27,%28,%29,%30,%31,%32,%33,%34,%35,%36,%37,%38,%39,%40,%41,%42,%43,%44,%45,%46,%47,"
                 "%48,%49,%50,%51,%52,%53,%54,%55,%56,%57,%58,%59,%60,%61,%62,%63,%64,%65,%66,%67,%68,%69,%70,%71,"
                 "%72,%73,%74,%75,%76,%77,%78,%79,%80,%81,%82,%83,%84,%85,%86,%87,%88,%89,%90,%91,%92,%93,%94,%95},"
                 "%96,%97,p,1,1,0,1;}"
                 : R8(0), R8(8), R8(16), R8(24), R8(32), R8(40), R8(48), R8(56), R8(64), R8(72), R8(80), R8(88)
                 : "l"(da), "l"(db), "r"(acc));
}

__device__ __forceinline__ void wgmma_ss_n96(float* d, uint64_t da, uint64_t db) {
    asm volatile("wgmma.mma_async.sync.aligned.m64n96k16.f32.bf16.bf16 "
                 "{%0,%1,%2,%3,%4,%5,%6,%7,%8,%9,%10,%11,%12,%13,%14,%15,%16,%17,%18,%19,%20,%21,%22,%23,"
                 "%24,%25,%26,%27,%28,%29,%30,%31,%32,%33,%34,%35,%36,%37,%38,%39,%40,%41,%42,%43,%44,%45,%46,%47},%48,%49,1,1,1,0,1;"
                 : R8(0), R8(8), R8(16), R8(24), R8(32), R8(40) : "l"(da), "l"(db));
}
__device__ __forceinline__ void wgmma_ss_n64(float* d, uint64_t da, uint64_t db) {
    asm volatile("wgmma.mma_async.sync.aligned.m64n64k16.f32.bf16.bf16 "
                 "{%0,%1,%2,%3,%4,%5,%6,%7,%8,%9,%10,%11,%12,%13,%14,%15,%16,%17,%18,%19,%20,%21,%22,%23,"
                 "%24,%25,%26,%27,%28,%29,%30,%31},%32,%33,1,1,1,0,1;"
                 : R8(0), R8(8), R8(16), R8(24) : "l"(da), "l"(db));
}

constexpr int NSS = 1;
constexpr int QCH = 4, QD = 4;
constexpr int WRES = 2, WO_PRE2 = 3, WO_PRE3 = 4;
constexpr int MP = 1168;
constexpr int XT = 36864;
constexpr int XR_STAGE = 14 * 1024;
constexpr int MR_STAGE = 14 * 256;
constexpr int SM_X = 0;
constexpr int SM_XR = 2 * XT;
constexpr int SM_MR = SM_XR + 3 * XR_STAGE;
constexpr int SM_MEM = SM_XR + 2 * XT;
constexpr int SM_SC = SM_MEM + 8 * MP;
constexpr int SM_OB = SM_SC + 3 * 1536;
constexpr int SM_ZERO = SM_OB + 2048;
constexpr int SM_WO = SM_ZERO + 512;
constexpr int SM_WS = SM_WO + 49152;
constexpr int SM_BAR = SM_WS + NSS * 4096;
constexpr int REC_SMEM = SM_BAR + 128 + 1024;

__device__ uint4 g_xr[NSEG * NH * 24 * 64];
__device__ uint4 g_mr[NSEG * NH * 16 * 16];
__device__ unsigned g_flagA[NSEG];

constexpr unsigned long long FSP = 0x111123564ull;
__host__ __device__ constexpr int f_split(int m) { return m < 3 ? 1 : (int)((FSP >> (4 * (11 - m))) & 15); }
constexpr int F_FIRST_SPLIT = f_split(3) > 1 ? 3 : (f_split(4) > 1 ? 4 : (f_split(5) > 1 ? 5 : (f_split(6) > 1 ? 6 : 7)));
struct RecMaps { CUtensorMap w[2][3], wo; };
struct RecParams {
    const bf16* mem0; const bf16* Wq; const bf16* Wk; const bf16* Wv;
    int d0, dv;
};

__device__ __forceinline__ float* red_line(int s, int line) { return g_red + ((s >> 3) * 192 + line) * 256 + (s & 7) * 32; }

#define PIN(x) asm volatile("" : "+r"(x))
#define PINL(x) asm volatile("" : "+l"(x))
__device__ __forceinline__ float4 ld_relaxed4(const float* q) {
    float4 v;
    asm volatile("ld.relaxed.gpu.global.v4.f32 {%0,%1,%2,%3},[%4];" : "=f"(v.x), "=f"(v.y), "=f"(v.z), "=f"(v.w) : "l"(q) : "memory");
    return v;
}
__device__ __forceinline__ unsigned ld_acq(const unsigned* q) {
    unsigned v; asm volatile("ld.acquire.gpu.global.u32 %0,[%1];" : "=r"(v) : "l"(q) : "memory"); return v;
}
__device__ __forceinline__ unsigned ld_relaxed1(const unsigned* q) {
    unsigned v; asm volatile("ld.relaxed.gpu.global.u32 %0,[%1];" : "=r"(v) : "l"(q) : "memory"); return v;
}
__device__ __forceinline__ uint4 ld_relaxed4u(const uint4* q) {
    uint4 v;
    asm volatile("ld.relaxed.gpu.global.v4.u32 {%0,%1,%2,%3},[%4];" : "=r"(v.x), "=r"(v.y), "=r"(v.z), "=r"(v.w) : "l"(q) : "memory");
    return v;
}
__device__ __forceinline__ void reld_relaxed4u(uint4& v, const uint4* q) {
    asm volatile("{.reg .pred p; .reg .b32 q; and.b32 q,%3,0xffff; setp.ne.u32 p,q,0x5000;\n"
                 "@p ld.relaxed.gpu.global.v4.u32 {%0,%1,%2,%3},[%4];}"
                 : "+r"(v.x), "+r"(v.y), "+r"(v.z), "+r"(v.w) : "l"(q) : "memory");
}
__device__ __forceinline__ uint32_t packh2(float lo, float hi) {
    uint32_t r; asm("cvt.rn.f16x2.f32 %0,%1,%2;" : "=r"(r) : "f"(hi), "f"(lo)); return r;
}
__device__ __forceinline__ float maxn(float a, float b) {
    float r; asm("max.NaN.f32 %0,%1,%2;" : "=f"(r) : "f"(fabsf(a)), "f"(fabsf(b))); return r;
}
__device__ __forceinline__ void redh4(uint4* q, const float* v, uint32_t tag) {
    asm volatile("red.relaxed.gpu.global.add.noftz.v4.f16x2 [%0],{%1,%2,%3,%4};"
                 ::"l"(q), "r"(packh2(v[0], v[1])), "r"(packh2(v[2], v[3])), "r"(packh2(v[4], v[5])), "r"(tag) : "memory");
}
__device__ __forceinline__ void red4(float* q, float a, float b, float c2, float d) {
    asm volatile("red.relaxed.gpu.global.add.v4.f32 [%0],{%1,%2,%3,%4};" ::"l"(q), "f"(a), "f"(b), "f"(c2), "f"(d) : "memory");
}
__device__ __forceinline__ unsigned clk32() { return (unsigned)clock64(); }
__device__ __forceinline__ void spin_until(unsigned tl) {
    asm volatile("{.reg .pred p; .reg .u64 c; .reg .u32 lo,hi; .reg .s32 d;\n"
                 "SP%=: mov.u64 c,%%clock64; mov.b64 {lo,hi},c; sub.s32 d,lo,%0; setp.lt.s32 p,d,0; @p bra.uni SP%=;}" ::"r"(tl) : "memory");
}
__device__ __forceinline__ float rcp_fast(float x) { float y; asm("rcp.approx.ftz.f32 %0,%1;" : "=f"(y) : "f"(x)); return y; }
__device__ __forceinline__ void bulk_store(void* gdst, uint32_t src, int bytes) {
    asm volatile("cp.async.bulk.global.shared::cta.bulk_group [%0],[%1],%2;" ::"l"(gdst), "r"(src), "r"(bytes) : "memory");
}
__device__ __forceinline__ void bulk_load(uint32_t dst, const void* gsrc, int bytes, uint32_t bar) {
    asm volatile("cp.async.bulk.shared::cluster.global.mbarrier::complete_tx::bytes [%0],[%1],%2,[%3];"
                 ::"r"(dst), "l"(gsrc), "r"(bytes), "r"(bar) : "memory");
}
__device__ __forceinline__ void bulk_s2s(uint32_t rdst, uint32_t src, int bytes, uint32_t rbar) {
    asm volatile("cp.async.bulk.shared::cluster.shared::cta.mbarrier::complete_tx::bytes [%0],[%1],%2,[%3];"
                 ::"r"(rdst), "r"(src), "r"(bytes), "r"(rbar) : "memory");
}
__device__ __forceinline__ void stas4(uint32_t rdst, uint32_t a, uint32_t b, uint32_t c2, uint32_t d, uint32_t rbar) {
    asm volatile("st.async.weak.shared::cluster.mbarrier::complete_tx::bytes.v4.b32 [%0],{%1,%2,%3,%4},[%5];"
                 ::"r"(rdst), "r"(a), "r"(b), "r"(c2), "r"(d), "r"(rbar) : "memory");
}
__device__ __forceinline__ void stas2(uint32_t rdst, uint32_t a, uint32_t b, uint32_t rbar) {
    asm volatile("st.async.weak.shared::cluster.mbarrier::complete_tx::bytes.v2.b32 [%0],{%1,%2},[%3];"
                 ::"r"(rdst), "r"(a), "r"(b), "r"(rbar) : "memory");
}
__device__ __forceinline__ float4 lds128f(uint32_t a) {
    float4 v; asm volatile("ld.shared.v4.f32 {%0,%1,%2,%3},[%4];" : "=f"(v.x), "=f"(v.y), "=f"(v.z), "=f"(v.w) : "r"(a) : "memory"); return v;
}

__device__ __forceinline__ void flag_seg(int seg) {
    asm volatile("cp.async.bulk.wait_group 0;" ::: "memory");
    asm volatile("red.relaxed.gpu.global.add.u32 [%0],1;" ::"l"(g_flagA + seg) : "memory");
}

__global__ void __launch_bounds__(384, 1) k_rec(const __grid_constant__ CUtensorMap tmx, const __grid_constant__ RecMaps rm, const RecParams p) {
    extern __shared__ uint8_t smem_raw[];
    const uint32_t sb = (s2u(smem_raw) + 1023) & ~1023u;
    const int tid = threadIdx.x, warp = __shfl_sync(0xffffffffu, tid >> 5, 0), lane = tid & 31, g = lane >> 2, t = lane & 3;
    const int l7 = lane & 7, l3 = lane >> 3;
    const int c = blockIdx.x % 3, h = blockIdx.x / 3;
    const int nq = c < 2 ? 3 : 2, nv = 8 - 2 * nq, v0 = 2 * c;
    const uint32_t bXF = sb + SM_BAR, bVX = bXF + 16, bS = bVX + 16, bV = bS + 8, bW = bV + 8;
    const uint32_t peer1 = (c + 1) % 3, peer2 = (c + 2) % 3;
    auto vslot = [](int r, int d) { return (r < 2 ? 6 : 4) + ((d - 2 * r) & 7); };

    if (blockIdx.x == 0) {
        for (int i = tid; i < 1920; i += 384) g_ctr[i] = 0;
        if (tid < NSEG) g_flagA[tid] = 0;
        __threadfence();
        __syncthreads();
    }
    asm volatile("griddepcontrol.launch_dependents;" ::: "memory");
    auto wbox = [&](int ch, int ty) {
        tma2d(sb + SM_XR + (ch & 1) * XT + ty * nq * 4608, &rm.w[c == 2][ty], h * DH + c * (ty == 2 ? 32 : 48), ch * 144, bW + 8 * (ch & 1));
    };
    if (lane == 0 && warp >= 1 && warp < 6)
        asm volatile("prefetch.tensormap [%0];" ::"l"(warp < 4 ? &rm.w[c == 2][warp - 1] : (warp == 4 ? &rm.wo : &tmx)) : "memory");
    if (tid == 0) {
        for (int i = 0; i < 2; i++) { mbar_init(bXF + 8 * i, 1); mbar_init(bVX + 8 * i, 1); mbar_init(bW + 8 * i, 1); }
        mbar_init(bS, 4); mbar_init(bV, nv + 1); mbar_init(bW + 16, 1);
        asm volatile("fence.mbarrier_init.release.cluster;" ::: "memory");
        for (int i = 0; i < 2; i++) { mbar_expect(bW + 8 * i, XT); mbar_expect(bXF + 8 * i, XT); mbar_expect(bVX + 8 * i, (8 - nv) * 1024); }
        mbar_expect(bW + 16, 49152); mbar_expect(bS, 2560); mbar_expect(bV, (8 - nv) * 256);
    }
    __syncthreads();
    if (lane == 0) {
        if (warp >= 1 && warp < 4) { wbox(0, warp - 1); wbox(1, warp - 1); }
        if (warp == 4) tma2d(sb + SM_WO, &rm.wo, c * 192, h * DH, bW + 16);
        if (warp >= 5 && warp < 8) {
            const bf16* W = warp == 5 ? p.Wq : (warp == 6 ? p.Wk : p.Wv);
            asm volatile("cp.async.bulk.prefetch.L2.global [%0],24576;" ::"l"(reinterpret_cast<const uint8_t*>(W) + (size_t)(96 + blockIdx.x) * 24576) : "memory");
        }
    }
    __syncwarp();
    cluster_sync_relaxed();

    if (warp < 8) {
        asm volatile("setmaxnreg.inc.sync.aligned.u32 %0;" ::"n"(184));
        const bool isv = warp >= 2 * nq;
        const int slot = warp;
        uint32_t w[36][4];
        {
            const uint32_t pitch = (isv ? nv : nq) * 32;
            const uint32_t src = sb + SM_XR + (isv ? nq * 9216 + (warp - 2 * nq) * 32 : (warp >= nq ? nq * 4608 + (warp - nq) * 32 : warp * 32)) + 2 * t * pitch + g * 4;
#pragma unroll
            for (int ch = 0; ch < 4; ch++) {
                mbar_wait(bW + 8 * (ch & 1), ch >> 1);
#pragma unroll
                for (int kk = 0; kk < 9; kk++) {
                    const uint32_t q = src + (ch & 1) * XT + kk * 16 * pitch;
                    const uint32_t a = lds32(q), b = lds32(q + pitch), d = lds32(q + 8 * pitch), e = lds32(q + 9 * pitch);
                    uint32_t* o = w[ch * 9 + kk];
                    o[0] = __byte_perm(a, b, 0x5410); o[1] = __byte_perm(a, b, 0x7632);
                    o[2] = __byte_perm(d, e, 0x5410); o[3] = __byte_perm(d, e, 0x7632);
                }
                if (ch < 2) {
                    bar_sync(9, 256);
                    if (tid == 0) mbar_expect(bW + 8 * ch, XT);
                    if (lane == 0 && warp >= 1 && warp < 4) wbox(ch + 2, warp - 1);
                    __syncwarp();
                }
            }
#pragma unroll
            for (int k = 0; k < NSS; k++) {
                const uint32_t a = sb + SM_WS + k * 4096 + (warp >> 2) * 2048 + (warp & 3) * 256 + lane * 4;
                sts32(a, w[36 - NSS + k][0]); sts32(a + 128, w[36 - NSS + k][1]);
                sts32(a + 1024, w[36 - NSS + k][2]); sts32(a + 1152, w[36 - NSS + k][3]);
            }
            fence_async();
            bar_sync(9, 256);
            asm volatile("barrier.cluster.arrive.relaxed.aligned;" ::: "memory");
        }
        const uint32_t wsd = (((sb + SM_WS + (warp >> 2) * 2048) & 0x3FFFF) >> 4) | (64u << 16);
        const uint32_t woff = 2 * t * 32 + (((g >> 2) ^ (t >> 1)) << 4) + (g & 3) * 4;

        float d[16];
        auto xdesc = [&](int sl) { return __shfl_sync(0xffffffffu, (((sb + SM_X + sl * XT) & 0x3FFFF) >> 4) | 0x10000u, 0); };
        auto filler = [&](uint32_t xd, int stg) {
            wg_fence();
#pragma unroll
            for (int k = 36 - NSS; k < 36; k++) wgmma_ss_n32(d, wsd + (k - 36 + NSS) * 256, xd + ((k >> 2) * 256 + (k & 3) * 2), k > 36 - NSS);
#pragma unroll
            for (int k = 0; k < 36 - NSS; k++) wgmma_rs_n32(d, w[k], xd + ((k >> 2) * 256 + (k & 3) * 2), 1);
            wg_commit();
            wg_wait<0>();
            const uint32_t dst = sb + SM_XR + stg * XR_STAGE + slot * 1024 + woff;
#pragma unroll
            for (int j = 0; j < 4; j++) {
                sts32(dst + j * 256, pack2(d[4 * j], d[4 * j + 2]));
                sts32(dst + j * 256 + 32, pack2(d[4 * j + 1], d[4 * j + 3]));
            }
        };
        auto publish = [&](int xs, int stg) {
            bulk_store(reinterpret_cast<uint8_t*>(g_xr) + (size_t)(xs * 96 + blockIdx.x) * 8192, sb + SM_XR + stg * XR_STAGE, 8192);
            asm volatile("cp.async.bulk.commit_group;" ::: "memory");
        };
        auto fwd_v = [&](int sl, int stg) {
            const uint32_t base = sb + SM_XR + stg * XR_STAGE;
            bulk_s2s(mapa(base + vslot(peer1, v0) * 1024, peer1), base + 2 * nq * 1024, nv * 1024, mapa(bVX + 8 * sl, peer1));
            bulk_s2s(mapa(base + vslot(peer2, v0) * 1024, peer2), base + 2 * nq * 1024, nv * 1024, mapa(bVX + 8 * sl, peer2));
        };

        mbar_wait(bXF, 0);
        filler(xdesc(0), 0);
        fence_async();
        bar_sync(9, 256);
        asm volatile("barrier.cluster.wait.aligned;" ::: "memory");
        if (tid == 32) { fwd_v(0, 0); publish(0, 0); }
        __syncwarp();
        mbar_wait(bXF + 8, 0);
        filler(xdesc(1), 1);
        bar_sync(9, 256);
        if (tid == 0) { mbar_expect(bXF, XT); mbar_expect(bXF + 8, XT); }
        cluster_sync_relaxed();
        if (tid == 0) {
            for (int sl = 0; sl < 2; sl++)
                for (int j = 0; j < 3; j++)
                    tma2d_mc(sb + SM_X + sl * XT + (c * 3 + j) * 4096, &tmx, (c * 3 + j) * 64, (2 + sl) * 32, bXF + 8 * sl, 7);
        }
        __syncwarp();
        uint32_t mema = sb + SM_MEM + l7 * MP + l3 * 16;
        const uint32_t xpeer = (g & 2) ? peer2 : peer1;
        const uint32_t rdst0 = mapa(sb + SM_MR + vslot(xpeer, v0 + warp - 2 * nq) * 256 + (2 * t + (g & 1)) * 32 + (((g >> 2) ^ (t >> 1)) << 4), xpeer);
        uint32_t rbar = mapa(bV, xpeer);
        int s3 = 0;
        for (int s = 0; s < NSEG; s++) {
            const int st = s & 1, s3n = s3 == 2 ? 0 : s3 + 1, s3p = s3 == 0 ? 2 : s3 - 1;
            uint32_t rdst = rdst0 + s3 * MR_STAGE;
            uint32_t ldst = sb + SM_MR + s3 * MR_STAGE + slot * 256 + woff;
            PIN(rdst); PIN(rbar); PIN(ldst); PIN(mema);
            float a[QCH][4];
#pragma unroll
            for (int i = 0; i < QCH; i++) { a[i][0] = 0.f; a[i][1] = 0.f; a[i][2] = 0.f; a[i][3] = 0.f; }
            uint32_t wx[NSS][4];
#pragma unroll
            for (int k = 0; k < NSS; k++)
                ldsm4(wx[k], sb + SM_WS + k * 4096 + (warp >> 2) * 2048 + (warp & 3) * 256 + (l3 >> 1) * 1024 + (l3 & 1) * 128 + l7 * 16);
            bar_sync(1, 384);
            if (isv) spin_until(clk32() + p.dv);
            uint32_t bf[18][4];
#pragma unroll
            for (int ii = 0; ii < QD; ii++) ldsm4(bf[17 - ii], mema + (17 - ii) * 64);
#pragma unroll
            for (int ii = 0; ii < 18; ii++) {
                const int i = 17 - ii;
                mma16v(a[(2 * i) % QCH], 2 * i >= 36 - NSS ? wx[2 * i - 36 + NSS] : w[2 * i], bf[i][0], bf[i][1]);
                mma16v(a[(2 * i + 1) % QCH], 2 * i + 1 >= 36 - NSS ? wx[2 * i + 1 - 36 + NSS] : w[2 * i + 1], bf[i][2], bf[i][3]);
                if (i - QD >= 0) ldsm4(bf[i - QD], mema + (i - QD) * 64);
            }
#pragma unroll
            for (int i = 0; i < 4; i++) {
                a[0][i] = (a[2][i] + a[3][i]) + (a[0][i] + a[1][i]);
            }
            const uint32_t w0 = pack2(a[0][0], a[0][2]), w1 = pack2(a[0][1], a[0][3]);
            sts32(ldst, w0); sts32(ldst + 32, w1);
            if (!isv) bar_arrive(8, nq * 64 + 96);
            if (isv && s + 1 < NSEG) {
                uint32_t snd = (g & 1) ? w0 : w1, keep = (g & 1) ? w1 : w0;
                uint32_t rcv = __shfl_xor_sync(0xffffffffu, snd, 4);
                uint32_t lo = (g & 1) ? rcv : keep, hi = (g & 1) ? keep : rcv;
                uint32_t olo = __shfl_xor_sync(0xffffffffu, lo, 8), ohi = __shfl_xor_sync(0xffffffffu, hi, 8);
                stas4(rdst, (g & 2) ? olo : lo, (g & 2) ? ohi : hi, (g & 2) ? lo : olo, (g & 2) ? hi : ohi, rbar);
                __syncwarp();
                if (lane == 0) mbar_arrive(bV);
            }
            const uint32_t xd = xdesc(st);
            if (s + 2 < NSEG) {
                mbar_wait(bXF + 8 * st, ((s + 2) >> 1) & 1);
            }
            fence_async();
            if (warp == 1) bar_sync(6, 256); else bar_arrive(6, 256);
            if (warp < 2) {
                if (s + 1 < NSEG) { mbar_wait(bS, st); mbar_wait(bV, st); }
                if (lane == 0) {
                    if (warp == 0) {
                        if (s >= 1 && s + 3 < NSEG) {
                            mbar_expect(bXF + 8 * (st ^ 1), XT);
                            for (int j = 0; j < 3; j++)
                                tma2d_mc(sb + SM_X + (st ^ 1) * XT + (c * 3 + j) * 4096, &tmx, (c * 3 + j) * 64, (s + 3) * 32, bXF + 8 * (st ^ 1), 7);
                        }
                    } else {
                        if (s >= 1) flag_seg(s - 1);
                        bulk_store(reinterpret_cast<uint8_t*>(g_mr) + (size_t)(s * 32 + h) * 4096 + c * 1280,
                                   sb + SM_MR + s3 * MR_STAGE + nq * 256, (8 - nq) * 256);
                        asm volatile("cp.async.bulk.commit_group;" ::: "memory");
                        if (s + 2 < NSEG) fwd_v(st ^ 1, s3n);
                    }
                }
                __syncwarp();
            }
            if (s + 2 < NSEG) {
                bar_sync(5, 384);
                filler(xd, s3p);
            } else {
                bar_sync(5, 384);
            }
            if (tid == 32 && s + 1 < NSEG) publish(s + 1, s3n);
            __syncwarp();
            s3 = s3n;
        }
        if (tid == 32) flag_seg(NSEG - 1);
    } else {
        asm volatile("setmaxnreg.dec.sync.aligned.u32 %0;" ::"n"(136));
        const int wq = warp - 8, wt = tid - 256;
        uint32_t woa = sb + SM_WO + wt * 16;
        uint32_t am0 = 0;
        {
            for (int i = wt; i < 576; i += 128) g_redh[blockIdx.x * 576 + i] = make_uint4(0u, 0u, 0u, 0u);
            float4* z = reinterpret_cast<float4*>(g_red) + blockIdx.x * 1024;
            for (int i = wt; i < 1024; i += 128) z[i] = make_float4(0.f, 0.f, 0.f, 0.f);
            constexpr int ZN = (SEQ - F_FIRST_SPLIT * 192) * (DM / 4) / 96;
            float4* za = reinterpret_cast<float4*>(g_acc + F_FIRST_SPLIT * 192 * DM) + blockIdx.x * ZN;
            for (int i = wt; i < ZN; i += 128) za[i] = make_float4(0.f, 0.f, 0.f, 0.f);
            if (wt == 96) {
                for (int sl = 0; sl < 2; sl++)
                    for (int j = 0; j < 3; j++)
                        tma2d_mc(sb + SM_X + sl * XT + (c * 3 + j) * 4096, &tmx, (c * 3 + j) * 64, sl * 32, bXF + 8 * sl, 7);
            }
            __syncwarp();
        }
        {
            asm volatile("barrier.cluster.arrive.relaxed.aligned;" ::: "memory");
            uint32_t wo[24][4];
            mbar_wait(bW + 16, 0);
#pragma unroll
            for (int k = 0; k < 24; k++) {
                const uint32_t q = sb + SM_WO + ((k & 7) * 16 + 2 * t) * 384 + (k >> 3) * 128 + wq * 32 + g * 4;
                wo[k][0] = lds32(q); wo[k][1] = lds32(q + 384); wo[k][2] = lds32(q + 8 * 384); wo[k][3] = lds32(q + 9 * 384);
            }
            bar_sync(4, 128);
#pragma unroll
            for (int k = 0; k < 24; k++) {
                uint32_t a = wo[k][0], b = wo[k][1], d = wo[k][2], e = wo[k][3];
                wo[k][0] = __byte_perm(a, b, 0x5410); wo[k][1] = __byte_perm(a, b, 0x7632);
                wo[k][2] = __byte_perm(d, e, 0x5410); wo[k][3] = __byte_perm(d, e, 0x7632);
                sts128(woa + k * 2048, wo[k]);
            }
            sts32(sb + SM_ZERO + wt * 4, 0u);
            for (int i = wt; i < 8 * 72; i += 128) {
                const int r = i / 72, cc = i % 72;
                uint4 v = __ldg(reinterpret_cast<const uint4*>(p.mem0 + r * DM) + cc);
                am0 = __vmaxu2(__vmaxu2(am0, __vmaxu2(v.x & 0x7fff7fffu, v.y & 0x7fff7fffu)), __vmaxu2(v.z & 0x7fff7fffu, v.w & 0x7fff7fffu));
                asm volatile("st.shared.v4.u32 [%0],{%1,%2,%3,%4};" ::"r"(sb + SM_MEM + r * MP + cc * 16), "r"(v.x), "r"(v.y), "r"(v.z), "r"(v.w) : "memory");
            }
        }
        __threadfence();
        bar_sync(4, 128);
        if (wt == 0) asm volatile("red.relaxed.gpu.global.add.u32 [%0],1;" ::"l"(g_sync) : "memory");
        asm volatile("barrier.cluster.wait.aligned;" ::: "memory");
        cluster_sync_relaxed();
        bar_arrive(1, 384);
        uint32_t wa[8][4], wb[8][4], wc[WRES + 1][4];
#pragma unroll
        for (int k = 0; k < 8; k++) lds128(wa[k], woa + k * 2048);
#pragma unroll
        for (int k = 0; k < 8; k++) lds128(wb[k], woa + (8 + k) * 2048);
#pragma unroll
        for (int k = 0; k < WRES; k++) lds128(wc[k], woa + (16 + k) * 2048);

        int ex;
        {
            const uint32_t m = __reduce_max_sync(0xffffffffu, max(am0 & 0xffffu, am0 >> 16));
            ex = m ? min(max(4 - ((int)(m >> 7) - 127), -60), 60) : 0;
        }
        const float SC = 0.08838834764831845f * 1.4426950408889634f;
        uint32_t L16 = lane * 16;
        uint32_t AB = (l3 >> 1) * 256 + l7 * 32 + (((l3 & 1) ^ (l7 >> 2)) << 4);
        uint32_t AA = (l3 & 1) * 256 + l7 * 32 + (((l3 >> 1) ^ (l7 >> 2)) << 4);
        const uint32_t scu = sb + SM_SC + c * 1536 + (wq == 0 ? 1024 : (wq - 1) * 512);
        const uint32_t sc1 = mapa(scu, peer1), sc2 = mapa(scu, peer2), sb1 = mapa(bS, peer1), sb2 = mapa(bS, peer2);
        const uint32_t wou = sb + SM_WO + wq * 512;
        const int vs = vslot(c, 2 * wq);
        int s3 = 0;
        for (int s = 0; s + 1 < NSEG; s++) {
            const int st = s & 1;
            const uint32_t xr = sb + SM_XR + s3 * XR_STAGE, mr = sb + SM_MR + s3 * MR_STAGE;
            PIN(L16); PIN(AB); PIN(AA);
            if (wq < 3) {
                uint32_t kf[3][4], q0[4], q1[4];
                float ca[4] = {0.f, 0.f, 0.f, 0.f}, cb[4] = {0.f, 0.f, 0.f, 0.f}, cc[4] = {0.f, 0.f, 0.f, 0.f};
                if (wq) {
                    const uint32_t ka = xr + nq * 1024 + (wq - 1) * 512 + AB;
                    ldsm4(kf[0], ka); ldsm4(kf[1], ka + 1024); ldsm4(kf[2], nq == 3 ? ka + 2048 : sb + SM_ZERO + AB);
                    uint32_t da1 = sc1 + L16, da2 = sc2 + L16, qa = mr + AA;
                    PIN(da1); PIN(da2); PIN(qa);
                    bar_sync(8, nq * 64 + 96);
                    ldsm4(q0, qa); ldsm4(q1, qa + 512);
                    float da[4] = {0.f, 0.f, 0.f, 0.f}, db[4] = {0.f, 0.f, 0.f, 0.f}, dc[4] = {0.f, 0.f, 0.f, 0.f};
                    mma16(ca, q0, kf[0][0], kf[0][1]); mma16(da, q0, kf[0][2], kf[0][3]);
                    mma16(cb, q0, kf[1][0], kf[1][1]); mma16(db, q0, kf[1][2], kf[1][3]);
                    mma16(cc, q1, kf[2][0], kf[2][1]); mma16(dc, q1, kf[2][2], kf[2][3]);
                    const uint32_t rr[4] = {__float_as_uint((ca[0] + cb[2]) + cc[0]), __float_as_uint((ca[1] + cb[3]) + cc[1]),
                                            __float_as_uint((da[0] + db[2]) + dc[0]), __float_as_uint((da[1] + db[3]) + dc[1])};
                    stas4(da1, rr[0], rr[1], rr[2], rr[3], sb1); stas4(da2, rr[0], rr[1], rr[2], rr[3], sb2);
                    sts128(scu + L16, rr);
                } else {
                    uint32_t da1 = sc1 + (L16 >> 1), da2 = sc2 + (L16 >> 1), qa = mr + AA, ka = mr + nq * 256 + AB;
                    uint32_t kb = nq == 3 ? ka + 512 : sb + SM_ZERO + AB;
                    PIN(da1); PIN(da2); PIN(qa); PIN(ka); PIN(kb);
                    bar_sync(8, nq * 64 + 96);
                    ldsm4(q0, qa); ldsm4(kf[0], ka); ldsm4(q1, qa + 512); ldsm2(kf[1], kb);
                    mma16(ca, q0, kf[0][0], kf[0][1]); mma16(cb, q0, kf[0][2], kf[0][3]); mma16(cc, q1, kf[1][0], kf[1][1]);
                    const uint32_t r0 = __float_as_uint((ca[0] + cb[2]) + cc[0]), r1 = __float_as_uint((ca[1] + cb[3]) + cc[1]);
                    stas2(da1, r0, r1, sb1); stas2(da2, r0, r1, sb2);
                    asm volatile("st.shared.v2.u32 [%0],{%1,%2};" ::"r"(scu + (L16 >> 1)), "r"(r0), "r"(r1) : "memory");
                }
                __syncwarp();
                if (L16 == 0) mbar_arrive(bS);
            } else {
                if (lane == 0) {
                    if (s >= 1 && s + 4 < NSEG)
                        asm volatile("prefetch.global.L2 [%0];" ::"l"(g_redh + (((s + 3) >> 3) * 96 + blockIdx.x) * 72 + ((s + 3) & 7) * 8));
                    if (s == 0) {
                        int it = 0;
                        while (ld_acq(g_sync) < 96) { if (++it > (1 << 22)) __trap(); }
                    }
                }
                __syncwarp();
            }
            uint32_t va[2][2][4], vb[4];
            mbar_wait(bVX + 8 * st, (s >> 1) & 1);
            const uint32_t v0a = xr + vs * 1024 + AB;
            ldsm4t(va[0][0], v0a); ldsm4t(va[1][0], v0a + 1024);
            uint4* rl = g_redh + (((s >> 3) * 96 + c * 32 + wq * 4) * 9 + (s & 7)) * 8 + (L16 >> 7) * 72 + ((L16 >> 4) & 7);
            PINL(rl);
            mbar_wait(bS, s & 1);
            float4 sa, sbb; float2 sm2;
            {
                const uint32_t scl = sb + SM_SC + L16;
                const float4 a0 = lds128f(scl), a1 = lds128f(scl + 1536), a2 = lds128f(scl + 3072);
                const float4 b0 = lds128f(scl + 512), b1 = lds128f(scl + 2048), b2 = lds128f(scl + 3584);
                const uint32_t scm = sb + SM_SC + 1024 + (L16 >> 1);
                const float2 m0 = lds64f(scm), m1 = lds64f(scm + 1536), m2 = lds64f(scm + 3072);
                sa.x = a0.x + a1.x + a2.x; sa.y = a0.y + a1.y + a2.y; sa.z = a0.z + a1.z + a2.z; sa.w = a0.w + a1.w + a2.w;
                sbb.x = b0.x + b1.x + b2.x; sbb.y = b0.y + b1.y + b2.y; sbb.z = b0.z + b1.z + b2.z; sbb.w = b0.w + b1.w + b2.w;
                sm2.x = m0.x + m1.x + m2.x; sm2.y = m0.y + m1.y + m2.y;
            }
            float mx = fmaxf(fmaxf(fmaxf(sa.x, sa.y), fmaxf(sa.z, sa.w)), fmaxf(fmaxf(sbb.x, sbb.y), fmaxf(sbb.z, sbb.w)));
            mx = fmaxf(mx, fmaxf(sm2.x, sm2.y));
            {
                const float x1 = __shfl_xor_sync(0xffffffffu, mx, 1), x2 = __shfl_xor_sync(0xffffffffu, mx, 2), x3 = __shfl_xor_sync(0xffffffffu, mx, 3);
                ldsm4t(va[0][1], v0a + 512); ldsm4t(va[1][1], v0a + 1024 + 512);
                mbar_wait(bV, s & 1);
                ldsm4t(vb, mr + vs * 256 + AB);
                mx = fmaxf(fmaxf(mx, x1), fmaxf(x2, x3));
            }
            uint32_t ws[8][4];
#pragma unroll
            for (int k = WRES; k < WRES + WO_PRE2 && k < 8; k++) lds128(ws[k], wou + L16 + (16 + k) * 2048);
            const float mo = mx * SC;
            const float e0 = ex2(fmaf(sa.x, SC, -mo)), e1 = ex2(fmaf(sa.y, SC, -mo)), e2 = ex2(fmaf(sa.z, SC, -mo)), e3 = ex2(fmaf(sa.w, SC, -mo));
            float o0[4] = {0.f, 0.f, 0.f, 0.f}, o1[4] = {0.f, 0.f, 0.f, 0.f}, o2[4] = {0.f, 0.f, 0.f, 0.f};
            const uint32_t one = 0x3f803f80u, one4[4] = {one, one, one, one};
            { const uint32_t p0 = pack2(e0, e1), p1 = pack2(e2, e3); mma16(o0, va[0][0], p0, p1); mma16(o1, va[1][0], p0, p1); mma16(o2, one4, p0, p1); }
            const float e4 = ex2(fmaf(sbb.x, SC, -mo)), e5 = ex2(fmaf(sbb.y, SC, -mo)), e6 = ex2(fmaf(sbb.z, SC, -mo)), e7 = ex2(fmaf(sbb.w, SC, -mo));
            { const uint32_t p0 = pack2(e4, e5), p1 = pack2(e6, e7); mma16(o0, va[0][1], p0, p1); mma16(o1, va[1][1], p0, p1); mma16(o2, one4, p0, p1); }
            const float e8 = ex2(fmaf(sm2.x, SC, -mo)), e9 = ex2(fmaf(sm2.y, SC, -mo));
            { const uint32_t p0 = pack2(e8, e9); mma8(o0, vb[0], vb[1], p0); mma8(o1, vb[2], vb[3], p0); mma8(o2, one, one, p0); }
            {
                const uint32_t oa = sb + SM_OB + wq * 512 + (L16 >> 2);
                sts32(oa, pack2(o0[0], o0[1])); sts32(oa + 128, pack2(o0[2], o0[3]));
                sts32(oa + 256, pack2(o1[0], o1[1])); sts32(oa + 384, pack2(o1[2], o1[3]));
            }
            bar_sync(4, 128);
            uint32_t ob[4][4];
#pragma unroll
            for (int j = 0; j < 4; j++) ldsm4t(ob[j], sb + SM_OB + L16 + 512 * j);
            const float fs = __int_as_float((127 + ex) << 23);
            const float i0 = rcp_fast(o2[0]) * fs, i1 = rcp_fast(o2[1]) * fs;
            float v[12];
            {
                float r[6][4];
#pragma unroll
                for (int i = 0; i < 6; i++) { r[i][0] = 0.f; r[i][1] = 0.f; r[i][2] = 0.f; r[i][3] = 0.f; }
#pragma unroll
                for (int k = WRES + WO_PRE2; k < WRES + WO_PRE3 && k < 8; k++) lds128(ws[k], wou + L16 + (16 + k) * 2048);
#pragma unroll
                for (int i = 0; i < 8; i++) {
                    mma16v(r[(i & 1) ? 3 : 0], wa[i], ob[i >> 1][(i & 1) * 2], ob[i >> 1][(i & 1) * 2 + 1]);
                    mma16v(r[(i & 1) ? 4 : 1], wb[i], ob[i >> 1][(i & 1) * 2], ob[i >> 1][(i & 1) * 2 + 1]);
                    mma16v(r[(i & 1) ? 5 : 2], i < WRES ? wc[i] : ws[i], ob[i >> 1][(i & 1) * 2], ob[i >> 1][(i & 1) * 2 + 1]);
                    if (i + WRES + WO_PRE3 < 8) lds128(ws[i + WRES + WO_PRE3], wou + L16 + (16 + i + WRES + WO_PRE3) * 2048);
                }
#pragma unroll
                for (int j = 0; j < 3; j++) {
                    { r[j][0] += r[3 + j][0]; r[j][1] += r[3 + j][1]; r[j][2] += r[3 + j][2]; r[j][3] += r[3 + j][3]; }
                    v[4 * j] = r[j][0] * i0; v[4 * j + 1] = r[j][2] * i0; v[4 * j + 2] = r[j][1] * i1; v[4 * j + 3] = r[j][3] * i1;
                }
                const float m8 = maxn(maxn(maxn(v[0], v[1]), maxn(v[2], v[3])), maxn(maxn(v[4], v[5]), maxn(v[6], v[7])));
                const float m = maxn(maxn(maxn(v[8], v[9]), maxn(v[10], v[11])), m8);
                const uint32_t tag = m < 1024.f ? (m >= 0.0625f ? 0x3c003c00u : 0x00003c00u) : 0x54003c00u;
                redh4(rl, v, tag);
                bar_arrive(5, 384);
                redh4(rl + 16 * 72, v + 6, tag);
            }
            const unsigned tred = clk32();
            if (wt == 0) {
                if (s + 2 < NSEG) { mbar_expect(bS, 2560); mbar_expect(bV, (8 - nv) * 256); }
                if (s + 3 < NSEG) mbar_expect(bVX + 8 * st, (8 - nv) * 1024);
            }
            {
                const uint4* gl = rl - c * 32 * 72;
                uint32_t ma = sb + SM_MEM + wq * 32 + ((L16 >> 4) & 3) * (2 * MP) + (L16 >> 6) * 4;
                PINL(gl); PIN(ma);
                unsigned tl = tred + p.d0;
                spin_until(tl);
                uint4 u[2][3];
#pragma unroll
                for (int j = 0; j < 2; j++)
#pragma unroll
                    for (int cc = 0; cc < 3; cc++) u[j][cc] = ld_relaxed4u(gl + (cc * 32 + j * 16) * 72);
                const uint32_t rebias = (uint32_t)(112 - ex) * 0x00800080u;
                int it = 0;
                auto cvt = [&](uint32_t x) { return ((((x + 0x00030004u) & 0x7ff87ff8u) >> 3) + rebias) | (x & 0x80008000u); };
                auto put = [&](int j, int cc) {
                    sts32(ma + (cc * 192 + ((3 * j) >> 1) * 64) * 2 + ((3 * j) & 1) * MP, u[j][cc].x);
                    sts32(ma + (cc * 192 + ((3 * j + 1) >> 1) * 64) * 2 + ((3 * j + 1) & 1) * MP, u[j][cc].y);
                    sts32(ma + (cc * 192 + ((3 * j + 2) >> 1) * 64) * 2 + ((3 * j + 2) & 1) * MP, u[j][cc].z);
                };
#pragma unroll
                for (int j = 0; j < 2; j++)
#pragma unroll
                    for (int cc = 0; cc < 3; cc++) {
                        u[j][cc].x = cvt(u[j][cc].x); u[j][cc].y = cvt(u[j][cc].y); u[j][cc].z = cvt(u[j][cc].z);
                        put(j, cc);
                    }
                {
                    const uint32_t bad = ((u[0][0].w ^ 0x5000u) | (u[0][1].w ^ 0x5000u) | (u[0][2].w ^ 0x5000u)) |
                                         ((u[1][0].w ^ 0x5000u) | (u[1][1].w ^ 0x5000u) | (u[1][2].w ^ 0x5000u));
                    const uint32_t tg = max(max(max(u[0][0].w, u[0][1].w), u[0][2].w), max(max(u[1][0].w, u[1][1].w), u[1][2].w));
                    const bool clean = __all_sync(0xffffffffu, (bad & 0xffffu) == 0 && tg < 0x54000000u);
                    const bool big = __any_sync(0xffffffffu, tg >= 0x3c000000u);
                    if (__builtin_expect(!(clean && big), 0)) {
                        while (true) {
                            bool ok = true;
#pragma unroll
                            for (int j = 0; j < 2; j++)
#pragma unroll
                                for (int cc = 0; cc < 3; cc++) ok = ok && (u[j][cc].w & 0xffffu) == 0x5000u;
                            if (__all_sync(0xffffffffu, ok)) break;
                            if (++it > (1 << 20)) __trap();
                            uint32_t redo = 0;
#pragma unroll
                            for (int j = 0; j < 2; j++)
#pragma unroll
                                for (int cc = 0; cc < 3; cc++) {
                                    if ((u[j][cc].w & 0xffffu) != 0x5000u) redo |= 1u << (j * 3 + cc);
                                    reld_relaxed4u(u[j][cc], gl + (cc * 32 + j * 16) * 72);
                                }
#pragma unroll
                            for (int j = 0; j < 2; j++)
#pragma unroll
                                for (int cc = 0; cc < 3; cc++) {
                                    const bool rd = (redo >> (j * 3 + cc)) & 1;
                                    u[j][cc].x = rd ? cvt(u[j][cc].x) : u[j][cc].x; u[j][cc].y = rd ? cvt(u[j][cc].y) : u[j][cc].y;
                                    u[j][cc].z = rd ? cvt(u[j][cc].z) : u[j][cc].z;
                                    put(j, cc);
                                }
                        }
                        const uint32_t t2 = max(max(max(u[0][0].w, u[0][1].w), u[0][2].w), max(max(u[1][0].w, u[1][1].w), u[1][2].w));
                        if (__any_sync(0xffffffffu, t2 >= 0x54000000u) || !__any_sync(0xffffffffu, t2 >= 0x3c000000u)) {
                            const float isc = __int_as_float((127 - ex) << 23);
                            float* fl = red_line(s, c * 64 + wq * 4 + (L16 >> 7)) + ((L16 >> 2) & 28);
#pragma unroll
                            for (int i = 0; i < 4; i++) red4(fl + i * 16 * 256, v[3 * i], v[3 * i + 1], v[3 * i + 2], 1.0f);
                            const float* fg = fl - c * 64 * 256;
#pragma unroll
                            for (int j = 0; j < 2; j++)
#pragma unroll
                                for (int cc = 0; cc < 3; cc++) {
                                    float4 a, b;
                                    while (true) {
                                        a = ld_relaxed4(fg + (cc * 64 + j * 32) * 256); b = ld_relaxed4(fg + (cc * 64 + j * 32 + 16) * 256);
                                        if (__all_sync(0xffffffffu, a.w == 32.f && b.w == 32.f)) break;
                                        if (++it > (1 << 20)) __trap();
                                    }
                                    u[j][cc].x = pack2(a.x * isc, a.y * isc); u[j][cc].y = pack2(a.z * isc, b.x * isc); u[j][cc].z = pack2(b.y * isc, b.z * isc);
                                    put(j, cc);
                                }
                        }
                    }
                }
                bar_arrive(1, 384);
                uint32_t am = max(max(u[0][0].x << 1, u[0][1].y << 1), max(u[1][1].x << 1, u[1][2].y << 1));
                am = __reduce_max_sync(0xffffffffu, am >> 24);
                if (am) ex = min(max(4 - ((int)am - 127), -60), 60);
                s3 = s3 == 2 ? 0 : s3 + 1;
            }
        }
        if (wq < 3) bar_sync(8, nq * 64 + 96);
        bar_arrive(5, 384);
    }
    cluster_sync();
}

constexpr int H_STAGES = 4, H_STAGE = 57344;
constexpr int HELP_SMEM = H_STAGES * H_STAGE + 1024 + 256;
constexpr int NBLK = 11;
enum { T_EXIT = 0, T_G0, T_F, T_AB, T_AA, T_FS, T_FN };
enum { C_HG = 0, C_HB = 32, C_GATE = 33, C_G0 = 48, C_AB = 64, C_HF = 96, C_AA = 128, C_HAA = 160, C_F = 256 };
constexpr int NG0 = NBLK * 9;
constexpr int ABH = 6;
constexpr int ABT = (BH + ABH - 1) / ABH;
constexpr int NB_UNITS = NG0 + 16 * ABT;
__host__ __device__ constexpr int aa_units(int seg) { return seg < 36 ? 3 : 6; }
constexpr unsigned AA_CTAS = 4;
constexpr unsigned AA_CTAS2 = 8;
constexpr unsigned AA_CTAS3 = 18;
constexpr int AA_B3 = 9;
constexpr int AA_LATE = 61;
constexpr int NFB = 12;
__host__ __device__ constexpr int f_row0(int m) { return m < 10 ? m * 192 : 1856 + (m - 10) * 128; }
__host__ __device__ constexpr int f_rows(int m) { return m < 9 ? 192 : (m < 11 ? 128 : 64); }
__host__ __device__ constexpr int f_blk(int seg) { return seg < 54 ? seg / 6 : 9 + (seg - 54) / 4; }
constexpr int DRAIN_B = 5;
constexpr int SPIN_NS = 20;
constexpr int FNM = 0x7f0;
__host__ __device__ constexpr int f_ntiles(int m) { return m < 11 ? (((FNM >> m) & 1) ? 6 : 3) : 9; }

__device__ __forceinline__ void signal(unsigned* q, int lane, unsigned n = 1) {
    __syncwarp();
    if (lane == 0) asm volatile("red.release.gpu.global.add.u32 [%0],%1;" ::"l"(q), "r"(n) : "memory");
}

__device__ __forceinline__ int pos_q(int d) { return (d / 3) * 8 + d % 3; }
__device__ __forceinline__ int pos_k(int d) { return (d / 3) * 8 + d % 3 + (d < 6 ? 3 : 2); }
__device__ __forceinline__ int mpos_k(int d) { return (d / 3) * 5 + d % 3; }
__device__ __forceinline__ int mpos_v(int d) { return d < 2 ? 3 + d : (d < 4 ? 6 + d : 8 + d); }
__device__ __forceinline__ int pos_v(int d) { return d < 2 ? 6 + d : (d < 4 ? 12 + d : 16 + d); }

__device__ __forceinline__ uint4 quad_tr(const uint32_t* v, int t) {
    uint32_t a0 = (t & 1) ? v[0] : v[1], a1 = (t & 1) ? v[2] : v[3];
    a0 = __shfl_xor_sync(0xffffffffu, a0, 1); a1 = __shfl_xor_sync(0xffffffffu, a1, 1);
    const uint32_t b0 = (t & 1) ? a0 : v[0], b1 = (t & 1) ? v[1] : a0, b2 = (t & 1) ? a1 : v[2], b3 = (t & 1) ? v[3] : a1;
    uint32_t c0 = (t & 2) ? b0 : b2, c1 = (t & 2) ? b1 : b3;
    c0 = __shfl_xor_sync(0xffffffffu, c0, 2); c1 = __shfl_xor_sync(0xffffffffu, c1, 2);
    uint4 o;
    o.x = (t & 2) ? c0 : b0; o.y = (t & 2) ? c1 : b1; o.z = (t & 2) ? b2 : c0; o.w = (t & 2) ? b3 : c1;
    return o;
}
template <int BN>
__device__ __forceinline__ void store_tile(const float* acc, bf16* q, int pitch, int t) {
#pragma unroll
    for (int j = 0; j < BN / 32; j++) {
        uint32_t lo[4], hi[4];
#pragma unroll
        for (int i = 0; i < 4; i++) {
            lo[i] = pack2(acc[16 * j + 4 * i], acc[16 * j + 4 * i + 1]); hi[i] = pack2(acc[16 * j + 4 * i + 2], acc[16 * j + 4 * i + 3]);
        }
        *reinterpret_cast<uint4*>(q + j * 32 + t * 8) = quad_tr(lo, t);
        *reinterpret_cast<uint4*>(q + (size_t)8 * pitch + j * 32 + t * 8) = quad_tr(hi, t);
    }
}

template <int MT>
__device__ __forceinline__ void attnA_unit(uint32_t xr, uint32_t mr, int s, int h, int lane, uint32_t rel) {
    const int g = lane >> 2, t = lane & 3, l7 = lane & 7, l3 = lane >> 3;
    const float SC = 0.08838834764831845f * 1.4426950408889634f;
    constexpr int NT = MT ? 5 : 3;
    const uint32_t offA = (l7 + (l3 & 1) * 8) * 32 + (((l3 >> 1) ^ (l7 >> 2)) << 4);
    const uint32_t offB = (l7 + (l3 >> 1) * 8) * 32 + (((l3 & 1) ^ (l7 >> 2)) << 4);
    float sa[NT][4];
#pragma unroll
    for (int n = 0; n < NT; n++)
#pragma unroll
        for (int i = 0; i < 4; i++) sa[n][i] = 0.f;
#pragma unroll
    for (int hf = 0; hf < 2; hf++) {
        uint32_t qf[4][4], k0[4][4], k1[4][4], km[4][2];
#pragma unroll
        for (int i = 0; i < 4; i++) {
            const int d = hf * 4 + i;
            ldsm4(qf[i], xr + pos_q(d) * 1024 + MT * 512 + offA);
            ldsm2(km[i], mr + mpos_k(d) * 256 + (offB & 255));
            ldsm4(k0[i], xr + pos_k(d) * 1024 + offB);
            if (MT) ldsm4(k1[i], xr + pos_k(d) * 1024 + 512 + offB);
        }
#pragma unroll
        for (int i = 0; i < 4; i++) {
            mma16(sa[0], qf[i], km[i][0], km[i][1]);
            mma16(sa[1], qf[i], k0[i][0], k0[i][1]); mma16(sa[2], qf[i], k0[i][2], k0[i][3]);
            if (MT) { mma16(sa[NT - 2], qf[i], k1[i][0], k1[i][1]); mma16(sa[NT - 1], qf[i], k1[i][2], k1[i][3]); }
        }
    }
    if (2 * t > g) sa[NT - 2][0] = -INFINITY;
    if (2 * t + 1 > g) sa[NT - 2][1] = -INFINITY;
    sa[NT - 1][0] = -INFINITY; sa[NT - 1][1] = -INFINITY;
    if (2 * t > g) sa[NT - 1][2] = -INFINITY;
    if (2 * t + 1 > g) sa[NT - 1][3] = -INFINITY;
    float m0 = fmaxf(sa[0][0], sa[0][1]), m1 = fmaxf(sa[0][2], sa[0][3]);
#pragma unroll
    for (int n = 1; n < NT; n++) { m0 = fmaxf(m0, fmaxf(sa[n][0], sa[n][1])); m1 = fmaxf(m1, fmaxf(sa[n][2], sa[n][3])); }
    m0 = fmaxf(m0, __shfl_xor_sync(0xffffffffu, m0, 1)); m1 = fmaxf(m1, __shfl_xor_sync(0xffffffffu, m1, 1));
    m0 = fmaxf(m0, __shfl_xor_sync(0xffffffffu, m0, 2)); m1 = fmaxf(m1, __shfl_xor_sync(0xffffffffu, m1, 2));
    m0 *= SC; m1 *= SC;
    float s0 = 0.f, s1 = 0.f;
#pragma unroll
    for (int n = 0; n < NT; n++) {
        sa[n][0] = ex2(fmaf(sa[n][0], SC, -m0)); sa[n][1] = ex2(fmaf(sa[n][1], SC, -m0));
        sa[n][2] = ex2(fmaf(sa[n][2], SC, -m1)); sa[n][3] = ex2(fmaf(sa[n][3], SC, -m1));
        s0 += sa[n][0] + sa[n][1]; s1 += sa[n][2] + sa[n][3];
    }
    s0 += __shfl_xor_sync(0xffffffffu, s0, 1); s1 += __shfl_xor_sync(0xffffffffu, s1, 1);
    s0 += __shfl_xor_sync(0xffffffffu, s0, 2); s1 += __shfl_xor_sync(0xffffffffu, s1, 2);
    s0 = rcp_fast(s0); s1 = rcp_fast(s1);
    uint32_t pa[NT][2];
#pragma unroll
    for (int n = 0; n < NT; n++) { pa[n][0] = pack2(sa[n][0] * s0, sa[n][1] * s0); pa[n][1] = pack2(sa[n][2] * s1, sa[n][3] * s1); }
    const uint32_t p0[4] = {pa[1][0], pa[1][1], pa[2][0], pa[2][1]}, p1[4] = {pa[NT - 2][0], pa[NT - 2][1], pa[NT - 1][0], pa[NT - 1][1]};
    bf16* op = g_O + (size_t)(s * 32 + MT * 16 + g) * OK + h * DH + t * 8;
#pragma unroll
    for (int dh = 0; dh < 2; dh++) {
        uint32_t f0[4][4], f1[4][4], f2[4][2];
#pragma unroll
        for (int n2 = 0; n2 < 4; n2++) {
            const int d = dh * 4 + n2;
            ldsm4t(f0[n2], xr + pos_v(d) * 1024 + offA);
            if (MT) ldsm4t(f1[n2], xr + pos_v(d) * 1024 + 512 + offA);
            ldsm2t(f2[n2], mr + mpos_v(d) * 256 + (offB & 255));
        }
        uint32_t lo[8], hi[8];
#pragma unroll
        for (int n2 = 0; n2 < 4; n2++) {
            float oa0[4] = {0.f, 0.f, 0.f, 0.f}, oa1[4] = {0.f, 0.f, 0.f, 0.f};
            mma16(oa0, p0, f0[n2][0], f0[n2][1]); mma16(oa1, p0, f0[n2][2], f0[n2][3]);
            if (MT) { mma16(oa0, p1, f1[n2][0], f1[n2][1]); mma16(oa1, p1, f1[n2][2], f1[n2][3]); }
            mma8(oa0, pa[0][0], pa[0][1], f2[n2][0]); mma8(oa1, pa[0][0], pa[0][1], f2[n2][1]);
            lo[2 * n2] = pack2(oa0[0], oa0[1]); hi[2 * n2] = pack2(oa0[2], oa0[3]);
            lo[2 * n2 + 1] = pack2(oa1[0], oa1[1]); hi[2 * n2 + 1] = pack2(oa1[2], oa1[3]);
        }
        if (dh == 1) { __syncwarp(); if (lane == 0) mbar_arrive(rel); }
#pragma unroll
        for (int q = 0; q < 2; q++) {
            *reinterpret_cast<uint4*>(op + dh * 64 + q * 32) = quad_tr(lo + 4 * q, t);
            *reinterpret_cast<uint4*>(op + (size_t)8 * OK + dh * 64 + q * 32) = quad_tr(hi + 4 * q, t);
        }
    }
}

template <int V> struct IC { static constexpr int value = V; };
__device__ __forceinline__ void attnB_unit(uint32_t sQ, int q0, int hh, int wq, int lane, uint32_t rel) {
    const int g = lane >> 2, t = lane & 3, l7 = lane & 7, l3 = lane >> 3;
    const uint32_t sK = sQ + 128 * 48, sV = sK + 384 * 48;
    const int sh = (hh & 3) * 2;
    uint32_t qa[2][4], qb[2][2];
#pragma unroll
    for (int m = 0; m < 2; m++) {
        ldsm4(qa[m], sQ + (wq * 32 + m * 16 + l7 + (l3 & 1) * 8) * 48 + (l3 >> 1) * 16);
        ldsm2(qb[m], sQ + (wq * 32 + m * 16 + l7 + (l3 & 1) * 8) * 48 + 32);
        if (2 * t < sh) { qa[m][0] = 0u; qa[m][1] = 0u; }
        if (16 + 2 * t >= sh + 18) { qb[m][0] = 0u; qb[m][1] = 0u; }
    }
    const bool one0 = (sh == 6 && g == 0), one2 = (sh != 6 && g == 7);
    float gt[2][2];
#pragma unroll
    for (int m = 0; m < 2; m++) { gt[m][0] = __ldcg(g_gate + q0 + wq * 32 + m * 16 + g); gt[m][1] = __ldcg(g_gate + q0 + wq * 32 + m * 16 + g + 8); }
    const float SC = 0.23570226039551584f * 1.4426950408889634f;
    float o[2][3][4];
    float mx[2][2];
#pragma unroll
    for (int m = 0; m < 2; m++) {
        mx[m][0] = -INFINITY; mx[m][1] = -INFINITY;
#pragma unroll
        for (int n = 0; n < 3; n++)
#pragma unroll
            for (int i = 0; i < 4; i++) o[m][n][i] = 0.f;
    }
    const int tfirst = max(0, (256 - q0) / 16 - 2 * wq);
    const uint32_t kb0 = sK + (wq * 32 + l7 + (l3 >> 1) * 8) * 48 + (l3 & 1) * 16;
    const uint32_t kb1 = sK + (wq * 32 + l7 + (l3 & 1) * 8) * 48 + 32;
    const uint32_t vb0 = sV + (wq * 32 + l7 + (l3 & 1) * 8) * 48 + (l3 >> 1) * 16;
    const uint32_t vb1 = sV + (wq * 32 + l7 + (l3 & 1) * 8) * 48 + 32;
    constexpr int CH = 3;
    auto chunk = [&](auto mode, int c0) {
        constexpr int MODE = decltype(mode)::value;
        auto dead = [](int m, int u) { return (MODE == 0 && m == 0 && u == 2) || (MODE == 2 && m == 1 && u == 0); };
        float sc[2][CH][2][4];
#pragma unroll
        for (int u = 0; u < CH; u++) {
            uint32_t kf[4], kg[2];
            const int ti = MODE == 3 ? max(c0 + u, tfirst) : c0 + u;
            ldsm4(kf, kb0 + ti * 768); ldsm2(kg, kb1 + ti * 768);
#pragma unroll
            for (int m = 0; m < 2; m++) {
                if (dead(m, u)) continue;
#pragma unroll
                for (int n = 0; n < 2; n++) {
#pragma unroll
                    for (int i = 0; i < 4; i++) sc[m][u][n][i] = 0.f;
                    mma16(sc[m][u][n], qa[m], kf[2 * n], kf[2 * n + 1]);
                    mma8(sc[m][u][n], qb[m][0], qb[m][1], kg[n]);
                }
            }
        }
#pragma unroll
        for (int m = 0; m < 2; m++)
#pragma unroll
            for (int u = 0; u < CH; u++)
#pragma unroll
                for (int n = 0; n < 2; n++)
#pragma unroll
                    for (int i = 0; i < 4; i++) {
                        const int dl = g + (i >> 1) * 8 - (n * 8 + 2 * t + (i & 1));
                        if (MODE == 0 && u == m + 1 && dl < 0) sc[m][u][n][i] = -INFINITY;
                        if (MODE == 2 && u == m && dl >= 0) sc[m][u][n][i] = -INFINITY;
                        if (MODE == 3) {
                            const int d = 256 + (m - c0 - u) * 16 + dl;
                            if (d < 0 || d >= 256 || c0 + u < tfirst) sc[m][u][n][i] = -INFINITY;
                        }
                    }
        float bs[2][2];
#pragma unroll
        for (int m = 0; m < 2; m++) {
            float n0 = mx[m][0], n1 = mx[m][1];
#pragma unroll
            for (int u = 0; u < CH; u++) {
                if (dead(m, u)) continue;
#pragma unroll
                for (int n = 0; n < 2; n++) {
                    n0 = fmaxf(n0, fmaxf(sc[m][u][n][0], sc[m][u][n][1])); n1 = fmaxf(n1, fmaxf(sc[m][u][n][2], sc[m][u][n][3]));
                }
            }
            n0 = fmaxf(n0, __shfl_xor_sync(0xffffffffu, n0, 1)); n1 = fmaxf(n1, __shfl_xor_sync(0xffffffffu, n1, 1));
            n0 = fmaxf(n0, __shfl_xor_sync(0xffffffffu, n0, 2)); n1 = fmaxf(n1, __shfl_xor_sync(0xffffffffu, n1, 2));
            if (MODE != 0) {
                const float f0 = ex2((mx[m][0] - n0) * SC), f1 = ex2((mx[m][1] - n1) * SC);
#pragma unroll
                for (int n = 0; n < 3; n++) { o[m][n][0] *= f0; o[m][n][1] *= f0; o[m][n][2] *= f1; o[m][n][3] *= f1; }
            }
            mx[m][0] = n0; mx[m][1] = n1;
            bs[m][0] = n0 * SC; bs[m][1] = n1 * SC;
        }
#pragma unroll
        for (int u = 0; u < CH; u++) {
            uint32_t vf[4], vg[2];
            const int ti = MODE == 3 ? max(c0 + u, tfirst) : c0 + u;
            ldsm4t(vf, vb0 + ti * 768); ldsm2t(vg, vb1 + ti * 768);
            if (one0) { vf[0] = 0x3f803f80u; vf[1] = 0x3f803f80u; }
            if (one2) { vg[0] = 0x3f803f80u; vg[1] = 0x3f803f80u; }
#pragma unroll
            for (int m = 0; m < 2; m++) {
                if (dead(m, u)) continue;
                uint32_t pa[4];
#pragma unroll
                for (int n = 0; n < 2; n++) {
                    pa[2 * n] = pack2(ex2(fmaf(sc[m][u][n][0], SC, -bs[m][0])), ex2(fmaf(sc[m][u][n][1], SC, -bs[m][0])));
                    pa[2 * n + 1] = pack2(ex2(fmaf(sc[m][u][n][2], SC, -bs[m][1])), ex2(fmaf(sc[m][u][n][3], SC, -bs[m][1])));
                }
                mma16(o[m][0], pa, vf[0], vf[1]); mma16(o[m][1], pa, vf[2], vf[3]); mma16(o[m][2], pa, vg[0], vg[1]);
            }
        }
    };
    if (tfirst == 0) {
        chunk(IC<0>{}, 15);
#pragma unroll 1
        for (int c0 = 12; c0 > 0; c0 -= CH) chunk(IC<1>{}, c0);
        chunk(IC<2>{}, 0);
    } else {
#pragma unroll 1
        for (int c0 = 15; c0 >= 0 && c0 + CH > tfirst; c0 -= CH) chunk(IC<3>{}, c0);
    }
    __syncwarp();
    if (lane == 0) mbar_arrive(rel);
#pragma unroll
    for (int m = 0; m < 2; m++) {
        const int src = sh == 6 ? (lane & ~3) : (lane | 3);
        const float s0 = __shfl_sync(0xffffffffu, sh == 6 ? o[m][0][0] : o[m][2][1], src);
        const float s1 = __shfl_sync(0xffffffffu, sh == 6 ? o[m][0][2] : o[m][2][3], src);
        const int r = q0 + wq * 32 + m * 16 + g;
        const float i0 = (1.f - gt[m][0]) * rcp_fast(s0), i1 = (1.f - gt[m][1]) * rcp_fast(s1);
        bf16* op = g_O + (size_t)r * OK + HD + hh * BD + 2 * t - sh;
#pragma unroll
        for (int n = 0; n < 3; n++) {
            const int col = n * 8 + 2 * t;
            if (col >= sh && col < sh + 18) {
                *reinterpret_cast<uint32_t*>(op + n * 8) = pack2(o[m][n][0] * i0, o[m][n][1] * i0);
                *reinterpret_cast<uint32_t*>(op + n * 8 + 8 * OK) = pack2(o[m][n][2] * i1, o[m][n][3] * i1);
            }
        }
    }
}

template <int BN>
__device__ __forceinline__ void gemm_unit(int ty, const uint32_t* d, uint32_t sb, uint32_t bF, uint32_t bE, int& sg, int& ph,
                                          int warp, int lane, bf16* __restrict__ out) {
    const int wg = warp >> 2, wq = warp & 3, g = lane >> 2, t = lane & 3;
    auto release = [&](int q) { __syncwarp(); if (lane == 0) mbar_arrive(bE + 8 * q); };
    const int n0 = d[2] * BN, kb0 = d[3] & 255, kb1 = d[3] >> 8;
    const int rb = (ty == T_G0 ? d[1] * 192 : f_row0(d[1])) + (BN == 64 ? wq : warp) * 16, r0 = rb + g;
    float g0 = 1.f, g1 = 1.f;
    if (ty != T_G0) { g0 = __ldcg(g_gate + r0); g1 = __ldcg(g_gate + r0 + 8); }
    if (ty != T_G0 && f_split(d[1]) > 1) {
        const float* pa = g_acc + (size_t)rb * DM + n0 * 16 + lane * 32;
#pragma unroll
        for (int i = 0; i < (BN + 63) / 64; i++) if (i * 64 + lane * 2 < BN) asm volatile("prefetch.global.L2 [%0];" ::"l"(pa + i * 1024));
    }
    float acc[BN / 2];
#pragma unroll
    for (int i = 0; i < BN / 2; i++) acc[i] = 0.f;
    int prev = -1;
    constexpr int KPS = BN == 64 ? 3 : 1;
    for (int kb = kb0; kb < kb1;) {
        if (kb > kb0) mbar_wait(bF + 8 * sg, ph);
        for (int j = 0; j < KPS && kb < kb1; j++, kb++) {
            const uint32_t a = sb + sg * H_STAGE + (BN == 64 ? j * 16384 : wg * 8192), b = BN == 64 ? a + 8192 : sb + sg * H_STAGE + 24576;
            if (kb == 64 && kb0 < 64) {
                wg_wait<0>();
#pragma unroll
                for (int i = 0; i < BN / 8; i++) { acc[4 * i] *= g0; acc[4 * i + 1] *= g0; acc[4 * i + 2] *= g1; acc[4 * i + 3] *= g1; }
            }
            const uint64_t da = desc_sw128(a, 16, 1024), db = desc_sw128(b, 8192, 1024);
            wg_fence();
#pragma unroll
            for (int k = 0; k < 4; k++) {
                if (BN == 192) wgmma_ss_n192(acc, da + (uint64_t)(k * 2), db + (uint64_t)(k * 128), 1);
                else if (BN == 96) wgmma_ss_n96(acc, da + (uint64_t)(k * 2), db + (uint64_t)(k * 128));
                else wgmma_ss_n64(acc, da + (uint64_t)(k * 2), db + (uint64_t)(k * 128));
            }
            wg_commit();
            wg_wait<1>();
            if (j == 0 && prev >= 0) release(prev);
        }
        prev = sg;
        if (++sg == H_STAGES) { sg = 0; ph ^= 1; }
    }
    wg_wait<0>();
    if (ty == T_G0) {
        release(prev);
        store_tile<BN>(acc, g_qkvB + (size_t)r0 * (3 * DM) + n0, 3 * DM, t);
        signal(g_ctr + C_G0 + d[1], lane);
        return;
    }
    if (kb1 <= 64) {
#pragma unroll
        for (int i = 0; i < BN / 8; i++) { acc[4 * i] *= g0; acc[4 * i + 1] *= g0; acc[4 * i + 2] *= g1; acc[4 * i + 3] *= g1; }
    }
    const int ks = f_split(d[1]);
    bool fin = true;
    if (ks == 1) release(prev);
    if (ks > 1) {
        float4* ga = reinterpret_cast<float4*>(g_acc + (size_t)rb * DM + n0 * 16) + lane;
#pragma unroll
        for (int i = 0; i < BN / 8; i++) red4(reinterpret_cast<float*>(ga + i * 32), acc[4 * i], acc[4 * i + 1], acc[4 * i + 2], acc[4 * i + 3]);
        release(prev);
        unsigned old = 0;
        if (lane == 0) asm volatile("atom.acq_rel.gpu.global.add.u32 %0,[%1],1;" : "=r"(old) : "l"(g_ctr + C_F + (d[1] * 9 + d[2]) * 12 + warp) : "memory");
        old = __shfl_sync(0xffffffffu, old, 0);
        fin = (old == (unsigned)ks - 1);
        if (fin) {
#pragma unroll
            for (int i = 0; i < BN / 8; i++) {
                const float4 u = __ldcg(ga + i * 32);
                acc[4 * i] = u.x; acc[4 * i + 1] = u.y; acc[4 * i + 2] = u.z; acc[4 * i + 3] = u.w;
            }
        }
    }
    if (fin) store_tile<BN>(acc, out + (size_t)r0 * DM + n0, DM, t);
}

struct HelpMaps { CUtensorMap x, wqkv, O, O128, O64, Wo, wo, qkv; };

__global__ void __launch_bounds__(512, 1) k_help(const __grid_constant__ HelpMaps tm, const bf16* __restrict__ x,
                                                  const bf16* __restrict__ gw, bf16* __restrict__ out) {
    extern __shared__ uint8_t smem_raw[];
    const uint32_t sb = (s2u(smem_raw) + 1023) & ~1023u;
    const uint32_t bF = sb + H_STAGES * H_STAGE, bE = bF + 8 * H_STAGES, dsc = bF + 128;
    const int tid = threadIdx.x, warp = __shfl_sync(0xffffffffu, tid >> 5, 0), lane = tid & 31;
    if (lane == 0 && warp >= 1 && warp <= (int)(sizeof(HelpMaps) / sizeof(CUtensorMap)))
        asm volatile("prefetch.tensormap [%0];" ::"l"(&tm.x + (warp - 1)) : "memory");
    if (tid == 0) {
        for (int i = 0; i < H_STAGES; i++) { mbar_init(bF + 8 * i, 1); mbar_init(bE + 8 * i, 12); }
        asm volatile("fence.mbarrier_init.release.cluster;" ::: "memory");
    }
    __syncthreads();
    if (warp >= 12) {
        asm volatile("setmaxnreg.dec.sync.aligned.u32 56;");
        if (warp != 12) {
            while (true) {
                unsigned u = 0;
                if (lane == 0) u = atomicAdd(g_ctr + C_HG, 1);
                u = __shfl_sync(0xffffffffu, u, 0);
                if (u >= SEQ / 16) return;
#pragma unroll 1
                for (int r0 = u * 16; r0 < u * 16 + 16; r0 += 2) {
                    float a0 = 0.f, a1 = 0.f;
                    const __nv_bfloat162* xr = reinterpret_cast<const __nv_bfloat162*>(x + (size_t)r0 * DM);
#pragma unroll
                    for (int i = 0; i < 9; i++) {
                        const float2 b = __bfloat1622float2(reinterpret_cast<const __nv_bfloat162*>(gw)[lane + 32 * i]);
                        const float2 y = __bfloat1622float2(xr[lane + 32 * i]), z = __bfloat1622float2(xr[DM / 2 + lane + 32 * i]);
                        a0 += y.x * b.x + y.y * b.y; a1 += z.x * b.x + z.y * b.y;
                    }
#pragma unroll
                    for (int o = 16; o; o >>= 1) { a0 += __shfl_xor_sync(0xffffffffu, a0, o); a1 += __shfl_xor_sync(0xffffffffu, a1, o); }
                    if (lane < 2) g_gate[r0 + lane] = 1.f / (1.f + __expf(-(lane ? a1 : a0)));
                }
                signal(g_ctr + C_GATE, lane);
            }
        }
        int sg = 0, ph = 1;
        auto next = [&](int ty, int a, int b, int c2) {
            mbar_wait(bE + 8 * sg, ph);
            if (lane == 0) asm volatile("st.shared.v4.u32 [%0],{%1,%2,%3,%4};" ::"r"(dsc + 16 * sg), "r"(ty), "r"(a), "r"(b), "r"(c2) : "memory");
        };
        auto adv = [&]() { __syncwarp(); if (++sg == H_STAGES) { sg = 0; ph ^= 1; } };
        auto acquire = [&]() { asm volatile("fence.acq_rel.gpu; fence.proxy.async.global;" ::: "memory"); };
        auto ticket = [&](unsigned* q) { unsigned u = 0; if (lane == 0) u = atomicAdd(q, 1); return __shfl_sync(0xffffffffu, u, 0); };
        auto gemm = [&](int ty, int m, int n, int kb0, int kb1) {
            for (int kb = kb0; kb < kb1; kb++) {
                next(ty, m, n, kb0 | (kb1 << 8));
                if (lane == 0) {
                    const uint32_t a = sb + sg * H_STAGE, b = a + 24576, bar = bF + 8 * sg;
                    const bool half = ty != T_G0 && m >= 9;
                    mbar_expect(bar, (ty == T_FN ? 40960 : 49152) - (half ? 8192 : 0));
                    tma2d(a, ty == T_G0 ? &tm.x : (half ? &tm.O128 : &tm.O), kb * 64, ty == T_G0 ? m * 192 : f_row0(m), bar);
                    const CUtensorMap* mb = ty == T_G0 ? &tm.wqkv : (kb >= 64 ? &tm.wo : &tm.Wo);
                    const int kr = (kb >= 64 ? kb - 64 : kb) * 64;
                    if (ty == T_FN) for (int j = 0; j < 2; j++) tma2d(b + j * 8192, mb, n * 96 + j * 64, kr, bar);
                    else for (int j = 0; j < 3; j++) tma2d(b + j * 8192, mb, n * 192 + j * 64, kr, bar);
                }
                adv();
            }
        };
        bool bdone = false;
        int idle = 0, rr = 0;
        const int fl = min(lane, 10);
        constexpr int NLATE = (NSEG - AA_LATE) * 6, NSMALL = 9 * f_split(11);
        auto attn_a = [&](int as, int u) {
            const int per = (15 + aa_units(as)) / aa_units(as), ns = min(per, 16 - u * per), h0 = u * per * 2;
            for (int i = 0; i < ns; i++) {
                next(T_AA, as, h0 + 2 * i, rr | (i + 3 >= ns ? 4 : 0)); rr = rr == 2 ? 0 : rr + 1;
                if (lane == 0) {
                    const uint32_t a = sb + sg * H_STAGE, bar = bF + 8 * sg;
                    mbar_expect(bar, 57344);
                    bulk_load(a, reinterpret_cast<uint8_t*>(g_xr) + (size_t)(as * 32 + h0 + 2 * i) * 24576, 49152, bar);
                    bulk_load(a + 49152, reinterpret_cast<uint8_t*>(g_mr) + (size_t)(as * 32 + h0 + 2 * i) * 4096, 8192, bar);
                }
                adv();
            }
        };
        auto spin_ge = [&](const unsigned* q, unsigned target) {
            int it = 0;
            while (ld_acq(q) < target) { __nanosleep(SPIN_NS); if (++it > (1 << 22)) __trap(); }
        };
        auto drain = [&]() {
            const int ls = sg == 0 ? H_STAGES - 1 : sg - 1;
            mbar_wait(bE + 8 * ls, sg == 0 ? ph : ph ^ 1);
        };
        while (true) {
            const unsigned tk0 = ld_relaxed1(g_ctr + C_HAA + lane), tk1 = ld_relaxed1(g_ctr + C_HAA + 32 + lane);
            const unsigned f0 = ld_relaxed1(g_flagA + lane), f1 = ld_relaxed1(g_flagA + 32 + lane);
            const unsigned tkf = ld_relaxed1(g_ctr + C_HF + min(lane, 12)), ca = ld_relaxed1(g_ctr + C_AA + fl);
            const unsigned cb0 = ld_relaxed1(g_ctr + C_AB + (lane > 10 ? 15 : f_row0(fl) / 128));
            const unsigned cb1 = ld_relaxed1(g_ctr + C_AB + (lane > 10 ? 15 : (f_row0(fl) + f_rows(fl) - 1) / 128));
            const bool e0 = tk0 < (unsigned)aa_units(lane), e1 = 32 + lane < AA_LATE && tk1 < (unsigned)aa_units(32 + lane);
            const unsigned a0 = __ballot_sync(0xffffffffu, e0 && f0 >= 96), a1 = __ballot_sync(0xffffffffu, e1 && f1 >= 96);
            const bool early_left = __any_sync(0xffffffffu, e0 || e1);
            const unsigned tl = __shfl_sync(0xffffffffu, tkf, 11), ts = __shfl_sync(0xffffffffu, tkf, 12);
            const bool fleft = lane < 11 && tkf < (unsigned)(f_ntiles(fl) * f_split(fl));
            const unsigned fl_m = __ballot_sync(0xffffffffu, fleft);
            const bool may = blockIdx.x >= (fl >= AA_B3 ? AA_CTAS3 : (fl >= 6 ? AA_CTAS2 : AA_CTAS)) || tl >= NLATE;
            const unsigned fr = __ballot_sync(0xffffffffu, fleft && ca >= (unsigned)(2 * f_rows(fl)) && cb0 >= 128 && cb1 >= 128 && may);
            if (a0 | a1) {
                const int as = a0 ? __ffs(a0) - 1 : 31 + __ffs(a1);
                const unsigned u = ticket(g_ctr + C_HAA + as);
                if (u < (unsigned)aa_units(as)) { acquire(); attn_a(as, u); continue; }
            }
            if (tl < NLATE && !early_left) {
                const bool ready = __shfl_sync(0xffffffffu, f1, (AA_LATE - 32 + tl / 6) & 31) >= 96;
                if (ready || (blockIdx.x < AA_CTAS3 && bdone)) {
                    drain();
                    const unsigned u = ticket(g_ctr + C_HF + 11);
                    if (u < NLATE) { spin_ge(g_flagA + AA_LATE + u / 6, 96); attn_a(AA_LATE + u / 6, u % 6); drain(); continue; }
                }
            }
            if (fr) {
                const int fm = __ffs(fr) - 1;
                const unsigned u = ticket(g_ctr + C_HF + fm);
                const int ks = f_split(fm), nt = f_ntiles(fm);
                if (u < (unsigned)(nt * ks)) {
                    const int kp = u / nt;
                    acquire();
                    gemm(nt == 3 ? T_F : T_FN, fm, u % nt, kp * 73 / ks, (kp + 1) * 73 / ks);
                    if (fm >= DRAIN_B) drain();
                    continue;
                }
            }
            if (ts < NSMALL && tl >= NLATE && __shfl_sync(0xffffffffu, cb0 >= 128, 11)) {
                const unsigned u = ticket(g_ctr + C_HF + 12);
                if (u < NSMALL) {
                    acquire();
                    const int fm = 11, v = u;
                    const int nn = v % 9, kp = v / 9, kb0 = kp * 73 / f_split(fm), kb1 = (kp + 1) * 73 / f_split(fm);
                    for (int k0 = kb0; k0 < kb1; k0 += 3 * H_STAGES) {
                        const int sg0 = sg, k1 = min(kb1, k0 + 3 * H_STAGES);
                        for (int kb = k0; kb < k1; kb += 3) {
                            next(T_FS, fm, nn, kb0 | (kb1 << 8));
                            const int kk = kb + lane;
                            if (lane == 0) mbar_expect(bF + 8 * sg, min(3, k1 - kb) * 16384);
                            __syncwarp();
                            if (lane < 3 && kk < k1) {
                                tma2d(sb + sg * H_STAGE + lane * 16384 + 8192, kk >= 64 ? &tm.wo : &tm.Wo, nn * 64, (kk >= 64 ? kk - 64 : kk) * 64, bF + 8 * sg);
                                if (k0 > kb0) tma2d(sb + sg * H_STAGE + lane * 16384, &tm.O64, kk * 64, f_row0(fm), bF + 8 * sg);
                            }
                            adv();
                        }
                        if (k0 == kb0) {
                            spin_ge(g_ctr + C_AA + fm, 128);
                            if (k0 + lane < k1) {
                                const int q = (sg0 + lane / 3) % H_STAGES;
                                tma2d(sb + q * H_STAGE + (lane % 3) * 16384, &tm.O64, (k0 + lane) * 64, f_row0(fm), bF + 8 * q);
                            }
                            __syncwarp();
                        }
                    }
                    drain();
                    continue;
                }
            }
            if (a0 | a1 | fr) continue;
            if (!bdone) {
                const unsigned u = ticket(g_ctr + C_HB);
                if (u < NG0) {
                    gemm(T_G0, u / 9, u % 9, 0, 9);
                } else if (u < NB_UNITS) {
                    const int m = (u - NG0) / ABT, h0 = ((u - NG0) % ABT) * ABH, h1 = min(h0 + ABH, BH);
                    const int mm = min(max(0, m * 128 - 256) / 192 + lane, (m * 128 + 127) / 192);
                    const unsigned* q = lane == 31 ? g_ctr + C_GATE : g_ctr + C_G0 + mm;
                    int it = 0;
                    while (!__all_sync(0xffffffffu, ld_relaxed1(q) >= (lane == 31 ? 128u : 108u))) { __nanosleep(100); if (++it > (1 << 22)) __trap(); }
                    acquire();
                    for (int hh = h0; hh < h1; hh++) {
                        next(T_AB, m, hh, rr | (hh + 3 >= h1 ? 4 : 0)); rr = rr == 2 ? 0 : rr + 1;
                        if (lane == 0) {
                            const uint32_t a = sb + sg * H_STAGE, bar = bF + 8 * sg;
                            const int col = (hh >> 2) * 72 + (hh & 3) * 16;
                            mbar_expect(bar, 7 * 6144);
                            tma2d(a, &tm.qkv, col, m * 128, bar);
                            for (int j = 0; j < 3; j++) {
                                tma2d(a + (1 + j) * 6144, &tm.qkv, DM + col, (m - 2 + j) * 128, bar);
                                tma2d(a + (4 + j) * 6144, &tm.qkv, 2 * DM + col, (m - 2 + j) * 128, bar);
                            }
                        }
                        adv();
                    }
                } else bdone = true;
                continue;
            }
            if (fl_m == 0 && ts >= NSMALL) break;
            __nanosleep(150);
            if (++idle > (1 << 22)) __trap();
        }
        next(T_EXIT, 0, 0, 0);
        if (lane == 0) mbar_arrive(bF + 8 * sg);
    } else {
        asm volatile("setmaxnreg.inc.sync.aligned.u32 152;");
        const int wg = warp >> 2, wq = warp & 3;
        int sg = 0, ph = 0, skip = 0;
        unsigned pend = 0;
        auto release = [&](int q) { __syncwarp(); if (lane == 0) mbar_arrive(bE + 8 * q); };
        auto adv = [&]() { if (++sg == H_STAGES) { sg = 0; ph ^= 1; } };
        while (true) {
            mbar_wait(bF + 8 * sg, ph);
            uint32_t d[4];
            lds128(d, dsc + 16 * sg);
            const int ty = d[0];
            if (ty == T_EXIT) break;
            if ((ty == T_G0 && wg == 2 && d[1] == NBLK - 1) || ((ty == T_F || ty == T_FN) && wg == 2 && d[1] >= 9) || (ty == T_FS && wg != 0)) {
                release(sg); adv();
                if (ty == T_G0 && ++skip == 9) { skip = 0; signal(g_ctr + C_G0 + d[1], lane); }
            } else if (ty == T_G0 || ty == T_F) {
                gemm_unit<192>(ty, d, sb, bF, bE, sg, ph, warp, lane, out);
            } else if (ty == T_FN) {
                gemm_unit<96>(ty, d, sb, bF, bE, sg, ph, warp, lane, out);
            } else if (ty == T_FS) {
                gemm_unit<64>(ty, d, sb, bF, bE, sg, ph, warp, lane, out);
                if (tid == 0 && d[1] == NFB - 1) g_sync[0] = 0;
            } else {
                if ((int)(d[3] & 3) == wg) {
                    if (ty == T_AA) {
                        const uint32_t xr = sb + sg * H_STAGE + (wq >> 1) * 24576, mr = sb + sg * H_STAGE + 49152 + (wq >> 1) * 4096;
                        if ((wq + wg) & 1) attnA_unit<1>(xr, mr, d[1], d[2] + (wq >> 1), lane, bE + 8 * sg);
                        else attnA_unit<0>(xr, mr, d[1], d[2] + (wq >> 1), lane, bE + 8 * sg);
                        pend++;
                        if (d[1] >= 62) asm volatile("fence.proxy.async.global;" ::: "memory");
                        if (d[3] & 4) { signal(g_ctr + C_AA + f_blk(d[1]), lane, pend); pend = 0; }
                    } else {
                        attnB_unit(sb + sg * H_STAGE, d[1] * 128, d[2], wq, lane, bE + 8 * sg);
                        pend++;
                        if (d[3] & 4) { signal(g_ctr + C_AB + d[1], lane, pend); pend = 0; }
                    }
                } else {
                    release(sg);
                }
                adv();
            }
        }
    }
}

__device__ float g_fmem[(NSEG + 1) * 8 * DM];
__device__ bf16 g_fq[8 * HD];
__device__ __forceinline__ int tile_off(int row, int e) { return row * 16 + ((((e >> 3) ^ (row >> 2)) & 1) << 3) + (e & 7); }

__global__ void fb_init(const bf16* __restrict__ mem0) {
    const int i = blockIdx.x * blockDim.x + threadIdx.x;
    if (i < (NSEG + 1) * 8 * DM) g_fmem[i] = i < 8 * DM ? __bfloat162float(mem0[i]) : 0.f;
    if (i < SEQ * DM) g_acc[i] = 0.f;
    if (i < 1920) g_ctr[i] = 0;
    if (i < NSEG) g_flagA[i] = 96;
}
__global__ void fb_proj(const bf16* __restrict__ x, const bf16* __restrict__ Wq, const bf16* __restrict__ Wk, const bf16* __restrict__ Wv, int seg) {
    __shared__ float in[8][DM];
    for (int i = threadIdx.x; i < 8 * DM; i += blockDim.x)
        in[i / DM][i % DM] = seg >= 0 ? __bfloat162float(__float2bfloat16(g_fmem[seg * 8 * DM + i])) : __bfloat162float(x[(size_t)blockIdx.y * 8 * DM + i]);
    __syncthreads();
    const int col = blockIdx.x * blockDim.x + threadIdx.x, ty = col / HD, hc = col % HD, h = hc / DH, d = (hc % DH) >> 4, e = hc & 15;
    const bf16* W = (ty == 0 ? Wq : (ty == 1 ? Wk : Wv)) + hc;
    float a[8] = {0.f, 0.f, 0.f, 0.f, 0.f, 0.f, 0.f, 0.f};
    for (int k = 0; k < DM; k++) {
        const float w = __bfloat162float(W[(size_t)k * HD]);
#pragma unroll
        for (int r = 0; r < 8; r++) a[r] += in[r][k] * w;
    }
    for (int r = 0; r < 8; r++) {
        const bf16 v = __float2bfloat16(a[r]);
        if (seg < 0) {
            const int pos = ty == 0 ? pos_q(d) : (ty == 1 ? pos_k(d) : pos_v(d));
            reinterpret_cast<bf16*>(g_xr)[((size_t)((blockIdx.y >> 2) * 32 + h) * 24 + pos) * 512 + tile_off((blockIdx.y & 3) * 8 + r, e)] = v;
        } else if (ty == 0) g_fq[r * HD + hc] = v;
        else reinterpret_cast<bf16*>(g_mr)[((size_t)(seg * 32 + h) * 16 + (ty == 1 ? mpos_k(d) : mpos_v(d))) * 128 + tile_off(r, e)] = v;
    }
}
__global__ void fb_attn(const bf16* __restrict__ Wo, int seg) {
    __shared__ float sc[8][40], o[8][DH];
    const int h = blockIdx.x, tid = threadIdx.x;
    const bf16* xr = reinterpret_cast<const bf16*>(g_xr) + (size_t)(seg * 32 + h) * 24 * 512;
    const bf16* mr = reinterpret_cast<const bf16*>(g_mr) + (size_t)(seg * 32 + h) * 16 * 128;
    {
        const int r = tid / 40, j = tid % 40;
        float a = 0.f;
        for (int c = 0; c < DH; c++) {
            const bf16 kv = j < 8 ? mr[mpos_k(c >> 4) * 128 + tile_off(j, c & 15)] : xr[pos_k(c >> 4) * 512 + tile_off(j - 8, c & 15)];
            a += __bfloat162float(g_fq[r * HD + h * DH + c]) * __bfloat162float(kv);
        }
        sc[r][j] = a * 0.08838834764831845f;
    }
    __syncthreads();
    if (tid < 8) {
        float m = sc[tid][0], z = 0.f;
        for (int j = 1; j < 40; j++) m = fmaxf(m, sc[tid][j]);
        for (int j = 0; j < 40; j++) { sc[tid][j] = __expf(sc[tid][j] - m); z += sc[tid][j]; }
        for (int j = 0; j < 40; j++) sc[tid][j] /= z;
    }
    __syncthreads();
    for (int i = tid; i < 8 * DH; i += 320) {
        const int r = i / DH, c = i % DH;
        float a = 0.f;
        for (int j = 0; j < 40; j++)
            a += sc[r][j] * __bfloat162float(j < 8 ? mr[mpos_v(c >> 4) * 128 + tile_off(j, c & 15)] : xr[pos_v(c >> 4) * 512 + tile_off(j - 8, c & 15)]);
        o[r][c] = __bfloat162float(__float2bfloat16(a));
    }
    __syncthreads();
    for (int n = tid; n < DM; n += 320) {
        float a[8] = {0.f, 0.f, 0.f, 0.f, 0.f, 0.f, 0.f, 0.f};
        for (int c = 0; c < DH; c++) {
            const float w = __bfloat162float(Wo[(size_t)(h * DH + c) * DM + n]);
#pragma unroll
            for (int r = 0; r < 8; r++) a[r] += o[r][c] * w;
        }
        for (int r = 0; r < 8; r++) atomicAdd(g_fmem + ((seg + 1) * 8 + r) * DM + n, a[r]);
    }
}

typedef CUresult (*EncodeFn)(CUtensorMap*, CUtensorMapDataType, cuuint32_t, void*, const cuuint64_t*, const cuuint64_t*,
                             const cuuint32_t*, const cuuint32_t*, CUtensorMapInterleave, CUtensorMapSwizzle,
                             CUtensorMapL2promotion, CUtensorMapFloatOOBfill);

static void make_map(EncodeFn fn, CUtensorMap* m, const void* ptr, uint64_t cols, uint64_t rows, uint32_t bc, uint32_t br,
                     CUtensorMapSwizzle sw = CU_TENSOR_MAP_SWIZZLE_128B, bool promote = false) {
    cuuint64_t dims[2] = {cols, rows};
    cuuint64_t strides[1] = {cols * 2};
    cuuint32_t box[2] = {bc, br};
    cuuint32_t es[2] = {1, 1};
    fn(m, CU_TENSOR_MAP_DATA_TYPE_BFLOAT16, 2, const_cast<void*>(ptr), dims, strides, box, es, CU_TENSOR_MAP_INTERLEAVE_NONE,
       sw, sw == CU_TENSOR_MAP_SWIZZLE_NONE && !promote ? CU_TENSOR_MAP_L2_PROMOTION_NONE : CU_TENSOR_MAP_L2_PROMOTION_L2_256B, CU_TENSOR_MAP_FLOAT_OOB_FILL_NONE);
}

extern "C" void kernel_launch(void* const* d_in, const int* in_sizes, int n_in, void* d_out, int out_size) {
    const bf16* x = (const bf16*)d_in[0];
    const bf16* mem0 = (const bf16*)d_in[1];
    const bf16* Wq = (const bf16*)d_in[2];
    const bf16* Wk = (const bf16*)d_in[3];
    const bf16* Wv = (const bf16*)d_in[4];
    const bf16* Wo = (const bf16*)d_in[5];
    const bf16* wqkv = (const bf16*)d_in[8];
    const bf16* wo = (const bf16*)d_in[9];
    const bf16* gw = (const bf16*)d_in[10];
    bf16* out = (bf16*)d_out;

    void* fp = nullptr;
    cudaDriverEntryPointQueryResult qr;
    cudaGetDriverEntryPoint("cuTensorMapEncodeTiled", &fp, cudaEnableDefault, &qr);
    EncodeFn enc = (EncodeFn)fp;
    void* pO = nullptr;
    cudaGetSymbolAddress(&pO, g_O);
    CUtensorMap tx32;
    HelpMaps hm;
    RecMaps rm;
    for (int r = 0; r < 2; r++) {
        make_map(enc, &rm.w[r][0], Wq, HD, DM, r ? 32 : 48, 144, CU_TENSOR_MAP_SWIZZLE_NONE, true);
        make_map(enc, &rm.w[r][1], Wk, HD, DM, r ? 32 : 48, 144, CU_TENSOR_MAP_SWIZZLE_NONE, true);
        make_map(enc, &rm.w[r][2], Wv, HD, DM, r ? 64 : 32, 144, CU_TENSOR_MAP_SWIZZLE_NONE, true);
    }
    make_map(enc, &rm.wo, Wo, DM, HD, 192, 128, CU_TENSOR_MAP_SWIZZLE_NONE, true);
    make_map(enc, &tx32, x, DM, SEQ, 64, 32);
    make_map(enc, &hm.x, x, DM, SEQ, 64, 192);
    make_map(enc, &hm.wqkv, wqkv, 3 * DM, DM, 64, 64);
    make_map(enc, &hm.O, pO, OK, SEQ, 64, 192);
    make_map(enc, &hm.O128, pO, OK, SEQ, 64, 128);
    make_map(enc, &hm.O64, pO, OK, SEQ, 64, 64);
    make_map(enc, &hm.Wo, Wo, DM, HD, 64, 64);
    make_map(enc, &hm.wo, wo, DM, DM, 64, 64);
    void* pQ = nullptr;
    cudaGetSymbolAddress(&pQ, g_qkvB);
    make_map(enc, &hm.qkv, pQ, 3 * DM, SEQ, 24, 128, CU_TENSOR_MAP_SWIZZLE_NONE);
    cudaFuncSetAttribute(k_rec, cudaFuncAttributeMaxDynamicSharedMemorySize, REC_SMEM);
    cudaFuncSetAttribute(k_help, cudaFuncAttributeMaxDynamicSharedMemorySize, HELP_SMEM);

    cudaStream_t st = cudaStreamPerThread;
    bool fast;
    int nsm = 132;
    cudaDeviceGetAttribute(&nsm, cudaDevAttrMultiProcessorCount, 0);
    {
        RecParams p{mem0, Wq, Wk, Wv, 880, 240};
        cudaLaunchConfig_t cfg = {};
        cfg.gridDim = dim3(96); cfg.blockDim = dim3(384); cfg.dynamicSmemBytes = REC_SMEM; cfg.stream = st;
        cudaLaunchAttribute at[1];
        at[0].id = cudaLaunchAttributeClusterDimension;
        at[0].val.clusterDim.x = 3; at[0].val.clusterDim.y = 1; at[0].val.clusterDim.z = 1;
        cfg.attrs = at; cfg.numAttrs = 1;
        int ncl = 0;
        fast = cudaOccupancyMaxActiveClusters(&ncl, k_rec, &cfg) == cudaSuccess && ncl >= NH;
        if (fast) {
            cudaLaunchKernelEx(&cfg, k_rec, tx32, rm, p);
        } else {
            fb_init<<<SEQ * DM / 256, 256, 0, st>>>(mem0);
            fb_proj<<<dim3(3 * HD / 256, SEQ / 8), 256, 0, st>>>(x, Wq, Wk, Wv, -1);
            for (int s = 0; s < NSEG; s++) {
                fb_proj<<<dim3(3 * HD / 128, 1), 128, 0, st>>>(x, Wq, Wk, Wv, s);
                if (s + 1 < NSEG) fb_attn<<<NH, 320, 0, st>>>(Wo, s);
            }
        }
    }
    {
        cudaLaunchConfig_t cfg = {};
        cfg.gridDim = dim3(nsm); cfg.blockDim = dim3(512); cfg.dynamicSmemBytes = HELP_SMEM; cfg.stream = st;
        cudaLaunchAttribute at[1];
        at[0].id = cudaLaunchAttributeProgrammaticStreamSerialization;
        at[0].val.programmaticStreamSerializationAllowed = 1;
        cfg.attrs = at; cfg.numAttrs = fast ? 1 : 0;
        cudaLaunchKernelEx(&cfg, k_help, hm, x, gw, out);
    }
}
```
